```python
import torch

def _softmax(x, axis=-1):
    return torch.softmax(x, dim=axis)
def _gelu(x):
    return torch.nn.functional.gelu(x, approximate="tanh")
def _silu(x):
    return torch.nn.functional.silu(x)
def _sigmoid(x):
    return torch.sigmoid(x)
def _layernorm(x, axis=-1, eps=1e-5):
    m = x.mean(dim=axis, keepdim=True)
    v = x.var(dim=axis, keepdim=True, unbiased=False)
    return (x - m) / torch.sqrt(v + eps)
def _scatter_add(tgt, idx, src, axis=0):
    return tgt.clone().index_add_(axis, idx, src)
def _segment_sum(src, seg, n):
    out = torch.zeros((n,) + src.shape[1:], dtype=src.dtype)
    return out.index_add_(0, seg, src)
def _pad(x, pw):
    flat = tuple(v for pair in reversed(pw) for v in pair)
    return torch.nn.functional.pad(x, flat)

kernel_name = 'sequential_preLN__mha_block_cached__moe_arch_mod__decode'

def setup_inputs():

    _w = (lambda a: (lambda t: t.to(torch.bfloat16) if t.is_floating_point() else t)(torch.as_tensor(a)))
    def _A_setup():
        B, Sq, D = 4, 1, 640
        H, Sk, Dh = 32, 8192, 192
        return {
            "x": _w((lambda *s: torch.randn(*s, dtype=torch.bfloat16) * 0.05)(B, Sq, D)),
            "k_cache": _w((lambda *s: torch.randn(*s, dtype=torch.bfloat16) * 3.2)(B, H, Sk, Dh)),
            "v_cache": _w((lambda *s: torch.randn(*s, dtype=torch.bfloat16) * 0.4)(B, H, Sk, Dh)),
            "wq": _w((lambda *s: torch.randn(*s, dtype=torch.bfloat16) * 3.2)(D, H * Dh) * (D ** -0.5)),
            "wo": _w((lambda *s: torch.randn(*s, dtype=torch.bfloat16) * 0.4)(H * Dh, D) * ((H * Dh) ** -0.5)),
        }
    _A_in = _A_setup()

    def _B_setup():
        B, S, D, F, C = 4, 1, 640, 1536, 1
        return {
            "x": _w((lambda *s: torch.randn(*s, dtype=torch.bfloat16) * 0.05)(B, S, D)),
            "w_r": _w((lambda *s: torch.randn(*s, dtype=torch.bfloat16) * 0.05)(D)),
            "w_gate": _w((lambda *s: torch.randn(*s, dtype=torch.bfloat16) * 0.05)(D, F)),
            "w_up": _w((lambda *s: torch.randn(*s, dtype=torch.bfloat16) * 0.05)(D, F)),
            "w_down": _w((lambda *s: torch.randn(*s, dtype=torch.bfloat16) * 0.05)(F, D)),
        }
    _B_in = _B_setup()

    return {
        "A_x": _A_in["x"],
        "A_k_cache": _A_in["k_cache"],
        "A_v_cache": _A_in["v_cache"],
        "A_wq": _A_in["wq"],
        "A_wo": _A_in["wo"],
        "B_x": _B_in["x"],
        "B_w_r": _B_in["w_r"],
        "B_w_gate": _B_in["w_gate"],
        "B_w_up": _B_in["w_up"],
        "B_w_down": _B_in["w_down"],
    }

def reference(A_x, A_k_cache, A_v_cache, A_wq, A_wo, B_x, B_w_r, B_w_gate, B_w_up, B_w_down):
    def _A_ref(x, k_cache, v_cache, wq, wo):
        B, Sq, D = x.shape
        H, Dh = 32, 192
        q = (lambda x, *d: x.permute(*d))((x @ wq).reshape(B, Sq, H, Dh), 0, 2, 1, 3)
        scores = torch.einsum("bhqd,bhkd->bhqk", q, k_cache) * (Dh ** -0.5)
        p = _softmax(scores, axis=-1)
        o = torch.einsum("bhqk,bhkd->bhqd", p, v_cache)
        return (lambda x, *d: x.permute(*d))(o, 0, 2, 1, 3).reshape(B, Sq, H * Dh) @ wo

    def _B_ref(x, w_r, w_gate, w_up, w_down):
        B, S, D = x.shape
        C = 1
        r = x @ w_r
        idx = torch.argsort(-r, axis=-1)[:, :C]
        idx_e = (lambda x, n, axis: torch.repeat_interleave(x, n, dim=axis))(idx.reshape(B, C, 1), D, axis=2)
        x_sel = (lambda x, i, axis: torch.take_along_dim(x, i, dim=axis))(x, idx_e, axis=1)
        g = _silu(x_sel @ w_gate)
        u = x_sel @ w_up
        y = (g * u) @ w_down
        r_sel = _sigmoid((lambda x, i, axis: torch.take_along_dim(x, i, dim=axis))(r, idx, axis=1))
        y = y * r_sel.reshape(B, C, 1)
        b_off = (torch.arange(B) * S).reshape(B, 1)
        flat_idx = (idx + b_off).reshape(B * C)
        zero = (x * 0.0).reshape(B * S, D)
        upd = _scatter_add(zero, flat_idx, y.reshape(B * C, D), axis=0)
        return x + upd.reshape(B, S, D)

    x = A_x
    h = x + _A_ref(_layernorm(x, axis=-1), A_k_cache, A_v_cache, A_wq, A_wo)
    h2 = h + _B_ref(_layernorm(h, axis=-1), B_w_r, B_w_gate, B_w_up, B_w_down)
    return h2
```

```cpp
#include <cuda_runtime.h>
#include <cuda_bf16.h>
#include <cuda.h>
#include <stdint.h>

namespace {

constexpr int NB = 4, NH = 32, SK = 8192, DH = 192, DM = 640, FF = 1536;
constexpr int NBH = NB * NH;
constexpr int TILE = 64;
constexpr int UPB = SK / TILE;
constexpr int NUNITS = NBH * UPB;
constexpr int TILE_BYTES = TILE * DH * 2;
constexpr int TILE_ROWS = TILE * 3;
constexpr int NCTAS = 132;
constexpr int NQ_CTAS = 128;
constexpr int NE_CTAS = 112;
constexpr int NF_CTAS = 96;
constexpr int NG_CTAS = 80;

#define NWORK 2
#define LAG 2
#define NPOOL 640
#define RED0 116
#define RING 12
#define OREP 2
#define SROW0 124
#define NPROBE 6
#define NEARLY 0
#define VTRIG 300
#define TRIG_NS 4700
#define GPROMO 2
#define GCLK 300
#define K0_DELAY_NS 1700
#define K0_STEP_NS 900
#define WO_GAP_NS 550
#define WO_ROWS 48
#define WEF 2
#define CLEAR_AT_NS 0
#define XTOP 0
#define WQ_GAP 0
#define X_AT_NS 0
#define QNAP 250
#define WO_AT_NS 3600
#define W_AT_NS 2000
#define W_GAP_NS 400
constexpr int NAUX = 8;
constexpr int NTHREADS = (NAUX + NWORK + 2) * 32;
constexpr int SPIN_MAX = 1 << 22;

constexpr int SM_KV = 0;
constexpr int SM_A = SM_KV + NWORK * TILE_BYTES;
constexpr int SM_G = SM_A + 61440;
constexpr int SM_D = SM_G + 40960;
constexpr int SM_WQ = SM_G;
constexpr int SM_X = SM_D + 24576;
constexpr int XPITCH = 648;
constexpr int HPITCH = 1312;
constexpr int SM_RED = SM_X + 5 * HPITCH;
constexpr int FPITCH = 1040;
constexpr int SM_RED2 = SM_RED + 5 * FPITCH;
constexpr int SM_MISC = SM_RED2 + 16 * 48 * 4;
constexpr int BAR_KV = SM_MISC, BAR_WQ = SM_MISC + 32, BAR_W = SM_MISC + 40, SM_SIDE = SM_MISC + 48, BAR_G = SM_MISC + 64;
constexpr int SM_TOTAL = SM_MISC + 128;

struct Params {
    CUtensorMap k, v;
    CUtensorMap wq;
    CUtensorMap wo;
    CUtensorMap wg, wu;
    CUtensorMap wd;
    const __nv_bfloat16 *x, *wr;
    __nv_bfloat16* out;
};

struct Early {
    uint32_t q[96];
    uint32_t umax[UPB];
};
#define LSTRIDE 16
struct State {
    float4 oacc[SROW0][64];
    float2 attn[NB][DM];
    float2 lsum[SROW0][LSTRIDE];
    uint32_t tstart[32];
    uint32_t score[NPOOL][32];
};
constexpr int STATE_V4 = ((sizeof(State) / 32 + NQ_CTAS - 1) / NQ_CTAS) * 2;
static_assert(sizeof(State) % 32 == 0, "State is cleared in whole sectors");
static_assert(sizeof(Early) == 56 * 16, "an Early entry is cleared by 56 threads");
constexpr uint32_t X_O = 0;
constexpr uint32_t X_H = X_O + (NBH - SROW0 + 4 * (OREP - 1)) * 1280;
constexpr uint32_t X_A = X_H + NB * DM * 2;
constexpr uint32_t X_P = X_A + NB * FF * 2;
constexpr uint32_t X_END = X_P + 4096;
static_assert(X_END <= 16 * 4096 && (SROW0 <= NBH - 4 || OREP == 1) && SROW0 >= RED0, "");
struct Scratch {
    unsigned char sided[16][2][4096];
    unsigned work[64];
    unsigned cnt_z[32];
    Early early[NBH];
    State st;
    float4 ring[RING][UPB][64];
};
constexpr size_t PAGE = 2u << 20;
static_assert(sizeof(Scratch) <= PAGE, "scratch must fit one page");
__device__ __align__(128) unsigned char g_raw[2 * PAGE];
__device__ __forceinline__ Scratch* scratch() {
    return reinterpret_cast<Scratch*>((reinterpret_cast<uintptr_t>(g_raw) + PAGE - 1) & ~(uintptr_t)(PAGE - 1));
}
template <typename T> __device__ __forceinline__ T* sided(int side, uint32_t x) {
    const uint32_t pair = (x >> 8) & 15;
    return reinterpret_cast<T*>(&scratch()->sided[pair][(side ^ pair ^ (pair >> 3)) & 1][((x >> 12) << 8) + (x & 255)]);
}
template <typename T> __device__ __forceinline__ T* other_side(T* p) { return reinterpret_cast<T*>(reinterpret_cast<uintptr_t>(p) ^ 4096); }
#define g_early scratch()->early
#define g_st scratch()->st
#define g_ring scratch()->ring
#define g_cnt_z scratch()->cnt_z
#define g_work scratch()->work
#define TS(i)
#define TSW(i)
#define TS2(i)
#define TSI(n, i)
#define PH(i)
#define CK(i, dep)
#define ARR()
#define PROG(u)

__device__ __forceinline__ uint32_t s2u(const void* p) { return (uint32_t)__cvta_generic_to_shared(p); }
__device__ __forceinline__ void mbar_init(uint32_t bar, int cnt) {
    asm volatile("mbarrier.init.shared::cta.b64 [%0], %1;" :: "r"(bar), "r"(cnt) : "memory");
}
__device__ __forceinline__ void mbar_expect_tx(uint32_t bar, uint32_t bytes) {
    asm volatile("mbarrier.arrive.expect_tx.shared::cta.b64 _, [%0], %1;" :: "r"(bar), "r"(bytes) : "memory");
}
__device__ __forceinline__ void mbar_wait(uint32_t bar, uint32_t parity) {
    asm volatile("{\n.reg .pred p;\n.reg .u32 n;\nmov.u32 n, 0;\nWAIT_LOOP:\n"
                 "mbarrier.try_wait.parity.shared::cta.b64 p, [%0], %1;\n"
                 "@p bra WAIT_DONE;\nadd.u32 n, n, 1;\nsetp.lt.u32 p, n, %2;\n@p bra WAIT_LOOP;\nWAIT_DONE:\n}"
                 :: "r"(bar), "r"(parity), "n"(SPIN_MAX) : "memory");
}
__device__ __forceinline__ void tma_tile(uint32_t dst, const CUtensorMap* tm, int row, uint32_t bar, uint64_t pol) {
    asm volatile("cp.async.bulk.tensor.2d.shared::cluster.global.mbarrier::complete_tx::bytes.L2::cache_hint "
                 "[%0], [%1, {%3, %4}], [%2], %5;"
                 :: "r"(dst), "l"(tm), "r"(bar), "r"(0), "r"(row), "l"(pol) : "memory");
}
__device__ __forceinline__ void request_tile(uint32_t dst, const CUtensorMap* tm, int unit, uint32_t bar, uint64_t pol) {
    asm volatile("{\n.reg .pred p;\nelect.sync _|p, 0xffffffff;\n"
                 "@p mbarrier.arrive.expect_tx.shared::cta.b64 _, [%2], %6;\n"
                 "@p cp.async.bulk.tensor.2d.shared::cluster.global.mbarrier::complete_tx::bytes.L2::cache_hint "
                 "[%0], [%1, {%3, %4}], [%2], %5;\n}"
                 :: "r"(dst), "l"(tm), "r"(bar), "r"(0), "r"(unit * TILE_ROWS), "l"(pol), "n"(TILE_BYTES) : "memory");
}
__device__ __forceinline__ void tma_box(uint32_t dst, const CUtensorMap* tm, int col, int row, uint32_t bar) {
    asm volatile("cp.async.bulk.tensor.2d.shared::cluster.global.mbarrier::complete_tx::bytes [%0], [%1, {%3, %4}], [%2];"
                 :: "r"(dst), "l"(tm), "r"(bar), "r"(col), "r"(row) : "memory");
}
__device__ __forceinline__ void request_gate_up(uint32_t dst, const CUtensorMap* tg, const CUtensorMap* tu, int col, int row, uint32_t bar) {
    asm volatile("{\n.reg .pred p;\nelect.sync _|p, 0xffffffff;\n"
                 "@p mbarrier.arrive.expect_tx.shared::cta.b64 _, [%4], 5120;\n"
                 "@p cp.async.bulk.tensor.2d.shared::cluster.global.mbarrier::complete_tx::bytes [%0], [%2, {%5, %6}], [%4];\n"
                 "@p cp.async.bulk.tensor.2d.shared::cluster.global.mbarrier::complete_tx::bytes [%1], [%3, {%5, %6}], [%4];\n}"
                 :: "r"(dst), "r"(dst + 20480), "l"(tg), "l"(tu), "r"(bar), "r"(col), "r"(row) : "memory");
}
__device__ __forceinline__ uint32_t now_ns() { uint32_t t; asm volatile("mov.u32 %0, %%globaltimer_lo;" : "=r"(t)); return t; }
__device__ __forceinline__ uint32_t now_clk() { uint32_t t; asm volatile("mov.u32 %0, %%clock;" : "=r"(t)); return t; }
__device__ __forceinline__ void wait_clk(uint32_t t) { while (__any_sync(0xffffffffu, (int)(now_clk() - t) < 0)) {} }
constexpr uint64_t EVICT_FIRST = 0x12F0000000000000ull, EVICT_NORMAL = 0x1000000000000000ull;
__device__ __forceinline__ void request_box(uint32_t dst, const CUtensorMap* tm, int col, int row, uint32_t bar, uint64_t pol) {
    asm volatile("{\n.reg .pred p;\nelect.sync _|p, 0xffffffff;\n"
                 "@p cp.async.bulk.tensor.2d.shared::cluster.global.mbarrier::complete_tx::bytes.L2::cache_hint [%0], [%1, {%3, %4}], [%2], %5;\n}"
                 :: "r"(dst), "l"(tm), "r"(bar), "r"(col), "r"(row), "l"(pol) : "memory");
}
__device__ __forceinline__ uint32_t lds32(uint32_t addr) {
    uint32_t v;
    asm volatile("ld.shared.u32 %0, [%1];" : "=r"(v) : "r"(addr) : "memory");
    return v;
}
__device__ __forceinline__ void ldsm4(uint32_t (&r)[4], uint32_t addr) {
    asm volatile("ldmatrix.sync.aligned.m8n8.x4.shared.b16 {%0,%1,%2,%3}, [%4];"
                 : "=r"(r[0]), "=r"(r[1]), "=r"(r[2]), "=r"(r[3]) : "r"(addr) : "memory");
}
__device__ __forceinline__ void ldsm4t(uint32_t (&r)[4], uint32_t addr) {
    asm volatile("ldmatrix.sync.aligned.m8n8.x4.trans.shared.b16 {%0,%1,%2,%3}, [%4];"
                 : "=r"(r[0]), "=r"(r[1]), "=r"(r[2]), "=r"(r[3]) : "r"(addr) : "memory");
}
__device__ __forceinline__ void mma16816(float (&c)[4], const uint32_t (&a)[4], uint32_t b0, uint32_t b1) {
    asm volatile("mma.sync.aligned.m16n8k16.row.col.f32.bf16.bf16.f32 {%0,%1,%2,%3}, {%4,%5,%6,%7}, {%8,%9}, {%0,%1,%2,%3};"
                 : "+f"(c[0]), "+f"(c[1]), "+f"(c[2]), "+f"(c[3])
                 : "r"(a[0]), "r"(a[1]), "r"(a[2]), "r"(a[3]), "r"(b0), "r"(b1));
}
__device__ __forceinline__ uint4 ld_relaxed_v4(const void* p) {
    uint4 v;
    asm volatile("ld.relaxed.gpu.global.v4.u32 {%0,%1,%2,%3}, [%4];" : "=r"(v.x), "=r"(v.y), "=r"(v.z), "=r"(v.w) : "l"(p) : "memory");
    return v;
}
__device__ __forceinline__ float4 ld_relaxed_f4(const void* p) {
    float4 v;
    asm volatile("ld.relaxed.gpu.global.v4.f32 {%0,%1,%2,%3}, [%4];" : "=f"(v.x), "=f"(v.y), "=f"(v.z), "=f"(v.w) : "l"(p) : "memory");
    return v;
}
__device__ __forceinline__ float2 ld_relaxed_f2(const void* p) {
    float2 v;
    asm volatile("ld.relaxed.gpu.global.v2.f32 {%0,%1}, [%2];" : "=f"(v.x), "=f"(v.y) : "l"(p) : "memory");
    return v;
}
__device__ __forceinline__ float4 ld_relaxed_b128(const void* p) {
    float4 v;
    asm volatile("{\n.reg .b128 t;\n.reg .b64 a, b;\nld.relaxed.gpu.global.b128 t, [%4];\nmov.b128 {a, b}, t;\n"
                 "mov.b64 {%0, %1}, a;\nmov.b64 {%2, %3}, b;\n}" : "=f"(v.x), "=f"(v.y), "=f"(v.z), "=f"(v.w) : "l"(p) : "memory");
    return v;
}
__device__ __forceinline__ void st_relaxed_b128(void* p, float x, float y, float z, float w) {
    asm volatile("{\n.reg .b128 t;\n.reg .b64 a, b;\nmov.b64 a, {%1, %2};\nmov.b64 b, {%3, %4};\nmov.b128 t, {a, b};\n"
                 "st.relaxed.gpu.global.b128 [%0], t;\n}" :: "l"(p), "f"(x), "f"(y), "f"(z), "f"(w) : "memory");
}
__device__ __forceinline__ unsigned ld_acquire(const unsigned* p) {
    unsigned v;
    asm volatile("ld.acquire.gpu.global.u32 %0, [%1];" : "=r"(v) : "l"(p) : "memory");
    return v;
}
__device__ __forceinline__ void st_relaxed(void* p, uint32_t v) {
    asm volatile("st.relaxed.gpu.global.u32 [%0], %1;" :: "l"(p), "r"(v) : "memory");
}
__device__ __forceinline__ void red_f2(float* p, float a, float b) {
    asm volatile("red.relaxed.gpu.global.add.v2.f32 [%0], {%1,%2};" :: "l"(p), "f"(a), "f"(b) : "memory");
}
__device__ __forceinline__ void red_f4(float* p, float a, float b, float c, float d) {
    asm volatile("red.relaxed.gpu.global.add.v4.f32 [%0], {%1,%2,%3,%4};" :: "l"(p), "f"(a), "f"(b), "f"(c), "f"(d) : "memory");
}
__device__ __forceinline__ void draw(int& ticket, unsigned* ctr, bool pred) {
    asm volatile("{\n.reg .pred p;\nsetp.ne.u32 p, %2, 0;\n@p atom.relaxed.gpu.global.inc.u32 %0, [%1], 0x7fffffff;\n}"
                 : "+r"(ticket) : "l"(ctr), "r"((uint32_t)pred) : "memory");
}
__device__ __forceinline__ void red_release(unsigned* p) {
    asm volatile("red.release.gpu.global.add.u32 [%0], 1;" :: "l"(p) : "memory");
}
__device__ __forceinline__ uint32_t ld_relaxed_u32(const void* p) {
    uint32_t v;
    asm volatile("ld.relaxed.gpu.global.u32 %0, [%1];" : "=r"(v) : "l"(p) : "memory");
    return v;
}
__device__ __forceinline__ float rcp_approx(float v) {
    float r;
    asm("rcp.approx.ftz.f32 %0, %1;" : "=f"(r) : "f"(v));
    return r;
}
__device__ __forceinline__ float sigmoid_approx(float v) {
    float e;
    asm("ex2.approx.ftz.f32 %0, %1;" : "=f"(e) : "f"(v * -1.4426950408889634f));
    return rcp_approx(1.0f + e);
}
__device__ __forceinline__ float sqrt_approx(float v) {
    float r;
    asm("sqrt.approx.ftz.f32 %0, %1;" : "=f"(r) : "f"(v));
    return r;
}
__device__ __forceinline__ uint2 ld_relaxed_v2(const void* p) {
    uint2 v;
    asm volatile("ld.relaxed.gpu.global.v2.u32 {%0,%1}, [%2];" : "=r"(v.x), "=r"(v.y) : "l"(p) : "memory");
    return v;
}
__device__ __forceinline__ void wait_count(const unsigned* p, unsigned target) {
#pragma unroll 1
    for (int it = 0; it < SPIN_MAX; it++) {
        if (ld_acquire(p) >= target) break;
        __nanosleep(400);
    }
}
__device__ __forceinline__ float4* oacc_at(int side, int row, int grp) {
    return row >= SROW0 ? sided<float4>(side, X_O + (row - SROW0) * 1280 + grp * 16) : &g_st.oacc[row][grp];
}
__device__ __forceinline__ float2* lsum_at(int side, int row) {
    return row >= SROW0 ? sided<float2>(side, X_O + (row - SROW0) * 1280 + 1024) : g_st.lsum[row];
}
__device__ __forceinline__ void wait_row(int side, int bh, float n) {
    const float2* l = lsum_at(side, bh);
#pragma unroll 1
    for (int it = 0; it < SPIN_MAX; it++) {
        const float c = ld_relaxed_f2(l).y;
        if (c >= n) break;
        if (c == 0.f) __nanosleep(600);
    }
}
__device__ __forceinline__ void wait_row_o(int side, int bh, float n) {
    wait_row(side, bh, n);
    if (bh >= RED0) return;
#pragma unroll 1
    for (int it = 0; it < SPIN_MAX; it++) {
        if (__uint_as_float(ld_relaxed_u32(&g_st.oacc[bh][0].w)) == UPB) break;
        __nanosleep(300);
    }
}
__device__ __forceinline__ void spin_ns(int ns) {
    const long long t0 = clock64();
    while (clock64() - t0 < (long long)ns * 2) {}
}
__device__ __forceinline__ uint32_t pack_bf16(float lo, float hi) {
    uint32_t r;
    asm("cvt.rn.bf16x2.f32 %0, %1, %2;" : "=r"(r) : "f"(hi), "f"(lo));
    return r;
}
__device__ __forceinline__ float bf16r(float v) { return __uint_as_float(pack_bf16(0.f, v)); }
__device__ __forceinline__ uint32_t pack_neg(float lo, float hi) {
    const uint32_t w = pack_bf16(-lo, -hi);
    return w ? w : 0x80008000u;
}
__device__ __forceinline__ float lo_f(uint32_t v) { return __uint_as_float(v << 16); }
__device__ __forceinline__ float hi_f(uint32_t v) { return __uint_as_float(v & 0xffff0000u); }
__device__ __forceinline__ float warp_sum(float v) {
#pragma unroll
    for (int o = 16; o; o >>= 1) v += __shfl_xor_sync(0xffffffffu, v, o);
    return v;
}
__device__ __forceinline__ void layernorm20(float (&v)[20]) {
    float s = 0.f;
#pragma unroll
    for (int i = 0; i < 20; i++) s += v[i];
    const float mean = warp_sum(s) * (1.0f / DM);
    float q = 0.f;
#pragma unroll
    for (int i = 0; i < 20; i++) { const float d = v[i] - mean; q += d * d; }
    const float var = bf16r(warp_sum(q) * (1.0f / DM));
    const float m = bf16r(mean);
    const float rden = 1.0f / bf16r(sqrtf(bf16r(var + 1e-5f)));
#pragma unroll
    for (int i = 0; i < 20; i++) v[i] = bf16r(bf16r(v[i] - m) * rden);
}

__device__ __forceinline__ float sel4(int j, float a, float b, float c, float d) {
    float lo, hi, r;
    asm("{\n.reg .pred p;\nsetp.ne.s32 p, %3, 0;\nselp.f32 %0, %2, %1, p;\n}" : "=f"(lo) : "f"(a), "f"(b), "r"(j & 1));
    asm("{\n.reg .pred p;\nsetp.ne.s32 p, %3, 0;\nselp.f32 %0, %2, %1, p;\n}" : "=f"(hi) : "f"(c), "f"(d), "r"(j & 1));
    asm("{\n.reg .pred p;\nsetp.ne.s32 p, %3, 0;\nselp.f32 %0, %2, %1, p;\n}" : "=f"(r) : "f"(lo), "f"(hi), "r"(j & 2));
    return r;
}
template <typename T> __device__ __forceinline__ void pin(T*& p) { asm volatile("" : "+l"(p)); }
__device__ __forceinline__ void pin(uint32_t& v) { asm volatile("" : "+r"(v)); }
__device__ __forceinline__ void pin(float& v) { asm volatile("" : "+f"(v)); }
__device__ __forceinline__ uint32_t after(uint32_t n, float v) {
    asm volatile("{\n.reg .pred p;\nsetp.eq.u32 p, %1, 0x7fc1a5a5;\n@p add.u32 %0, %0, 32;\n}" : "+r"(n) : "r"(__float_as_uint(v)));
    return n;
}
__device__ __forceinline__ float2 lds64f(uint32_t addr) {
    float2 v;
    asm volatile("ld.shared.v2.f32 {%0,%1}, [%2];" : "=f"(v.x), "=f"(v.y) : "r"(addr) : "memory");
    return v;
}
__device__ __forceinline__ float4 lds128f(uint32_t addr) {
    float4 v;
    asm volatile("ld.shared.v4.f32 {%0,%1,%2,%3}, [%4];" : "=f"(v.x), "=f"(v.y), "=f"(v.z), "=f"(v.w) : "r"(addr) : "memory");
    return v;
}
__device__ __forceinline__ void sts128f(uint32_t addr, float a, float b, float c, float d, bool pred) {
    asm volatile("{\n.reg .pred p;\nsetp.ne.u32 p, %5, 0;\n@p st.shared.v4.f32 [%0], {%1,%2,%3,%4};\n}"
                 :: "r"(addr), "f"(a), "f"(b), "f"(c), "f"(d), "r"((uint32_t)pred) : "memory");
}
__device__ __forceinline__ void sts32f(uint32_t addr, float v) { asm volatile("st.shared.f32 [%0], %1;" :: "r"(addr), "f"(v) : "memory"); }
template <int ID> __device__ __forceinline__ void fin_arrive() { asm volatile("bar.arrive %0, 288;" :: "n"(ID) : "memory"); }
template <int ID> __device__ __forceinline__ void fin_sync() { asm volatile("bar.sync %0, 288;" :: "n"(ID) : "memory"); }
template <int ID> __device__ __forceinline__ void fin_sync(uint32_t n) { asm volatile("bar.sync %0, %1;" :: "n"(ID), "r"(n) : "memory"); }
__device__ __forceinline__ float2 sum8(uint32_t addr) {
    float2 t[8];
#pragma unroll
    for (int w = 0; w < 8; w++) t[w] = lds64f(addr + w * 128);
    return make_float2(((t[0].x + t[1].x) + (t[2].x + t[3].x)) + ((t[4].x + t[5].x) + (t[6].x + t[7].x)),
                       ((t[0].y + t[1].y) + (t[2].y + t[3].y)) + ((t[4].y + t[5].y) + (t[6].y + t[7].y)));
}
__device__ __forceinline__ float4 sum8x4(uint32_t addr) {
    float4 t[8];
#pragma unroll
    for (int w = 0; w < 8; w++) t[w] = lds128f(addr + w * 128);
#pragma unroll
    for (int o = 1; o < 8; o <<= 1) {
#pragma unroll
        for (int w = 0; w < 8; w += 2 * o) { t[w].x += t[w + o].x; t[w].y += t[w + o].y; t[w].z += t[w + o].z; t[w].w += t[w + o].w; }
    }
    return t[0];
}
template <int NJ>
__device__ __forceinline__ void load_o(uint32_t (&ob)[3 * NJ][2], int side, int bh, int J0, int j) {
    float4 v[NJ][4];
    float2 l;
#pragma unroll 1
    for (int it = 0; it < SPIN_MAX; it++) {
#pragma unroll
        for (int J = 0; J < NJ; J++) {
#pragma unroll
            for (int e = 0; e < 4; e++) v[J][e] = ld_relaxed_f4(oacc_at(side, bh, (J0 + J) * 16 + j) + e * 4);
        }
        l = ld_relaxed_f2(lsum_at(side, bh));
        bool ok = l.y == UPB;
#pragma unroll
        for (int J = 0; J < NJ; J++) {
#pragma unroll
            for (int e = 0; e < 4; e++) ok &= v[J][e].w == UPB;
        }
        if (__all_sync(0xffffffffu, ok)) break;
    }
    const float rl = __fdividef(1.0f, l.x);
#pragma unroll
    for (int J = 0; J < NJ; J++) {
        ob[3 * J][0] = pack_bf16(v[J][0].x * rl, v[J][1].x * rl);     ob[3 * J][1] = pack_bf16(v[J][2].x * rl, v[J][3].x * rl);
        ob[3 * J + 1][0] = pack_bf16(v[J][0].y * rl, v[J][1].y * rl); ob[3 * J + 1][1] = pack_bf16(v[J][2].y * rl, v[J][3].y * rl);
        ob[3 * J + 2][0] = pack_bf16(v[J][0].z * rl, v[J][1].z * rl); ob[3 * J + 2][1] = pack_bf16(v[J][2].z * rl, v[J][3].z * rl);
    }
}
__device__ __forceinline__ void aux_sync() { asm volatile("bar.sync 1, 256;" ::: "memory"); }

__global__ void __launch_bounds__(NTHREADS, 1)
fused_decode_kernel(const __grid_constant__ Params p) {
    extern __shared__ __align__(1024) unsigned char smem[];
    const uint32_t sb = s2u(smem);
    const int tid = threadIdx.x, warp = __shfl_sync(0xffffffffu, tid >> 5, 0), lane = tid & 31;
    const int cta = blockIdx.x;
    constexpr int grid = NCTAS;
    const int g = lane >> 2, j = lane & 3;

    TS(0);
    if (warp == 4 && cta < NQ_CTAS) {
        asm volatile("{\n.reg .pred p;\nelect.sync _|p, 0xffffffff;\n"
                     "@p mbarrier.init.shared::cta.b64 [%0], 1;\n"
                     "@p fence.mbarrier_init.release.cluster;\n"
                     "@p mbarrier.arrive.expect_tx.shared::cta.b64 _, [%0], 61440;\n}" :: "r"(sb + BAR_WQ) : "memory");
        uint32_t t = now_clk();
#pragma unroll
        for (int i = 0; i < 4; i++) {
            request_box(sb + SM_WQ + i * 15360, &p.wq, cta * 48, i * 160, sb + BAR_WQ, (WEF & 1) ? EVICT_FIRST : EVICT_NORMAL);
            if (WQ_GAP && i < 3) wait_clk(t += WQ_GAP);
        }
    }
    uint2 xr[5];
    if (XTOP && cta >= NQ_CTAS && tid < 40) asm volatile("prefetch.global.L2 [%0];" :: "l"(p.x + (cta - NQ_CTAS) * DM + tid * 16));
    if (tid == 160) {
#pragma unroll
        for (int w = 0; w < NWORK; w++) mbar_init(sb + BAR_KV + w * 8, 1);
        mbar_init(sb + BAR_W, 2);
#pragma unroll
        for (int w = 0; w < NAUX; w++) mbar_init(sb + BAR_G + w * 8, 1);
        asm volatile("fence.mbarrier_init.release.cluster;" ::: "memory");
    }
    __syncthreads();
    if (warp == NAUX + NWORK + 1) {
        uint32_t t = now_clk() + 2 * WO_AT_NS;
        if (lane == 0) mbar_expect_tx(sb + BAR_W, cta < NE_CTAS ? 61440 : 49152);
        const int col = cta < NE_CTAS ? (cta & 3) * 160 : (cta - NE_CTAS) * 32, row = cta < NE_CTAS ? (cta >> 2) * DH : 28 * DH;
#pragma unroll 1
        for (int r = 0; r < DH; r += WO_ROWS) {
            wait_clk(t);
#pragma unroll 1
            for (int i = 0; i < (cta < NE_CTAS ? 5 : 4); i++)
                request_box(sb + SM_A + i * 12288 + r * 64, &p.wo, cta < NE_CTAS ? col + i * 32 : col, (cta < NE_CTAS ? row : row + i * DH) + r, sb + BAR_W, (WEF & 2) ? EVICT_FIRST : EVICT_NORMAL);
            t += 2 * WO_GAP_NS;
        }
        return;
    }
    if (warp == NAUX + NWORK) {
        if (cta < NQ_CTAS) {
            spin_ns(CLEAR_AT_NS);
#pragma unroll
            for (int i = lane; i < STATE_V4; i += 32)
                if (cta * STATE_V4 + i < (int)(sizeof(State) / 16)) reinterpret_cast<uint4*>(&g_st)[cta * STATE_V4 + i] = make_uint4(0u, 0u, 0u, 0u);
            if (cta * 512 < X_END) {
                uint4* z = sided<uint4>(0, cta * 512 + lane * 16);
                *z = make_uint4(0u, 0u, 0u, 0u);
                *other_side(z) = make_uint4(0u, 0u, 0u, 0u);
            }
            __syncwarp();
            if (lane == 0) red_release(g_cnt_z);
        }
        if (lane == 0) { TS2(2); wait_count(g_cnt_z, NQ_CTAS); TS2(29); }
        __syncwarp();
        asm volatile("bar.arrive 2, %0;" :: "n"((NWORK + 1) * 32) : "memory");
        uint32_t rtt[2] = {0xffffffffu, 0xffffffffu};
        if (lane == 0) {
#pragma unroll 1
            for (int r = 0; r < 2 * NPROBE; r++) {
                int v = 0;
                uint32_t t1 = 0;
                unsigned* ctr = sided<unsigned>(r & 1, X_P + ((cta * 32 + (r >> 1) * 768) & 4095));
                pin(ctr);
                const uint32_t t0 = now_clk();
                draw(v, ctr, true);
                asm volatile("{\n.reg .pred q;\nsetp.ge.s32 q, %1, 0;\n@q mov.u32 %0, %%clock;\n}" : "+r"(t1) : "r"(v) : "memory");
                if (r & 1) rtt[1] = min(rtt[1], t1 - t0); else rtt[0] = min(rtt[0], t1 - t0);
            }
            sts32f(sb + SM_SIDE, __int_as_float(rtt[1] < rtt[0]));
        }
        const int side = __shfl_sync(0xffffffffu, rtt[1] < rtt[0], 0);
        fin_arrive<3>();
        int job = cta;
        auto sum_rows = [&](int row_end) {
#pragma unroll 1
            for (; job < 8 * min(row_end, RED0); job += NCTAS) {
                const int row = job >> 3, grp = (job & 7) * 8 + (lane & 7);
                if (lane == 0) wait_row(side, row, UPB);
                __syncwarp();
                const float4* src = &g_ring[row % RING][lane >> 3][grp];
                float sx = 0.f, sy = 0.f, sz = 0.f;
#pragma unroll 1
                for (int i = 0; i < 2; i++, src += 64 * 64) {
                    float4 v[16];
#pragma unroll 1
                    for (int it = 0; it < SPIN_MAX; it++) {
                        bool ok = true;
#pragma unroll
                        for (int k = 0; k < 16; k++) v[k] = ld_relaxed_b128(src + k * 4 * 64);
#pragma unroll
                        for (int k = 0; k < 16; k++) ok &= v[k].w == (float)(row + 1);
                        if (__all_sync(0xffffffffu, ok)) break;
                    }
#pragma unroll
                    for (int k = 0; k < 16; k++) { sx += v[k].x; sy += v[k].y; sz += v[k].z; }
                }
#pragma unroll
                for (int o = 8; o < 32; o <<= 1) {
                    sx += __shfl_xor_sync(0xffffffffu, sx, o); sy += __shfl_xor_sync(0xffffffffu, sy, o); sz += __shfl_xor_sync(0xffffffffu, sz, o);
                }
                if (lane < 8) st_relaxed_b128(&g_st.oacc[row][grp], sx, sy, sz, UPB);
            }
        };
        if (cta >= NE_CTAS) {
            const int col = (cta - NE_CTAS) * 32 + 2 * (lane & 15);
            uint32_t part = sb + SM_RED + (lane & 15) * 8;
#pragma unroll 1
            for (int b = 0; b < NB; b++) {
                const uint32_t xv = *reinterpret_cast<const uint32_t*>(p.x + b * DM + col);
                uint32_t* dst = sided<uint32_t>(lane >> 4, X_H + b * (DM * 2) + 4 * ((col >> 4) * 8 + (col & 6) + ((col >> 3) & 1)));
                sum_rows((b + 1) * NH);
                if (lane == 0) wait_row(side, b * NH + 28, 1);
                __syncwarp();
                float4 early;
#pragma unroll 1
                for (int it = 0; it < SPIN_MAX; it++) {
                    early = ld_relaxed_f4(&g_st.attn[b][col]);
                    if (__all_sync(0xffffffffu, early.y == NE_CTAS / 4 && early.w == NE_CTAS / 4)) break;
                }
                float x0 = lo_f(xv), x1 = hi_f(xv);
                pin(dst); pin(part); pin(x0); pin(x1);
                fin_sync<4>();
                CK(2, lds32(sb + SM_RED));
                const float2 late = sum8(part);
                const uint32_t hv = pack_neg(x0 + bf16r(early.x + late.x), x1 + bf16r(early.z + late.y));
                st_relaxed(dst, hv);
                CK(3, 0);
                if (lane == 0) TS2(15);
                fin_sync<5>();
            }
        } else if (cta < NF_CTAS) {
            uint32_t wr[10];
            float wsum = 0.f;
#pragma unroll
            for (int i = 0; i < 10; i++) {
                const int w = 4 * lane + 128 * (i >> 2) + (i & 3) - (i >= 8 ? 2 * lane : 0);
                wr[i] = *reinterpret_cast<const uint32_t*>(p.wr + (w >> 3) * 16 + (w & 1) * 8 + (w & 6));
                wsum += lo_f(wr[i]) + hi_f(wr[i]);
            }
            wsum = warp_sum(wsum);
            const int lb = lane >> 3, lc = lane & 7;
            uint32_t part = sb + SM_RED + lb * FPITCH + lc * 16, cpart = sb + SM_RED + 4 * FPITCH + lc * 16;
            uint32_t ypart = sb + SM_RED2 + (lc * 4 + lb) * 4;
            uint32_t* dst = sided<uint32_t>(side ^ 1, X_A + cta * 128 + lane * 4);
            uint32_t* dst2 = other_side(dst);
            __nv_bfloat16* out = p.out + lb * DM + cta * 8 + lc;
            float nmean_l = 0.f, rden_l = 0.f, sig_l = 0.f;
#pragma unroll 1
            for (int b = 0; b < NB; b++) {
                const uint32_t hx = X_H + b * (DM * 2), hrow = sb + SM_X + b * HPITCH;
                const uint4 *src0 = sided<uint4>(side, hx + 16 * lane), *src1 = sided<uint4>(side, hx + 512 + 16 * lane);
                const uint2* src2 = sided<uint2>(side, hx + 1024 + 8 * lane);
                sum_rows((b + 1) * NH);
                pin(dst); pin(dst2); pin(src0); pin(src1); pin(src2); pin(part); pin(cpart); pin(ypart); pin(out);
                if (lane == 0) wait_row(side, b * NH + NH - 1, 1);
                __syncwarp();
                uint4 h0, h1;
                uint2 h2;
#pragma unroll 1
                for (int it = 0; it < SPIN_MAX; it++) {
                    h0 = ld_relaxed_v4(src0);
                    h1 = ld_relaxed_v4(src1);
                    h2 = ld_relaxed_v2(src2);
                    asm volatile("st.shared.v4.u32 [%0], {%1,%2,%3,%4};" :: "r"(hrow + lane * 16), "r"(h0.x), "r"(h0.y), "r"(h0.z), "r"(h0.w) : "memory");
                    asm volatile("st.shared.v4.u32 [%0], {%1,%2,%3,%4};" :: "r"(hrow + 512 + lane * 16), "r"(h1.x), "r"(h1.y), "r"(h1.z), "r"(h1.w) : "memory");
                    asm volatile("st.shared.v2.u32 [%0], {%1,%2};" :: "r"(hrow + 1024 + lane * 8), "r"(h2.x), "r"(h2.y) : "memory");
                    const uint32_t lo = min(min(min(h0.x, h0.y), min(h0.z, h0.w)), min(min(min(h1.x, h1.y), min(h1.z, h1.w)), min(h2.x, h2.y)));
                    const bool ok = __all_sync(0xffffffffu, lo != 0) || it == SPIN_MAX - 1;
                    asm volatile("{\n.reg .pred p;\nsetp.ne.u32 p, %0, 0;\n@p bar.arrive 7, 288;\n}" :: "r"((uint32_t)ok) : "memory");
                    if (ok) break;
                }
                CK(4, h0.x);
                if (lane == 0) TS2(12);
                const uint32_t hw[10] = {h0.x, h0.y, h0.z, h0.w, h1.x, h1.y, h1.z, h1.w, h2.x, h2.y};
                float s1[2] = {}, s2[2] = {};
#pragma unroll
                for (int i = 0; i < 10; i++) {
                    const float v0 = lo_f(hw[i]), v1 = hi_f(hw[i]);
                    s1[i & 1] += v0 + v1;
                    s2[i & 1] = fmaf(v0, v0, fmaf(v1, v1, s2[i & 1]));
                }
                float m1 = s1[0] + s1[1], m2 = s2[0] + s2[1];
#pragma unroll
                for (int o = 16; o; o >>= 1) { m1 += __shfl_xor_sync(0xffffffffu, m1, o); m2 += __shfl_xor_sync(0xffffffffu, m2, o); }
                CK(5, __float_as_uint(m2));
                fin_sync<4>();
                CK(6, lds32(part));
                const float4 d = sum8x4(part), cs = sum8x4(cpart);
                m1 *= 1.0f / DM;
                const float nmean = bf16r(m1);
                const float var = bf16r(fmaxf(fmaf(-m1, m1, m2 * (1.0f / DM)), 0.f));
                const float rden = rcp_approx(bf16r(sqrt_approx(bf16r(var + 1e-5f))));
                if (lb == b) { nmean_l = nmean; rden_l = rden; }
                const float g0 = bf16r(fmaf(nmean_l, cs.x, -d.x) * rden_l), g1 = bf16r(fmaf(nmean_l, cs.y, -d.y) * rden_l);
                const float u0 = bf16r(fmaf(nmean_l, cs.z, -d.z) * rden_l), u1 = bf16r(fmaf(nmean_l, cs.w, -d.w) * rden_l);
                const uint32_t av = pack_neg(bf16r(g0 * sigmoid_approx(g0)) * u0, bf16r(g1 * sigmoid_approx(g1)) * u1);
                asm volatile("{\n.reg .pred p;\nsetp.eq.u32 p, %3, 3;\n@p st.relaxed.gpu.global.u32 [%0], %2;\n@p st.relaxed.gpu.global.u32 [%1], %2;\n}"
                             :: "l"(dst), "l"(dst2), "r"(av), "r"(b) : "memory");
                CK(7, 0);
                if (lane == 0) TS2(14);
                if (cta < NG_CTAS) {
                    fin_arrive<8>();
                    const uint32_t hw2 = lds32(sb + SM_X + lb * HPITCH + ((cta >> 1) * 8 + (lc & 6) + (cta & 1)) * 4);
                    const float nh = (lc & 1) ? hi_f(hw2) : lo_f(hw2);
                    float rr = 0.f;
#pragma unroll
                    for (int i = 0; i < 10; i++) rr = fmaf(lo_f(hw[i]), lo_f(wr[i]), fmaf(hi_f(hw[i]), hi_f(wr[i]), rr));
                    const float sig = bf16r(sigmoid_approx(bf16r((nmean * wsum - warp_sum(rr)) * rden)));
                    if (lb == b) sig_l = sig;
                    const float ln = bf16r(bf16r(nmean_l - nh) * rden_l);
                    fin_sync<6>(after(after(288, sig_l), ln));
                    CK(10, lds32(ypart));
                    float t[16];
#pragma unroll
                    for (int i = 0; i < 16; i++) t[i] = __uint_as_float(lds32(ypart + i * 192));
#pragma unroll
                    for (int o = 1; o < 16; o <<= 1) {
#pragma unroll
                        for (int i = 0; i < 16; i += 2 * o) t[i] += t[i + o];
                    }
                    const uint32_t ov = pack_bf16(bf16r(ln + bf16r(bf16r(-t[0]) * sig_l)) - nh, 0.f);
                    asm volatile("{\n.reg .pred p;\nsetp.eq.u32 p, %2, 3;\n@p st.global.u16 [%0], %1;\n}" :: "l"(out), "h"((unsigned short)ov), "r"(b) : "memory");
                    CK(11, 0);
                    if (lane == 0) TS2(13);
                }
                fin_sync<5>();
            }
            if (cta == 0 && lane == 0) { g_work[0] = 0; g_work[32] = 0; g_cnt_z[0] = 0; }
        } else {
            sum_rows(NBH);
        }
        return;
    }
    if (warp >= NAUX) {
        const int wk = warp - NAUX;
        const uint32_t bar = sb + BAR_KV + wk * 8;
        const uint32_t buf = sb + SM_KV + wk * TILE_BYTES;
        uint64_t pol;
        asm volatile("createpolicy.fractional.L2::evict_first.b64 %0, 1.0;" : "=l"(pol));
        const int nstatic = NWORK * grid;
        constexpr int POOL0 = NUNITS - NPOOL;
        int uk = wk * grid + cta;
        if (lane == 0) {
            spin_ns(K0_DELAY_NS + wk * K0_STEP_NS);
            mbar_expect_tx(bar, TILE_BYTES);
            tma_tile(buf, &p.k, uk * TILE_ROWS, bar, pol);
        }
        __syncwarp();
        uint32_t koff[3], voff[3];
        {
            const int r = lane & 7, hf = (lane >> 3) & 1;
            const int kkey = hf ? 8 + (r ^ 1) : r;
            const int vh = lane >> 4;
            const int vkey = ((r & 1) ? 8 : 0) + (vh ? (r ^ 1) : r);
#pragma unroll
            for (int b = 0; b < 3; b++) {
                const int rk = 3 * kkey + b, rv = 3 * vkey + b;
                koff[b] = buf + rk * 128 + (((lane >> 4) ^ (rk & 7)) << 4);
                voff[b] = buf + rv * 128 + ((hf ^ (rv & 7)) << 4);
            }
        }
        uint32_t phase = 0;
        uint4 qf[6];
        auto load_q = [&](int u) {
            const uint32_t* q = &g_early[u / UPB].q[j * 4];
#pragma unroll
            for (int i = 0; i < 6; i++) qf[i] = ld_relaxed_v4(q + i * 16);
        };
        load_q(uk);
        int uq[LAG];
        uint32_t sq[LAG];
#pragma unroll
        for (int i = 0; i < LAG; i++) { uq[i] = -1; sq[i] = 0; }
        uint4 mv = make_uint4(0u, 0u, 0u, 0u);
        float freed = UPB;
        while (true) {
            const int uv = uq[0];
            uint32_t sv = sq[0];
#pragma unroll
            for (int i = 0; i + 1 < LAG; i++) { uq[i] = uq[i + 1]; sq[i] = sq[i + 1]; }
            uq[LAG - 1] = uk;
            if (uk < NUNITS) {
                PH(7);
#pragma unroll 1
                for (int it = 0; it < SPIN_MAX; it++) {
                    uint32_t lo = 0xffffffffu;
#pragma unroll
                    for (int i = 0; i < 6; i++) lo = min(min(lo, min(qf[i].x, qf[i].y)), min(qf[i].z, qf[i].w));
                    if (__all_sync(0xffffffffu, lo != 0)) break;
                    __nanosleep(QNAP);
                    load_q(uk);
                }
                mbar_wait(bar, phase); phase ^= 1;
                PH(0); ARR();
                TSI(0, 16); TSI(1, 18);
                float acc[2][4][4] = {};
#pragma unroll
                for (int ks = 0; ks < 12; ks++) {
                    const uint4 qq = qf[ks >> 1];
                    const uint32_t b0 = (ks & 1) ? qq.z : qq.x, b1 = (ks & 1) ? qq.w : qq.y;
#pragma unroll
                    for (int mt = 0; mt < 4; mt++) {
                        uint32_t a[4];
                        ldsm4(a, (koff[ks >> 2] ^ ((ks & 3) << 5)) + mt * 6144);
                        mma16816(acc[ks & 1][mt], a, b0, b1);
                    }
                }
                PH(1);
                TSI(0, 17); TSI(1, 19);
                if (uv < NUNITS) request_tile(buf, uv >= 0 ? &p.v : &p.k, uv >= 0 ? uv : uk + nstatic, bar, pol);
                const float sa = sel4(j, acc[0][0][0], acc[0][1][0], acc[0][2][0], acc[0][3][0]) + sel4(j, acc[1][0][0], acc[1][1][0], acc[1][2][0], acc[1][3][0]);
                const float sc = sel4(j, acc[0][0][2], acc[0][1][2], acc[0][2][2], acc[0][3][2]) + sel4(j, acc[1][0][2], acc[1][1][2], acc[1][2][2], acc[1][3][2]);
                const uint32_t raw = pack_bf16(sa, sc);
                const float scale = -0.07216878364870322f;
                const uint32_t sk = pack_bf16(lo_f(raw) * scale, hi_f(raw) * scale);
                sq[LAG - 1] = sk;
                if (uk >= POOL0) st_relaxed(&g_st.score[uk - POOL0][lane], sk ? sk : 0x80008000u);
                int a = (int)(sk << 16), b = (int)(sk & 0xffff0000u);
                a ^= (a >> 31) & 0x7fff0000; b ^= (b >> 31) & 0x7fff0000;
                const int mx = __reduce_max_sync(0xffffffffu, max(a, b));
                if (lane == 0) st_relaxed(&g_early[uk / UPB].umax[uk % UPB], (uint32_t)mx | 1u);
            }
            if (uv < 0) {
                uk += nstatic;
                load_q(uk);
                continue;
            }
            if (uv >= NUNITS) break;
            const int bh = uv / UPB;
#pragma unroll 1
            for (int it = 0; it < SPIN_MAX; it++) {
                if (__all_sync(0xffffffffu, (mv.x & mv.y & mv.z & mv.w & 1u) && (uv < POOL0 || sv != 0) && freed == UPB)) break;
                mv = ld_relaxed_v4(&g_early[bh].umax[lane * 4]);
                if (bh >= RING && bh < RED0) freed = __uint_as_float(ld_relaxed_u32(&g_st.oacc[bh - RING][(lane & 7) * 8].w));
                if (uv >= POOL0) sv = ld_relaxed_u32(&g_st.score[uv - POOL0][lane]);
            }
            PH(2);
            int un = NUNITS, vn = 0;
            draw(un, g_work, uk < NUNITS && lane == 0);
            draw(vn, g_work + 32, uq[0] >= POOL0 && lane == 0);
            uint32_t tdraw = 0;
            if (NEARLY < NAUX && uq[0] >= POOL0) tdraw = now_ns();
            int mx = __reduce_max_sync(0xffffffffu, max(max((int)mv.x, (int)mv.y), max((int)mv.z, (int)mv.w))) & 0xffff0000;
            mx ^= (mx >> 31) & 0x7fff0000;
            const float m = __int_as_float(mx);
            const float l2e = 1.4426950408889634f;
            const uint32_t pp = pack_bf16(exp2f((lo_f(sv) - m) * l2e), exp2f((hi_f(sv) - m) * l2e));
            uint32_t pb[8];
#pragma unroll
            for (int t = 0; t < 4; t++) {
                pb[2 * t] = __shfl_sync(0xffffffffu, pp, 8 * j + t);
                pb[2 * t + 1] = __shfl_sync(0xffffffffu, pp, 8 * j + 4 + t);
            }
            float lacc[4] = {};
            const uint32_t ones[4] = {0x3f803f80u, 0x3f803f80u, 0x3f803f80u, 0x3f803f80u};
#pragma unroll
            for (int t = 0; t < 4; t++) mma16816(lacc, ones, pb[2 * t], pb[2 * t + 1]);
            PH(3);
            mbar_wait(bar, phase); phase ^= 1;
            PH(4); ARR();
            float acc[12][4] = {};
#pragma unroll
            for (int t = 0; t < 4; t++) {
#pragma unroll
                for (int mt = 0; mt < 12; mt++) {
                    uint32_t a[4];
                    ldsm4t(a, (voff[mt >> 2] ^ ((mt & 3) << 5)) + t * 6144);
                    mma16816(acc[mt], a, pb[2 * t], pb[2 * t + 1]);
                }
            }
            un = __shfl_sync(0xffffffffu, un, 0) + (LAG + 1) * nstatic;
            vn = __shfl_sync(0xffffffffu, vn, 0);
            if (uq[0] >= POOL0) uq[0] = POOL0 + vn;
            PH(5);
            if (lane == 0) PROG(un);
            if (un < NUNITS || uq[0] < NUNITS) request_tile(buf, un < NUNITS ? &p.k : &p.v, un < NUNITS ? un : uq[0], bar, pol);
            if (un < NUNITS) load_q(un);
            if (NEARLY < NAUX && vn == VTRIG && lane == 0) st_relaxed(g_st.tstart, (tdraw + TRIG_NS) | 1u);
            float o[6];
#pragma unroll
            for (int e = 0; e < 6; e++) {
                const int q = e % 3, c = (e / 3) * 2;
                o[e] = sel4(j, acc[q][c], acc[3 + q][c], acc[6 + q][c], acc[9 + q][c]);
            }
            if (uv < nstatic) {
                asm volatile("bar.sync 2, %0;" :: "n"((NWORK + 1) * 32) : "memory");
                TSW(3);
            }
            const int grp = 16 * j + 4 * (g & 1) + (g >> 1);
            if (bh < RED0) {
                float4* dst = &g_ring[bh % RING][uv % UPB][grp];
                st_relaxed_b128(dst, o[0], o[1], o[2], (float)(bh + 1));
                st_relaxed_b128(dst + 8, o[3], o[4], o[5], (float)(bh + 1));
            }
            const int acc_row = bh >= NBH - 4 && uv % OREP ? bh + 4 * (uv % OREP) : bh;
            if (bh >= RED0) {
                float4* dst = oacc_at(0, acc_row, grp);
                red_f4(&dst->x, o[0], o[1], o[2], 1.f);
                red_f4(&dst[8].x, o[3], o[4], o[5], 1.f);
                if (bh >= SROW0) {
                    red_f4(&other_side(dst)->x, o[0], o[1], o[2], 1.f);
                    red_f4(&other_side(dst)[8].x, o[3], o[4], o[5], 1.f);
                }
            }
            if (lane < (bh >= SROW0 ? 2 : 1)) red_f2(&lsum_at(lane, acc_row)->x, lacc[0], 1.f);
            PH(6);
            if (uq[0] >= NUNITS && un >= NUNITS) break;
            uk = un;
            if (uq[0] < NUNITS) {
                const int nb = uq[0] / UPB;
                mv = ld_relaxed_v4(&g_early[nb].umax[lane * 4]);
                freed = nb >= RING && nb < RED0 ? __uint_as_float(ld_relaxed_u32(&g_st.oacc[nb - RING][(lane & 7) * 8].w)) : UPB;
                if (uq[0] >= POOL0) sq[0] = ld_relaxed_u32(&g_st.score[uq[0] - POOL0][lane]);
            }
        }
        TSW(4 + wk);
        return;
    }

    __nv_bfloat16* xs = reinterpret_cast<__nv_bfloat16*>(smem + SM_X);
    float* red = reinterpret_cast<float*>(smem + SM_RED);
    const int frow = (lane & 7) + ((lane >> 4) << 3), fcol = (lane >> 3) & 1;
    if (cta < NQ_CTAS) {
        if (warp < NB) {
            spin_ns(X_AT_NS);
#pragma unroll
            for (int i = 0; i < 5; i++) xr[i] = *reinterpret_cast<const uint2*>(p.x + warp * DM + i * 128 + lane * 4);
        }
        TS(26);
        if (warp < NB) {
            float v[20];
#pragma unroll
            for (int i = 0; i < 5; i++) {
                v[4 * i] = lo_f(xr[i].x); v[4 * i + 1] = hi_f(xr[i].x); v[4 * i + 2] = lo_f(xr[i].y); v[4 * i + 3] = hi_f(xr[i].y);
            }
            layernorm20(v);
#pragma unroll
            for (int i = 0; i < 5; i++)
                *reinterpret_cast<uint2*>(xs + warp * XPITCH + i * 128 + lane * 4) =
                    make_uint2(pack_bf16(v[4 * i], v[4 * i + 1]), pack_bf16(v[4 * i + 2], v[4 * i + 3]));
        }
        TS(27);
        aux_sync();
        mbar_wait(sb + BAR_WQ, 0);
        TS(1);
        const uint32_t xfrag = sb + SM_X + ((g & 3) * XPITCH + 2 * j) * 2;
        float acc[3][4] = {};
#pragma unroll
        for (int s = 0; s < 5; s++) {
            const int ks = warp * 5 + s;
            const uint32_t b0 = lds32(xfrag + ks * 32), b1 = lds32(xfrag + ks * 32 + 16);
            const int row = ks * 16 + frow;
#pragma unroll
            for (int mt = 0; mt < 3; mt++) {
                uint32_t a[4];
                ldsm4t(a, sb + SM_WQ + (row * 6 + 2 * mt + fcol) * 16);
                mma16816(acc[mt], a, b0, b1);
            }
        }
        if (j < 2) {
#pragma unroll
            for (int mt = 0; mt < 3; mt++) {
                *reinterpret_cast<float2*>(red + (warp * 48 + mt * 16 + g) * 4 + 2 * j) = make_float2(acc[mt][0], acc[mt][1]);
                *reinterpret_cast<float2*>(red + (warp * 48 + mt * 16 + 8 + g) * 4 + 2 * j) = make_float2(acc[mt][2], acc[mt][3]);
            }
        }
        aux_sync();
        if (tid < 96) {
            const int b = tid & 3, cp = tid >> 2;
            float s0 = 0.f, s1 = 0.f;
#pragma unroll
            for (int w = 0; w < 8; w++) { s0 += red[(w * 48 + 2 * cp) * 4 + b]; s1 += red[(w * 48 + 2 * cp + 1) * 4 + b]; }
            const int h = cta >> 2, d = (cta & 3) * 48 + 2 * cp;
            const int ch = d >> 3, jj = (d & 7) >> 1;
            st_relaxed(&g_early[b * NH + h].q[(ch >> 2) * 16 + jj * 4 + (ch & 3)], pack_neg(s0, s1));
        }
        TS(28);
    }
    if (warp == 4) {
        const uint32_t wbar = sb + BAR_W;
        asm volatile("fence.proxy.async.shared::cta;" ::: "memory");
        if (lane == 0) mbar_expect_tx(wbar, cta < NG_CTAS ? 24576 : 0);
        spin_ns(W_AT_NS);
        if (cta < NF_CTAS) {
#pragma unroll 1
            for (int i = 0; i < NEARLY; i++) {
                request_gate_up(sb + SM_G + i * 2560, &p.wg, &p.wu, cta * 16, i * 80, sb + BAR_G + i * 8);
                spin_ns(W_GAP_NS);
            }
        }
        if (cta < NG_CTAS && lane == 0) {
#pragma unroll 1
            for (int i = 0; i < 6; i++) {
                tma_box(sb + SM_D + i * 4096, &p.wd, cta * 8, i * 256, wbar);
                spin_ns(W_GAP_NS);
            }
        }
        __syncwarp();
    }
    if (tid < 160) *reinterpret_cast<uint2*>(smem + SM_X + 4 * HPITCH + tid * 8) = make_uint2(0x3f803f80u, 0x3f803f80u);
    fin_sync<3>();
    const int side = lds32(sb + SM_SIDE);
    mbar_wait(sb + BAR_W, 0);
    TS(7);
    uint32_t part = sb + SM_RED + (warp * 32 + 8 * j + g) * 4;

#pragma unroll 1
    for (int b = 0; b < NB; b++) {
        if (cta >= NE_CTAS) {
            uint32_t a[6][2][4];
#pragma unroll
            for (int s = 0; s < 6; s++) {
                const int row = (warp * 6 + s) * 16 + frow;
#pragma unroll
                for (int mt = 0; mt < 2; mt++) ldsm4t(a[s][mt], sb + SM_A + (row * 4 + ((2 * mt + fcol) ^ ((row >> 1) & 3))) * 16);
            }
            const int bh = b * NH + 28 + (warp >> 1);
            const float4* osrc[OREP];
            const float2* lsrc[OREP];
#pragma unroll
            for (int c = 0; c < OREP; c++) {
                const int row = b == NB - 1 ? bh + 4 * c : bh;
                osrc[c] = oacc_at(side, row, (warp & 1) * 32 + lane);
                lsrc[c] = lsum_at(side, row);
                pin(osrc[c]); pin(lsrc[c]);
            }
            if (lane == 0) wait_row_o(side, bh, UPB * 3 / (4 * OREP));
            __syncwarp();
            float4 ov;
            float2 lv;
            pin(part);
#pragma unroll 1
            for (int it = 0; it < SPIN_MAX; it++) {
                float4 oc[OREP];
                float2 lc[OREP];
#pragma unroll
                for (int c = 0; c < OREP; c++) {
                    oc[c] = ld_relaxed_f4(osrc[c]);
                    lc[c] = ld_relaxed_f2(lsrc[c]);
                }
                ov = oc[0]; lv = lc[0];
                if (b == NB - 1) {
#pragma unroll
                    for (int c = 1; c < OREP; c++) {
                        ov.x += oc[c].x; ov.y += oc[c].y; ov.z += oc[c].z; ov.w += oc[c].w; lv.x += lc[c].x; lv.y += lc[c].y;
                    }
                }
                if (__all_sync(0xffffffffu, ov.w == UPB && lv.y == UPB)) break;
            }
            CK(0, __float_as_uint(ov.x));
            const float rl = rcp_approx(lv.x);
            const float px = __shfl_xor_sync(0xffffffffu, ov.x, 4), py = __shfl_xor_sync(0xffffffffu, ov.y, 4),
                        pz = __shfl_xor_sync(0xffffffffu, ov.z, 4);
            const uint32_t w[3] = {pack_bf16(ov.x * rl, px * rl), pack_bf16(ov.y * rl, py * rl), pack_bf16(ov.z * rl, pz * rl)};
            float acc[2][2][4] = {};
#pragma unroll
            for (int s = 0; s < 6; s++) {
                const uint32_t b0 = __shfl_sync(0xffffffffu, w[s % 3], (s / 3) * 16 + j);
                const uint32_t b1 = __shfl_sync(0xffffffffu, w[s % 3], (s / 3) * 16 + 8 + j);
#pragma unroll
                for (int mt = 0; mt < 2; mt++) mma16816(acc[mt][s & 1], a[s][mt], b0, b1);
            }
            sts32f(part, sel4(j, acc[0][0][0] + acc[0][1][0], acc[0][0][2] + acc[0][1][2], acc[1][0][0] + acc[1][1][0], acc[1][0][2] + acc[1][1][2]));
            CK(1, 0);
            fin_arrive<4>();
            fin_sync<5>();
            if (cta < NE_CTAS + 4 && tid < 56) reinterpret_cast<uint4*>(&g_early[b * NH + 28 + cta - NE_CTAS])[tid] = make_uint4(0u, 0u, 0u, 0u);
            continue;
        }
        {
            const int bh = b * NH + (cta >> 2);
            if (tid == 0) wait_row_o(side, bh, UPB);
            aux_sync();
            if (warp < 5) {
                uint32_t ob[12][2];
                load_o<4>(ob, side, bh, 0, j);
                float acc[2][2][4] = {};
#pragma unroll
                for (int ks = 0; ks < 12; ks++) {
                    const int row = ks * 16 + frow;
#pragma unroll
                    for (int mt = 0; mt < 2; mt++) {
                        uint32_t a[4];
                        ldsm4t(a, sb + SM_A + warp * 12288 + (row * 4 + ((2 * mt + fcol) ^ ((row >> 1) & 3))) * 16);
                        mma16816(acc[mt][ks & 1], a, ob[ks][0], ob[ks][1]);
                    }
                }
                red_f2(&g_st.attn[b][(cta & 3) * 160 + warp * 32 + 8 * j + g].x,
                       sel4(j, acc[0][0][0] + acc[0][1][0], acc[0][0][2] + acc[0][1][2], acc[1][0][0] + acc[1][1][0], acc[1][0][2] + acc[1][1][2]), 1.f);
                TS(8);
            } else if (warp > 5 && (cta & 3) == 0 && tid - 192 < 56) {
                reinterpret_cast<uint4*>(&g_early[bh])[tid - 192] = make_uint4(0u, 0u, 0u, 0u);
            }
        }
        if (cta >= NF_CTAS) continue;

        if (b == NB - 1) {
            if (NEARLY < NAUX && warp == NAUX - 1) {
                uint32_t t = 0;
                asm volatile("fence.proxy.async.shared::cta;" ::: "memory");
#pragma unroll 1
                for (int it = 0; it < SPIN_MAX; it++) {
                    t = ld_relaxed_u32(g_st.tstart);
                    if (__all_sync(0xffffffffu, t != 0)) break;
                    __nanosleep(300);
                }
#pragma unroll 1
                for (int it = 0; it < SPIN_MAX; it++) if (__all_sync(0xffffffffu, t - now_ns() > 2 * TRIG_NS)) break;
                TSW(11);
                t = now_clk();
#pragma unroll 1
                for (int i = NEARLY; i < NAUX; i++) {
                    wait_clk(t);
                    request_gate_up(sb + SM_G + i * 2560, &p.wg, &p.wu, cta * 16, i * 80, sb + BAR_G + i * 8);
                    t += GCLK;
                }
            }
            mbar_wait(sb + BAR_G + warp * 8, 0);
            if (warp == NAUX - 1) TSW(9);
        }
        uint32_t ga[5][2][4], wb[6][4];
#pragma unroll
        for (int s = 0; s < 5; s++) {
            const int row = (warp * 5 + s) * 16 + frow;
#pragma unroll
            for (int t = 0; t < 2; t++) ldsm4t(ga[s][t], sb + SM_G + fcol * 20480 + (row * 2 + (t ^ ((row >> 2) & 1))) * 16);
        }
#pragma unroll
        for (int s = 0; s < 6; s++) {
            const int kstep = warp * 12 + (s >> 1) * 4 + 2 * fcol + ((lane >> 2) & 1), word = (lane & 2) * 2 + (s & 1) * 2 + (lane >> 4);
            ldsm4t(wb[s], sb + SM_D + (kstep * 16 + word + (lane & 1) * 8) * 16);
        }
        const uint4* asrc[3];
#pragma unroll
        for (int q = 0; q < 3; q++) {
            asrc[q] = sided<uint4>(side, X_A + (warp * 12 + 4 * q + 2 * (g >> 2) + (j >> 1)) * 128 + (g & 3) * 32 + (j & 1) * 16);
            pin(asrc[q]);
        }
        uint32_t fpart = sb + SM_RED + 2 * j * FPITCH + warp * 128 + g * 16;
        uint32_t ypart = sb + SM_RED2 + ((warp * 2 + (j >> 1)) * 48 + g * 4 + 2 * (j & 1)) * 4;
        uint32_t hfrag = sb + SM_X + min(g, 4) * HPITCH + (warp * 40 + 2 * j) * 4;
        pin(fpart); pin(ypart); pin(hfrag);
        fin_sync<7>();
        {
            float acc[2][2][4] = {};
#pragma unroll
            for (int s = 0; s < 5; s++) {
                const float2 hv = lds64f(hfrag + s * 32);
#pragma unroll
                for (int t = 0; t < 2; t++) mma16816(acc[t][s & 1], ga[s][t], __float_as_uint(hv.x), __float_as_uint(hv.y));
            }
#pragma unroll
            for (int e = 0; e < 2; e++)
                sts128f(fpart + e * FPITCH, acc[0][0][e] + acc[0][1][e], acc[1][0][e] + acc[1][1][e],
                        acc[0][0][2 + e] + acc[0][1][2 + e], acc[1][0][2 + e] + acc[1][1][2 + e], 2 * j + e < 5);
        }
        CK(5, 0);
        fin_arrive<4>();
        if (cta < NG_CTAS) {
            uint4 v[3];
            fin_sync<8>();
#pragma unroll 1
            for (int it = 0; it < SPIN_MAX; it++) {
                uint32_t lo = 0xffffffffu;
#pragma unroll
                for (int q = 0; q < 3; q++) v[q] = ld_relaxed_v4(asrc[q]);
#pragma unroll
                for (int q = 0; q < 3; q++) lo = min(min(lo, min(v[q].x, v[q].y)), min(v[q].z, v[q].w));
                if (__all_sync(0xffffffffu, lo != 0 || b < NB - 1)) break;
            }
            CK(8, v[0].x);
            float acc[3][4] = {};
#pragma unroll
            for (int q = 0; q < 3; q++) mma16816(acc[q], wb[2 * q], v[q].x, v[q].y);
#pragma unroll
            for (int q = 0; q < 3; q++) mma16816(acc[q], wb[2 * q + 1], v[q].z, v[q].w);
            const float y0 = j < 2 ? acc[0][0] + acc[1][0] + acc[2][0] : acc[0][2] + acc[1][2] + acc[2][2];
            const float y1 = j < 2 ? acc[0][1] + acc[1][1] + acc[2][1] : acc[0][3] + acc[1][3] + acc[2][3];
            asm volatile("st.shared.v2.f32 [%0], {%1,%2};" :: "r"(ypart), "f"(y0), "f"(y1) : "memory");
            CK(9, 0);
            fin_arrive<6>();
        }
        fin_sync<5>();
    }
}

typedef CUresult (*EncodeFn)(CUtensorMap*, CUtensorMapDataType, cuuint32_t, void*, const cuuint64_t*, const cuuint64_t*,
                             const cuuint32_t*, const cuuint32_t*, CUtensorMapInterleave, CUtensorMapSwizzle,
                             CUtensorMapL2promotion, CUtensorMapFloatOOBfill);

CUtensorMap make_map(EncodeFn enc, void* ptr, uint64_t cols, uint64_t rows, uint32_t bcols, uint32_t brows,
                     CUtensorMapSwizzle sw, CUtensorMapL2promotion promo) {
    CUtensorMap m;
    const cuuint64_t dims[2] = {cols, rows};
    const cuuint64_t strides[1] = {cols * 2};
    const cuuint32_t box[2] = {bcols, brows};
    const cuuint32_t es[2] = {1, 1};
    enc(&m, CU_TENSOR_MAP_DATA_TYPE_BFLOAT16, 2, ptr, dims, strides, box, es, CU_TENSOR_MAP_INTERLEAVE_NONE, sw, promo,
        CU_TENSOR_MAP_FLOAT_OOB_FILL_NONE);
    return m;
}

}

extern "C" void kernel_launch(void* const* d_in, const int* in_sizes, int n_in, void* d_out, int out_size) {
    (void)in_sizes; (void)n_in; (void)out_size;
    static EncodeFn enc = nullptr;
    static int sms = 0;
    if (!enc) {
        cudaDriverEntryPointQueryResult qr;
        cudaGetDriverEntryPoint("cuTensorMapEncodeTiled", (void**)&enc, cudaEnableDefault, &qr);
        int dev = 0;
        cudaGetDevice(&dev);
        cudaDeviceGetAttribute(&sms, cudaDevAttrMultiProcessorCount, dev);
        cudaFuncSetAttribute(fused_decode_kernel, cudaFuncAttributeMaxDynamicSharedMemorySize, SM_TOTAL);
    }
    if (sms < NCTAS) return;
    const CUtensorMapL2promotion WPROMO = CU_TENSOR_MAP_L2_PROMOTION_L2_128B;
    Params p;
    p.k = make_map(enc, d_in[1], 64, (uint64_t)NBH * SK * 3, 64, TILE_ROWS, CU_TENSOR_MAP_SWIZZLE_128B, CU_TENSOR_MAP_L2_PROMOTION_NONE);
    p.v = make_map(enc, d_in[2], 64, (uint64_t)NBH * SK * 3, 64, TILE_ROWS, CU_TENSOR_MAP_SWIZZLE_128B, CU_TENSOR_MAP_L2_PROMOTION_NONE);
    p.wq = make_map(enc, d_in[3], NH * DH, DM, 48, 160, CU_TENSOR_MAP_SWIZZLE_NONE, WPROMO);
    p.wo = make_map(enc, d_in[4], DM, NH * DH, 32, WO_ROWS, CU_TENSOR_MAP_SWIZZLE_64B, WPROMO);
    p.wg = make_map(enc, d_in[7], FF, DM, 16, 80, CU_TENSOR_MAP_SWIZZLE_32B, (CUtensorMapL2promotion)GPROMO);
    p.wu = make_map(enc, d_in[8], FF, DM, 16, 80, CU_TENSOR_MAP_SWIZZLE_32B, (CUtensorMapL2promotion)GPROMO);
    p.wd = make_map(enc, d_in[9], DM, FF, 8, 256, CU_TENSOR_MAP_SWIZZLE_NONE, WPROMO);
    p.x = (const __nv_bfloat16*)d_in[0];
    p.wr = (const __nv_bfloat16*)d_in[6];
    p.out = (__nv_bfloat16*)d_out;
    fused_decode_kernel<<<NCTAS, NTHREADS, SM_TOTAL, cudaStreamPerThread>>>(p);
}
```

```cpp
#include <cuda_runtime.h>
#include <cuda_bf16.h>
#include <cuda.h>
#include <stdint.h>

namespace {

constexpr int NB = 4, NH = 32, SK = 8192, DH = 192, DM = 640, FF = 1536;
constexpr int NBH = NB * NH;
constexpr int TILE = 64;
constexpr int UPB = SK / TILE;
constexpr int NUNITS = NBH * UPB;
constexpr int TILE_BYTES = TILE * DH * 2;
constexpr int TILE_ROWS = TILE * 3;
constexpr int NCTAS = 132;
constexpr int NQ_CTAS = 128;
constexpr int NE_CTAS = 112;
constexpr int NF_CTAS = 96;

#define NWORK 2
#define LAG 2
#define NPOOL 640
#define RED0 116
#define RING 12
#define OREP 2
#define SROW0 124
#define NPROBE 6
#define VTRIG 300
#define TRIG_NS 4700
#define GPROMO 2
#define DCLK 150
#define GCLK 300
#define K0_DELAY_NS 1700
#define K0_STEP_NS 900
#define WO_GAP_NS 550
#define WO_ROWS 48
#define QNAP 250
#define WO_AT_NS 3600
constexpr int NAUX = 8;
constexpr int NTHREADS = (NAUX + NWORK + 2) * 32;
constexpr int SPIN_MAX = 1 << 22;

constexpr int SM_KV = 0;
constexpr int SM_A = SM_KV + NWORK * TILE_BYTES;
constexpr int SM_D = SM_A;
constexpr int SM_WQ = SM_A + 61440;
constexpr int SM_G = SM_WQ;
constexpr int SM_X = SM_WQ + 61440;
constexpr int XPITCH = 648;
constexpr int HPITCH = 1344;
constexpr int SM_RED = SM_X + 5 * HPITCH;
constexpr int FPITCH = 544;
constexpr int SM_RED2 = SM_RED + 5 * FPITCH;
constexpr int YPITCH = 320;
constexpr int SM_MISC = SM_RED2 + 16 * YPITCH;
constexpr int BAR_KV = SM_MISC, BAR_WQ = SM_MISC + 32, BAR_W = SM_MISC + 40, SM_SIDE = SM_MISC + 48, BAR_G = SM_MISC + 64, BAR_D = SM_MISC + 96;
constexpr int SM_TOTAL = SM_MISC + 160;

struct Params {
    CUtensorMap k, v;
    CUtensorMap wq;
    CUtensorMap wo;
    CUtensorMap wg, wu;
    CUtensorMap wd;
    const __nv_bfloat16 *x, *wr;
    __nv_bfloat16* out;
};

struct Early {
    uint32_t q[96];
    uint32_t umax[UPB];
};
#define LSTRIDE 16
struct State {
    float4 oacc[SROW0][64];
    float2 attn[NB][DM];
    float2 lsum[SROW0][LSTRIDE];
    uint32_t tstart[32];
    uint32_t score[NPOOL][32];
};
constexpr int STATE_V4 = ((sizeof(State) / 32 + NQ_CTAS - 1) / NQ_CTAS) * 2;
static_assert(sizeof(State) % 32 == 0, "State is cleared in whole sectors");
static_assert(sizeof(Early) == 56 * 16, "an Early entry is cleared by 56 threads");
constexpr uint32_t X_O = 0;
constexpr uint32_t X_H = X_O + (NBH - SROW0 + 4 * (OREP - 1)) * 1280;
constexpr uint32_t X_A = X_H + NB * DM * 2;
constexpr uint32_t X_P = X_A + NB * FF * 2;
constexpr uint32_t X_END = X_P + 4096;
static_assert(X_END <= 16 * 4096 && (SROW0 <= NBH - 4 || OREP == 1) && SROW0 >= RED0, "");
struct Scratch {
    unsigned char sided[16][2][4096];
    unsigned work[64];
    unsigned cnt_z[32];
    Early early[NBH];
    State st;
    float4 ring[RING][UPB][64];
};
constexpr size_t PAGE = 2u << 20;
static_assert(sizeof(Scratch) <= PAGE, "scratch must fit one page");
__device__ __align__(128) unsigned char g_raw[2 * PAGE];
__device__ __forceinline__ Scratch* scratch() {
    return reinterpret_cast<Scratch*>((reinterpret_cast<uintptr_t>(g_raw) + PAGE - 1) & ~(uintptr_t)(PAGE - 1));
}
template <typename T> __device__ __forceinline__ T* sided(int side, uint32_t x) {
    const uint32_t pair = (x >> 8) & 15;
    return reinterpret_cast<T*>(&scratch()->sided[pair][(side ^ pair ^ (pair >> 3)) & 1][((x >> 12) << 8) + (x & 255)]);
}
template <typename T> __device__ __forceinline__ T* other_side(T* p) { return reinterpret_cast<T*>(reinterpret_cast<uintptr_t>(p) ^ 4096); }
#define g_early scratch()->early
#define g_st scratch()->st
#define g_ring scratch()->ring
#define g_cnt_z scratch()->cnt_z
#define g_work scratch()->work
#define TS(i)
#define TSW(i)
#define TS2(i)
#define TSI(n, i)
#define PH(i)
#define CK(i, dep)
#define ARR()
#define PROG(u)

__device__ __forceinline__ uint32_t s2u(const void* p) { return (uint32_t)__cvta_generic_to_shared(p); }
__device__ __forceinline__ void mbar_init(uint32_t bar, int cnt) {
    asm volatile("mbarrier.init.shared::cta.b64 [%0], %1;" :: "r"(bar), "r"(cnt) : "memory");
}
__device__ __forceinline__ void mbar_expect_tx(uint32_t bar, uint32_t bytes) {
    asm volatile("mbarrier.arrive.expect_tx.shared::cta.b64 _, [%0], %1;" :: "r"(bar), "r"(bytes) : "memory");
}
__device__ __forceinline__ void mbar_wait(uint32_t bar, uint32_t parity) {
    asm volatile("{\n.reg .pred p;\n.reg .u32 n;\nmov.u32 n, 0;\nWAIT_LOOP:\n"
                 "mbarrier.try_wait.parity.shared::cta.b64 p, [%0], %1;\n"
                 "@p bra WAIT_DONE;\nadd.u32 n, n, 1;\nsetp.lt.u32 p, n, %2;\n@p bra WAIT_LOOP;\nWAIT_DONE:\n}"
                 :: "r"(bar), "r"(parity), "n"(SPIN_MAX) : "memory");
}
__device__ __forceinline__ void tma_tile(uint32_t dst, const CUtensorMap* tm, int row, uint32_t bar, uint64_t pol) {
    asm volatile("cp.async.bulk.tensor.2d.shared::cluster.global.mbarrier::complete_tx::bytes.L2::cache_hint "
                 "[%0], [%1, {%3, %4}], [%2], %5;"
                 :: "r"(dst), "l"(tm), "r"(bar), "r"(0), "r"(row), "l"(pol) : "memory");
}
__device__ __forceinline__ void request_tile(uint32_t dst, const CUtensorMap* tm, int unit, uint32_t bar, uint64_t pol) {
    asm volatile("{\n.reg .pred p;\nelect.sync _|p, 0xffffffff;\n"
                 "@p mbarrier.arrive.expect_tx.shared::cta.b64 _, [%2], %6;\n"
                 "@p cp.async.bulk.tensor.2d.shared::cluster.global.mbarrier::complete_tx::bytes.L2::cache_hint "
                 "[%0], [%1, {%3, %4}], [%2], %5;\n}"
                 :: "r"(dst), "l"(tm), "r"(bar), "r"(0), "r"(unit * TILE_ROWS), "l"(pol), "n"(TILE_BYTES) : "memory");
}
__device__ __forceinline__ uint32_t now_ns() { uint32_t t; asm volatile("mov.u32 %0, %%globaltimer_lo;" : "=r"(t)); return t; }
__device__ __forceinline__ uint32_t now_clk() { uint32_t t; asm volatile("mov.u32 %0, %%clock;" : "=r"(t)); return t; }
__device__ __forceinline__ void wait_clk(uint32_t t) { while (__any_sync(0xffffffffu, (int)(now_clk() - t) < 0)) {} }
constexpr uint64_t EVICT_FIRST = 0x12F0000000000000ull, EVICT_NORMAL = 0x1000000000000000ull;
__device__ __forceinline__ void request_box(uint32_t dst, const CUtensorMap* tm, int col, int row, uint32_t bar, uint64_t pol) {
    asm volatile("{\n.reg .pred p;\nelect.sync _|p, 0xffffffff;\n"
                 "@p cp.async.bulk.tensor.2d.shared::cluster.global.mbarrier::complete_tx::bytes.L2::cache_hint [%0], [%1, {%3, %4}], [%2], %5;\n}"
                 :: "r"(dst), "l"(tm), "r"(bar), "r"(col), "r"(row), "l"(pol) : "memory");
}
__device__ __forceinline__ uint32_t lds32(uint32_t addr) {
    uint32_t v;
    asm volatile("ld.shared.u32 %0, [%1];" : "=r"(v) : "r"(addr) : "memory");
    return v;
}
__device__ __forceinline__ void ldsm4(uint32_t (&r)[4], uint32_t addr) {
    asm volatile("ldmatrix.sync.aligned.m8n8.x4.shared.b16 {%0,%1,%2,%3}, [%4];"
                 : "=r"(r[0]), "=r"(r[1]), "=r"(r[2]), "=r"(r[3]) : "r"(addr) : "memory");
}
__device__ __forceinline__ void ldsm4t(uint32_t (&r)[4], uint32_t addr) {
    asm volatile("ldmatrix.sync.aligned.m8n8.x4.trans.shared.b16 {%0,%1,%2,%3}, [%4];"
                 : "=r"(r[0]), "=r"(r[1]), "=r"(r[2]), "=r"(r[3]) : "r"(addr) : "memory");
}
__device__ __forceinline__ void mma16816(float (&c)[4], const uint32_t (&a)[4], uint32_t b0, uint32_t b1) {
    asm volatile("mma.sync.aligned.m16n8k16.row.col.f32.bf16.bf16.f32 {%0,%1,%2,%3}, {%4,%5,%6,%7}, {%8,%9}, {%0,%1,%2,%3};"
                 : "+f"(c[0]), "+f"(c[1]), "+f"(c[2]), "+f"(c[3])
                 : "r"(a[0]), "r"(a[1]), "r"(a[2]), "r"(a[3]), "r"(b0), "r"(b1));
}
__device__ __forceinline__ uint4 ld_relaxed_v4(const void* p) {
    uint4 v;
    asm volatile("ld.relaxed.gpu.global.v4.u32 {%0,%1,%2,%3}, [%4];" : "=r"(v.x), "=r"(v.y), "=r"(v.z), "=r"(v.w) : "l"(p) : "memory");
    return v;
}
__device__ __forceinline__ float4 ld_relaxed_f4(const void* p) {
    float4 v;
    asm volatile("ld.relaxed.gpu.global.v4.f32 {%0,%1,%2,%3}, [%4];" : "=f"(v.x), "=f"(v.y), "=f"(v.z), "=f"(v.w) : "l"(p) : "memory");
    return v;
}
__device__ __forceinline__ float2 ld_relaxed_f2(const void* p) {
    float2 v;
    asm volatile("ld.relaxed.gpu.global.v2.f32 {%0,%1}, [%2];" : "=f"(v.x), "=f"(v.y) : "l"(p) : "memory");
    return v;
}
__device__ __forceinline__ float4 ld_relaxed_b128(const void* p) {
    float4 v;
    asm volatile("{\n.reg .b128 t;\n.reg .b64 a, b;\nld.relaxed.gpu.global.b128 t, [%4];\nmov.b128 {a, b}, t;\n"
                 "mov.b64 {%0, %1}, a;\nmov.b64 {%2, %3}, b;\n}" : "=f"(v.x), "=f"(v.y), "=f"(v.z), "=f"(v.w) : "l"(p) : "memory");
    return v;
}
__device__ __forceinline__ void st_relaxed_b128(void* p, float x, float y, float z, float w) {
    asm volatile("{\n.reg .b128 t;\n.reg .b64 a, b;\nmov.b64 a, {%1, %2};\nmov.b64 b, {%3, %4};\nmov.b128 t, {a, b};\n"
                 "st.relaxed.gpu.global.b128 [%0], t;\n}" :: "l"(p), "f"(x), "f"(y), "f"(z), "f"(w) : "memory");
}
__device__ __forceinline__ unsigned ld_acquire(const unsigned* p) {
    unsigned v;
    asm volatile("ld.acquire.gpu.global.u32 %0, [%1];" : "=r"(v) : "l"(p) : "memory");
    return v;
}
__device__ __forceinline__ void st_relaxed(void* p, uint32_t v) {
    asm volatile("st.relaxed.gpu.global.u32 [%0], %1;" :: "l"(p), "r"(v) : "memory");
}
__device__ __forceinline__ void red_f2(float* p, float a, float b) {
    asm volatile("red.relaxed.gpu.global.add.v2.f32 [%0], {%1,%2};" :: "l"(p), "f"(a), "f"(b) : "memory");
}
__device__ __forceinline__ void red_f4(float* p, float a, float b, float c, float d) {
    asm volatile("red.relaxed.gpu.global.add.v4.f32 [%0], {%1,%2,%3,%4};" :: "l"(p), "f"(a), "f"(b), "f"(c), "f"(d) : "memory");
}
__device__ __forceinline__ void draw(int& ticket, unsigned* ctr, bool pred) {
    asm volatile("{\n.reg .pred p;\nsetp.ne.u32 p, %2, 0;\n@p atom.relaxed.gpu.global.inc.u32 %0, [%1], 0x7fffffff;\n}"
                 : "+r"(ticket) : "l"(ctr), "r"((uint32_t)pred) : "memory");
}
__device__ __forceinline__ void red_release(unsigned* p) {
    asm volatile("red.release.gpu.global.add.u32 [%0], 1;" :: "l"(p) : "memory");
}
__device__ __forceinline__ uint32_t ld_relaxed_u32(const void* p) {
    uint32_t v;
    asm volatile("ld.relaxed.gpu.global.u32 %0, [%1];" : "=r"(v) : "l"(p) : "memory");
    return v;
}
__device__ __forceinline__ float rcp_approx(float v) {
    float r;
    asm("rcp.approx.ftz.f32 %0, %1;" : "=f"(r) : "f"(v));
    return r;
}
__device__ __forceinline__ float sigmoid_approx(float v) {
    float e;
    asm("ex2.approx.ftz.f32 %0, %1;" : "=f"(e) : "f"(v * -1.4426950408889634f));
    return rcp_approx(1.0f + e);
}
__device__ __forceinline__ float sqrt_approx(float v) {
    float r;
    asm("sqrt.approx.ftz.f32 %0, %1;" : "=f"(r) : "f"(v));
    return r;
}
__device__ __forceinline__ uint2 ld_relaxed_v2(const void* p) {
    uint2 v;
    asm volatile("ld.relaxed.gpu.global.v2.u32 {%0,%1}, [%2];" : "=r"(v.x), "=r"(v.y) : "l"(p) : "memory");
    return v;
}
__device__ __forceinline__ void wait_count(const unsigned* p, unsigned target) {
#pragma unroll 1
    for (int it = 0; it < SPIN_MAX; it++) {
        if (ld_acquire(p) >= target) break;
        __nanosleep(400);
    }
}
__device__ __forceinline__ float4* oacc_at(int side, int row, int grp) {
    return row >= SROW0 ? sided<float4>(side, X_O + (row - SROW0) * 1280 + grp * 16) : &g_st.oacc[row][grp];
}
__device__ __forceinline__ float2* lsum_at(int side, int row) {
    return row >= SROW0 ? sided<float2>(side, X_O + (row - SROW0) * 1280 + 1024) : g_st.lsum[row];
}
__device__ __forceinline__ void wait_row(int side, int bh, float n) {
    const float2* l = lsum_at(side, bh);
#pragma unroll 1
    for (int it = 0; it < SPIN_MAX; it++) {
        const float c = ld_relaxed_f2(l).y;
        if (c >= n) break;
        if (c == 0.f) __nanosleep(600);
    }
}
__device__ __forceinline__ void wait_row_o(int side, int bh, float n) {
    wait_row(side, bh, n);
    if (bh >= RED0) return;
#pragma unroll 1
    for (int it = 0; it < SPIN_MAX; it++) {
        if (__uint_as_float(ld_relaxed_u32(&g_st.oacc[bh][0].w)) == UPB) break;
        __nanosleep(300);
    }
}
__device__ __forceinline__ void spin_ns(int ns) {
    const long long t0 = clock64();
    while (clock64() - t0 < (long long)ns * 2) {}
}
__device__ __forceinline__ uint32_t pack_bf16(float lo, float hi) {
    uint32_t r;
    asm("cvt.rn.bf16x2.f32 %0, %1, %2;" : "=r"(r) : "f"(hi), "f"(lo));
    return r;
}
__device__ __forceinline__ float bf16r(float v) { return __uint_as_float(pack_bf16(0.f, v)); }
__device__ __forceinline__ uint32_t pack_neg(float lo, float hi) {
    const uint32_t w = pack_bf16(-lo, -hi);
    return w ? w : 0x80008000u;
}
__device__ __forceinline__ float lo_f(uint32_t v) { return __uint_as_float(v << 16); }
__device__ __forceinline__ float hi_f(uint32_t v) { return __uint_as_float(v & 0xffff0000u); }
__device__ __forceinline__ float warp_sum(float v) {
#pragma unroll
    for (int o = 16; o; o >>= 1) v += __shfl_xor_sync(0xffffffffu, v, o);
    return v;
}
__device__ __forceinline__ void layernorm20(float (&v)[20]) {
    float s = 0.f;
#pragma unroll
    for (int i = 0; i < 20; i++) s += v[i];
    const float mean = warp_sum(s) * (1.0f / DM);
    float q = 0.f;
#pragma unroll
    for (int i = 0; i < 20; i++) { const float d = v[i] - mean; q += d * d; }
    const float var = bf16r(warp_sum(q) * (1.0f / DM));
    const float m = bf16r(mean);
    const float rden = 1.0f / bf16r(sqrtf(bf16r(var + 1e-5f)));
#pragma unroll
    for (int i = 0; i < 20; i++) v[i] = bf16r(bf16r(v[i] - m) * rden);
}

__device__ __forceinline__ float sel4(int j, float a, float b, float c, float d) {
    float lo, hi, r;
    asm("{\n.reg .pred p;\nsetp.ne.s32 p, %3, 0;\nselp.f32 %0, %2, %1, p;\n}" : "=f"(lo) : "f"(a), "f"(b), "r"(j & 1));
    asm("{\n.reg .pred p;\nsetp.ne.s32 p, %3, 0;\nselp.f32 %0, %2, %1, p;\n}" : "=f"(hi) : "f"(c), "f"(d), "r"(j & 1));
    asm("{\n.reg .pred p;\nsetp.ne.s32 p, %3, 0;\nselp.f32 %0, %2, %1, p;\n}" : "=f"(r) : "f"(lo), "f"(hi), "r"(j & 2));
    return r;
}
template <typename T> __device__ __forceinline__ void pin(T*& p) { asm volatile("" : "+l"(p)); }
__device__ __forceinline__ void pin(uint32_t& v) { asm volatile("" : "+r"(v)); }
__device__ __forceinline__ void pin(float& v) { asm volatile("" : "+f"(v)); }
__device__ __forceinline__ uint32_t after(uint32_t n, float v) {
    asm volatile("{\n.reg .pred p;\nsetp.eq.u32 p, %1, 0x7fc1a5a5;\n@p add.u32 %0, %0, 32;\n}" : "+r"(n) : "r"(__float_as_uint(v)));
    return n;
}
__device__ __forceinline__ float2 lds64f(uint32_t addr) {
    float2 v;
    asm volatile("ld.shared.v2.f32 {%0,%1}, [%2];" : "=f"(v.x), "=f"(v.y) : "r"(addr) : "memory");
    return v;
}
__device__ __forceinline__ float4 lds128f(uint32_t addr) {
    float4 v;
    asm volatile("ld.shared.v4.f32 {%0,%1,%2,%3}, [%4];" : "=f"(v.x), "=f"(v.y), "=f"(v.z), "=f"(v.w) : "r"(addr) : "memory");
    return v;
}
__device__ __forceinline__ void sts64f(uint32_t addr, float a, float b, bool pred) {
    asm volatile("{\n.reg .pred p;\nsetp.ne.u32 p, %3, 0;\n@p st.shared.v2.f32 [%0], {%1,%2};\n}" :: "r"(addr), "f"(a), "f"(b), "r"((uint32_t)pred) : "memory");
}
__device__ __forceinline__ void lds128_if(uint4& v, uint32_t addr, bool pred) {
    asm volatile("{\n.reg .pred p;\nsetp.ne.u32 p, %5, 0;\n@p ld.shared.v4.u32 {%0,%1,%2,%3}, [%4];\n}"
                 : "+r"(v.x), "+r"(v.y), "+r"(v.z), "+r"(v.w) : "r"(addr), "r"((uint32_t)pred) : "memory");
}
__device__ __forceinline__ void sts32f(uint32_t addr, float v) { asm volatile("st.shared.f32 [%0], %1;" :: "r"(addr), "f"(v) : "memory"); }
template <int ID> __device__ __forceinline__ void fin_arrive() { asm volatile("bar.arrive %0, 288;" :: "n"(ID) : "memory"); }
template <int ID> __device__ __forceinline__ void fin_sync() { asm volatile("bar.sync %0, 288;" :: "n"(ID) : "memory"); }
template <int ID> __device__ __forceinline__ void fin_sync(uint32_t n) { asm volatile("bar.sync %0, %1;" :: "n"(ID), "r"(n) : "memory"); }
__device__ __forceinline__ float2 sum8(uint32_t addr) {
    float2 t[8];
#pragma unroll
    for (int w = 0; w < 8; w++) t[w] = lds64f(addr + w * 128);
    return make_float2(((t[0].x + t[1].x) + (t[2].x + t[3].x)) + ((t[4].x + t[5].x) + (t[6].x + t[7].x)),
                       ((t[0].y + t[1].y) + (t[2].y + t[3].y)) + ((t[4].y + t[5].y) + (t[6].y + t[7].y)));
}
__device__ __forceinline__ float4 sum4x4(uint32_t addr) {
    float4 t[4];
#pragma unroll
    for (int w = 0; w < 4; w++) t[w] = lds128f(addr + w * 128);
    return make_float4((t[0].x + t[1].x) + (t[2].x + t[3].x), (t[0].y + t[1].y) + (t[2].y + t[3].y),
                       (t[0].z + t[1].z) + (t[2].z + t[3].z), (t[0].w + t[1].w) + (t[2].w + t[3].w));
}
template <int NJ>
__device__ __forceinline__ void load_o(uint32_t (&ob)[3 * NJ][2], int side, int bh, int J0, int j) {
    float4 v[NJ][4];
    float2 l;
#pragma unroll 1
    for (int it = 0; it < SPIN_MAX; it++) {
#pragma unroll
        for (int J = 0; J < NJ; J++) {
#pragma unroll
            for (int e = 0; e < 4; e++) v[J][e] = ld_relaxed_f4(oacc_at(side, bh, (J0 + J) * 16 + j) + e * 4);
        }
        l = ld_relaxed_f2(lsum_at(side, bh));
        bool ok = l.y == UPB;
#pragma unroll
        for (int J = 0; J < NJ; J++) {
#pragma unroll
            for (int e = 0; e < 4; e++) ok &= v[J][e].w == UPB;
        }
        if (__all_sync(0xffffffffu, ok)) break;
    }
    const float rl = __fdividef(1.0f, l.x);
#pragma unroll
    for (int J = 0; J < NJ; J++) {
        ob[3 * J][0] = pack_bf16(v[J][0].x * rl, v[J][1].x * rl);     ob[3 * J][1] = pack_bf16(v[J][2].x * rl, v[J][3].x * rl);
        ob[3 * J + 1][0] = pack_bf16(v[J][0].y * rl, v[J][1].y * rl); ob[3 * J + 1][1] = pack_bf16(v[J][2].y * rl, v[J][3].y * rl);
        ob[3 * J + 2][0] = pack_bf16(v[J][0].z * rl, v[J][1].z * rl); ob[3 * J + 2][1] = pack_bf16(v[J][2].z * rl, v[J][3].z * rl);
    }
}
__device__ __forceinline__ void aux_sync() { asm volatile("bar.sync 1, 256;" ::: "memory"); }

__global__ void __launch_bounds__(NTHREADS, 1)
fused_decode_kernel(const __grid_constant__ Params p) {
    extern __shared__ __align__(1024) unsigned char smem[];
    const uint32_t sb = s2u(smem);
    const int tid = threadIdx.x, warp = __shfl_sync(0xffffffffu, tid >> 5, 0), lane = tid & 31;
    const int cta = blockIdx.x;
    constexpr int grid = NCTAS;
    const int g = lane >> 2, j = lane & 3;
    const int gidx = cta < NF_CTAS && (cta >> 2) * 5 % 12 < 5 ? (cta >> 2) * 5 / 12 * 4 + (cta & 3) : -1;

    TS(0);
    if (warp == 4 && cta < NQ_CTAS) {
        asm volatile("{\n.reg .pred p;\nelect.sync _|p, 0xffffffff;\n"
                     "@p mbarrier.init.shared::cta.b64 [%0], 1;\n"
                     "@p fence.mbarrier_init.release.cluster;\n"
                     "@p mbarrier.arrive.expect_tx.shared::cta.b64 _, [%0], 61440;\n}" :: "r"(sb + BAR_WQ) : "memory");
#pragma unroll
        for (int i = 0; i < 4; i++) request_box(sb + SM_WQ + i * 15360, &p.wq, cta * 48, i * 160, sb + BAR_WQ, EVICT_NORMAL);
    }
    if (tid == 160) {
#pragma unroll
        for (int w = 0; w < NWORK; w++) mbar_init(sb + BAR_KV + w * 8, 1);
        mbar_init(sb + BAR_W, 1);
#pragma unroll
        for (int w = 0; w < 12; w++) mbar_init(sb + BAR_G + w * 8, 1);
        asm volatile("fence.mbarrier_init.release.cluster;" ::: "memory");
    }
    __syncthreads();
    if (warp == NAUX + NWORK + 1) {
        uint32_t t = now_clk() + 2 * WO_AT_NS;
        if (lane == 0) mbar_expect_tx(sb + BAR_W, cta < NE_CTAS ? 61440 : 49152);
        const int col = cta < NE_CTAS ? (cta & 3) * 160 : (cta - NE_CTAS) * 32, row = cta < NE_CTAS ? (cta >> 2) * DH : 28 * DH;
#pragma unroll 1
        for (int r = 0; r < DH; r += WO_ROWS) {
            wait_clk(t);
#pragma unroll 1
            for (int i = 0; i < (cta < NE_CTAS ? 5 : 4); i++)
                request_box(sb + SM_A + i * 12288 + r * 64, &p.wo, cta < NE_CTAS ? col + i * 32 : col, (cta < NE_CTAS ? row : row + i * DH) + r, sb + BAR_W, EVICT_FIRST);
            t += 2 * WO_GAP_NS;
        }
        if (cta >= NF_CTAS) return;
        if (lane < (gidx < 0 ? 4 : 12)) mbar_expect_tx(sb + BAR_G + lane * 8, lane < 4 ? 10240 : 6144);
        asm volatile("bar.sync 9, 288;" ::: "memory");
        asm volatile("fence.proxy.async.shared::cta;" ::: "memory");
#pragma unroll 1
        for (int it = 0; it < SPIN_MAX; it++) {
            t = ld_relaxed_u32(g_st.tstart);
            if (__all_sync(0xffffffffu, t != 0)) break;
            __nanosleep(400);
        }
#pragma unroll 1
        for (int it = 0; it < SPIN_MAX; it++) if (__all_sync(0xffffffffu, t - now_ns() > 2 * TRIG_NS)) break;
        TSW(11);
        t = now_clk();
#pragma unroll 1
        for (int i = 0; i < 8; i++) {
            request_box(sb + SM_G + i * 2560, &p.wg, cta * 16, i * 80, sb + BAR_G + (i >> 1) * 8, EVICT_NORMAL);
            request_box(sb + SM_G + 20480 + i * 2560, &p.wu, cta * 16, i * 80, sb + BAR_G + (i >> 1) * 8, EVICT_NORMAL);
            wait_clk(t += GCLK);
        }
        if (gidx < 0) return;
#pragma unroll 1
        for (int i = 0; i < 8; i++) {
            request_box(sb + SM_D + i * 6144, &p.wd, gidx * 16, i * 192, sb + BAR_D + i * 8, EVICT_NORMAL);
            wait_clk(t += DCLK);
        }
        return;
    }
    if (warp == NAUX + NWORK) {
        if (cta < NQ_CTAS) {
#pragma unroll
            for (int i = lane; i < STATE_V4; i += 32)
                if (cta * STATE_V4 + i < (int)(sizeof(State) / 16)) reinterpret_cast<uint4*>(&g_st)[cta * STATE_V4 + i] = make_uint4(0u, 0u, 0u, 0u);
            if (cta * 512 < X_END) {
                uint4* z = sided<uint4>(0, cta * 512 + lane * 16);
                *z = make_uint4(0u, 0u, 0u, 0u);
                *other_side(z) = make_uint4(0u, 0u, 0u, 0u);
            }
            __syncwarp();
            if (lane == 0) red_release(g_cnt_z);
        }
        if (lane == 0) { TS2(2); wait_count(g_cnt_z, NQ_CTAS); TS2(29); }
        __syncwarp();
        asm volatile("bar.arrive 2, %0;" :: "n"((NWORK + 1) * 32) : "memory");
        uint32_t rtt[2] = {0xffffffffu, 0xffffffffu};
        if (lane == 0) {
#pragma unroll 1
            for (int r = 0; r < 2 * NPROBE; r++) {
                int v = 0;
                uint32_t t1 = 0;
                unsigned* ctr = sided<unsigned>(r & 1, X_P + ((cta * 32 + (r >> 1) * 768) & 4095));
                pin(ctr);
                const uint32_t t0 = now_clk();
                draw(v, ctr, true);
                asm volatile("{\n.reg .pred q;\nsetp.ge.s32 q, %1, 0;\n@q mov.u32 %0, %%clock;\n}" : "+r"(t1) : "r"(v) : "memory");
                if (r & 1) rtt[1] = min(rtt[1], t1 - t0); else rtt[0] = min(rtt[0], t1 - t0);
            }
            sts32f(sb + SM_SIDE, __int_as_float(rtt[1] < rtt[0]));
        }
        const int side = __shfl_sync(0xffffffffu, rtt[1] < rtt[0], 0);
        fin_arrive<3>();
        int job = cta;
        auto sum_rows = [&](int row_end) {
#pragma unroll 1
            for (; job < 8 * min(row_end, RED0); job += NCTAS) {
                const int row = job >> 3, grp = (job & 7) * 8 + (lane & 7);
                if (lane == 0) wait_row(side, row, UPB);
                __syncwarp();
                const float4* src = &g_ring[row % RING][lane >> 3][grp];
                float sx = 0.f, sy = 0.f, sz = 0.f;
#pragma unroll 1
                for (int i = 0; i < 2; i++, src += 64 * 64) {
                    float4 v[16];
#pragma unroll 1
                    for (int it = 0; it < SPIN_MAX; it++) {
                        bool ok = true;
#pragma unroll
                        for (int k = 0; k < 16; k++) v[k] = ld_relaxed_b128(src + k * 4 * 64);
#pragma unroll
                        for (int k = 0; k < 16; k++) ok &= v[k].w == (float)(row + 1);
                        if (__all_sync(0xffffffffu, ok)) break;
                    }
#pragma unroll
                    for (int k = 0; k < 16; k++) { sx += v[k].x; sy += v[k].y; sz += v[k].z; }
                }
#pragma unroll
                for (int o = 8; o < 32; o <<= 1) {
                    sx += __shfl_xor_sync(0xffffffffu, sx, o); sy += __shfl_xor_sync(0xffffffffu, sy, o); sz += __shfl_xor_sync(0xffffffffu, sz, o);
                }
                if (lane < 8) st_relaxed_b128(&g_st.oacc[row][grp], sx, sy, sz, UPB);
            }
        };
        if (cta >= NE_CTAS) {
            const int col = (cta - NE_CTAS) * 32 + 2 * (lane & 15);
            uint32_t part = sb + SM_RED + (lane & 15) * 8;
#pragma unroll 1
            for (int b = 0; b < NB; b++) {
                const uint32_t xv = *reinterpret_cast<const uint32_t*>(p.x + b * DM + col);
                uint32_t* dst = sided<uint32_t>(lane >> 4, X_H + b * (DM * 2) + 4 * ((col >> 5) * 16 + (col & 6) * 2 + ((col >> 3) & 3)));
                sum_rows((b + 1) * NH);
                if (lane == 0) wait_row(side, b * NH + 28, 1);
                __syncwarp();
                float4 early;
#pragma unroll 1
                for (int it = 0; it < SPIN_MAX; it++) {
                    early = ld_relaxed_f4(&g_st.attn[b][col]);
                    if (__all_sync(0xffffffffu, early.y == NE_CTAS / 4 && early.w == NE_CTAS / 4)) break;
                }
                float x0 = lo_f(xv), x1 = hi_f(xv);
                pin(dst); pin(part); pin(x0); pin(x1);
                fin_sync<4>();
                CK(2, lds32(sb + SM_RED));
                const float2 late = sum8(part);
                const uint32_t hv = pack_neg(x0 + bf16r(early.x + late.x), x1 + bf16r(early.z + late.y));
                st_relaxed(dst, hv);
                CK(3, 0);
                if (lane == 0) TS2(15);
                fin_sync<5>();
            }
        } else if (cta < NF_CTAS) {
            uint32_t wr[10];
            float wsum = 0.f;
#pragma unroll
            for (int i = 0; i < 10; i++) {
                const int w = 4 * lane + 128 * (i >> 2) + (i & 3) - (i >= 8 ? 2 * lane : 0);
                wr[i] = *reinterpret_cast<const uint32_t*>(p.wr + (w >> 4) * 32 + (w & 3) * 8 + ((w >> 1) & 6));
                wsum += lo_f(wr[i]) + hi_f(wr[i]);
            }
            wsum = warp_sum(wsum);
            const int lb = lane >> 3, lc = lane & 7;
            uint32_t part = sb + SM_RED + lb * FPITCH + lc * 16, cpart = sb + SM_RED + 4 * FPITCH + lc * 16;
            uint32_t ypart = sb + SM_RED2 + (lb >> 1) * 160 + lc * 16 + (lb & 1) * 8;
            uint32_t* dst = sided<uint32_t>(side ^ 1, X_A + cta * 128 + (lane ^ (cta & 1) * 2) * 4);
            uint32_t* dst2 = other_side(dst);
            __nv_bfloat16* out = p.out + lb * DM + gidx * 16 + lc;
            float nmean_l = 0.f, rden_l = 0.f, sig_l = 0.f;
#pragma unroll 1
            for (int b = 0; b < NB; b++) {
                const uint32_t hx = X_H + b * (DM * 2), hrow = sb + SM_X + b * HPITCH;
                const uint4 *src0 = sided<uint4>(side, hx + 16 * lane), *src1 = sided<uint4>(side, hx + 512 + 16 * lane);
                const uint2* src2 = sided<uint2>(side, hx + 1024 + 8 * lane);
                sum_rows((b + 1) * NH);
                pin(dst); pin(dst2); pin(src0); pin(src1); pin(src2); pin(part); pin(cpart); pin(ypart); pin(out);
                if (lane == 0) wait_row(side, b * NH + NH - 1, 1);
                __syncwarp();
                uint4 h0, h1;
                uint2 h2;
#pragma unroll 1
                for (int it = 0; it < SPIN_MAX; it++) {
                    h0 = ld_relaxed_v4(src0);
                    h1 = ld_relaxed_v4(src1);
                    h2 = ld_relaxed_v2(src2);
                    asm volatile("st.shared.v4.u32 [%0], {%1,%2,%3,%4};" :: "r"(hrow + lane * 16), "r"(h0.x), "r"(h0.y), "r"(h0.z), "r"(h0.w) : "memory");
                    asm volatile("st.shared.v4.u32 [%0], {%1,%2,%3,%4};" :: "r"(hrow + 512 + lane * 16), "r"(h1.x), "r"(h1.y), "r"(h1.z), "r"(h1.w) : "memory");
                    asm volatile("st.shared.v2.u32 [%0], {%1,%2};" :: "r"(hrow + 1024 + lane * 8), "r"(h2.x), "r"(h2.y) : "memory");
                    const uint32_t lo = min(min(min(h0.x, h0.y), min(h0.z, h0.w)), min(min(min(h1.x, h1.y), min(h1.z, h1.w)), min(h2.x, h2.y)));
                    const bool ok = __all_sync(0xffffffffu, lo != 0) || it == SPIN_MAX - 1;
                    asm volatile("{\n.reg .pred p;\nsetp.ne.u32 p, %0, 0;\n@p bar.arrive 7, 288;\n}" :: "r"((uint32_t)ok) : "memory");
                    if (ok) break;
                }
                CK(4, h0.x);
                if (lane == 0) TS2(12);
                const uint32_t hw[10] = {h0.x, h0.y, h0.z, h0.w, h1.x, h1.y, h1.z, h1.w, h2.x, h2.y};
                float ma[4] = {}, mb[4] = {};
#pragma unroll
                for (int i = 0; i < 5; i++) {
                    const uint32_t a[4] = {hw[2 * i], 0x3f803f80u, hw[2 * i + 1], 0x3f803f80u};
                    mma16816((i & 1) ? mb : ma, a, hw[2 * i], hw[2 * i + 1]);
                }
                float m1 = (ma[2] + mb[2]) + (ma[3] + mb[3]), m2 = (g & 1) ? ma[1] + mb[1] : ma[0] + mb[0];
                m2 += __shfl_xor_sync(0xffffffffu, m2, 4);
                m1 = (m1 + __shfl_xor_sync(0xffffffffu, m1, 1)) + (__shfl_xor_sync(0xffffffffu, m1, 2) + __shfl_xor_sync(0xffffffffu, m1, 3));
                m2 = (__shfl_sync(0xffffffffu, m2, 0) + __shfl_sync(0xffffffffu, m2, 9)) + (__shfl_sync(0xffffffffu, m2, 18) + __shfl_sync(0xffffffffu, m2, 27));
                CK(5, __float_as_uint(m2));
                fin_sync<4>();
                CK(6, lds32(part));
                const float4 d = sum4x4(part), cs = sum4x4(cpart);
                m1 *= 1.0f / DM;
                const float nmean = bf16r(m1);
                const float var = bf16r(fmaxf(fmaf(-m1, m1, m2 * (1.0f / DM)), 0.f));
                const float rden = rcp_approx(bf16r(sqrt_approx(bf16r(var + 1e-5f))));
                if (lb == b) { nmean_l = nmean; rden_l = rden; }
                const float g0 = bf16r(fmaf(nmean_l, cs.x, -d.x) * rden_l), g1 = bf16r(fmaf(nmean_l, cs.z, -d.z) * rden_l);
                const float u0 = bf16r(fmaf(nmean_l, cs.y, -d.y) * rden_l), u1 = bf16r(fmaf(nmean_l, cs.w, -d.w) * rden_l);
                const uint32_t av = pack_neg(bf16r(g0 * sigmoid_approx(g0)) * u0, bf16r(g1 * sigmoid_approx(g1)) * u1);
                asm volatile("{\n.reg .pred p;\nsetp.eq.u32 p, %3, 3;\n@p st.relaxed.gpu.global.u32 [%0], %2;\n@p st.relaxed.gpu.global.u32 [%1], %2;\n}"
                             :: "l"(dst), "l"(dst2), "r"(av), "r"(b) : "memory");
                CK(7, 0);
                if (lane == 0) TS2(14);
                if (gidx >= 0) {
                    fin_arrive<8>();
                    const float2 hw2 = lds64f(sb + SM_X + lb * HPITCH + ((gidx >> 1) * 16 + (lc & 6) * 2 + (gidx & 1) * 2) * 4);
                    const float nh0 = (lc & 1) ? hi_f(__float_as_uint(hw2.x)) : lo_f(__float_as_uint(hw2.x));
                    const float nh1 = (lc & 1) ? hi_f(__float_as_uint(hw2.y)) : lo_f(__float_as_uint(hw2.y));
                    float rr = 0.f;
#pragma unroll
                    for (int i = 0; i < 10; i++) rr = fmaf(lo_f(hw[i]), lo_f(wr[i]), fmaf(hi_f(hw[i]), hi_f(wr[i]), rr));
                    const float sig = bf16r(sigmoid_approx(bf16r((nmean * wsum - warp_sum(rr)) * rden)));
                    if (lb == b) sig_l = sig;
                    const float ln0 = bf16r(bf16r(nmean_l - nh0) * rden_l), ln1 = bf16r(bf16r(nmean_l - nh1) * rden_l);
                    fin_sync<6>(after(after(after(288, sig_l), ln0), ln1));
                    CK(10, lds32(ypart));
                    float2 t[16];
#pragma unroll
                    for (int i = 0; i < 16; i++) t[i] = lds64f(ypart + i * YPITCH);
#pragma unroll
                    for (int o = 1; o < 16; o <<= 1) {
#pragma unroll
                        for (int i = 0; i < 16; i += 2 * o) { t[i].x += t[i + o].x; t[i].y += t[i + o].y; }
                    }
                    const uint32_t ov = pack_bf16(bf16r(ln0 + bf16r(bf16r(-t[0].x) * sig_l)) - nh0, bf16r(ln1 + bf16r(bf16r(-t[0].y) * sig_l)) - nh1);
                    asm volatile("{\n.reg .pred p;\n.reg .b16 lo, hi;\nsetp.eq.u32 p, %2, 3;\nmov.b32 {lo, hi}, %1;\n"
                                 "@p st.global.u16 [%0], lo;\n@p st.global.u16 [%0 + 16], hi;\n}" :: "l"(out), "r"(ov), "r"(b) : "memory");
                    CK(11, 0);
                    if (lane == 0) TS2(13);
                }
                fin_sync<5>();
            }
            if (cta == 0 && lane == 0) { g_work[0] = 0; g_work[32] = 0; g_cnt_z[0] = 0; }
        } else {
            sum_rows(NBH);
        }
        return;
    }
    if (warp >= NAUX) {
        const int wk = warp - NAUX;
        const uint32_t bar = sb + BAR_KV + wk * 8;
        const uint32_t buf = sb + SM_KV + wk * TILE_BYTES;
        uint64_t pol;
        asm volatile("createpolicy.fractional.L2::evict_first.b64 %0, 1.0;" : "=l"(pol));
        const int nstatic = NWORK * grid;
        constexpr int POOL0 = NUNITS - NPOOL;
        int uk = wk * grid + cta;
        if (lane == 0) {
            spin_ns(K0_DELAY_NS + wk * K0_STEP_NS);
            mbar_expect_tx(bar, TILE_BYTES);
            tma_tile(buf, &p.k, uk * TILE_ROWS, bar, pol);
        }
        __syncwarp();
        uint32_t koff[3], voff[3];
        {
            const int r = lane & 7, hf = (lane >> 3) & 1;
            const int kkey = hf ? 8 + (r ^ 1) : r;
            const int vh = lane >> 4;
            const int vkey = ((r & 1) ? 8 : 0) + (vh ? (r ^ 1) : r);
#pragma unroll
            for (int b = 0; b < 3; b++) {
                const int rk = 3 * kkey + b, rv = 3 * vkey + b;
                koff[b] = buf + rk * 128 + (((lane >> 4) ^ (rk & 7)) << 4);
                voff[b] = buf + rv * 128 + ((hf ^ (rv & 7)) << 4);
            }
        }
        uint32_t phase = 0;
        uint4 qf[6];
        auto load_q = [&](int u) {
            const uint32_t* q = &g_early[u / UPB].q[j * 4];
#pragma unroll
            for (int i = 0; i < 6; i++) qf[i] = ld_relaxed_v4(q + i * 16);
        };
        load_q(uk);
        int uq[LAG];
        uint32_t sq[LAG];
#pragma unroll
        for (int i = 0; i < LAG; i++) { uq[i] = -1; sq[i] = 0; }
        uint4 mv = make_uint4(0u, 0u, 0u, 0u);
        float freed = UPB;
        while (true) {
            const int uv = uq[0];
            uint32_t sv = sq[0];
#pragma unroll
            for (int i = 0; i + 1 < LAG; i++) { uq[i] = uq[i + 1]; sq[i] = sq[i + 1]; }
            uq[LAG - 1] = uk;
            if (uk < NUNITS) {
                PH(7);
#pragma unroll 1
                for (int it = 0; it < SPIN_MAX; it++) {
                    uint32_t lo = 0xffffffffu;
#pragma unroll
                    for (int i = 0; i < 6; i++) lo = min(min(lo, min(qf[i].x, qf[i].y)), min(qf[i].z, qf[i].w));
                    if (__all_sync(0xffffffffu, lo != 0)) break;
                    __nanosleep(QNAP);
                    load_q(uk);
                }
                mbar_wait(bar, phase); phase ^= 1;
                PH(0); ARR();
                TSI(0, 16); TSI(1, 18);
                float acc[2][4][4] = {};
#pragma unroll
                for (int ks = 0; ks < 12; ks++) {
                    const uint4 qq = qf[ks >> 1];
                    const uint32_t b0 = (ks & 1) ? qq.z : qq.x, b1 = (ks & 1) ? qq.w : qq.y;
#pragma unroll
                    for (int mt = 0; mt < 4; mt++) {
                        uint32_t a[4];
                        ldsm4(a, (koff[ks >> 2] ^ ((ks & 3) << 5)) + mt * 6144);
                        mma16816(acc[ks & 1][mt], a, b0, b1);
                    }
                }
                PH(1);
                TSI(0, 17); TSI(1, 19);
                if (uv < NUNITS) request_tile(buf, uv >= 0 ? &p.v : &p.k, uv >= 0 ? uv : uk + nstatic, bar, pol);
                const float sa = sel4(j, acc[0][0][0], acc[0][1][0], acc[0][2][0], acc[0][3][0]) + sel4(j, acc[1][0][0], acc[1][1][0], acc[1][2][0], acc[1][3][0]);
                const float sc = sel4(j, acc[0][0][2], acc[0][1][2], acc[0][2][2], acc[0][3][2]) + sel4(j, acc[1][0][2], acc[1][1][2], acc[1][2][2], acc[1][3][2]);
                const uint32_t raw = pack_bf16(sa, sc);
                const float scale = -0.07216878364870322f;
                const uint32_t sk = pack_bf16(lo_f(raw) * scale, hi_f(raw) * scale);
                sq[LAG - 1] = sk;
                if (uk >= POOL0) st_relaxed(&g_st.score[uk - POOL0][lane], sk ? sk : 0x80008000u);
                int a = (int)(sk << 16), b = (int)(sk & 0xffff0000u);
                a ^= (a >> 31) & 0x7fff0000; b ^= (b >> 31) & 0x7fff0000;
                const int mx = __reduce_max_sync(0xffffffffu, max(a, b));
                if (lane == 0) st_relaxed(&g_early[uk / UPB].umax[uk % UPB], (uint32_t)mx | 1u);
            }
            if (uv < 0) {
                uk += nstatic;
                load_q(uk);
                continue;
            }
            if (uv >= NUNITS) break;
            const int bh = uv / UPB;
#pragma unroll 1
            for (int it = 0; it < SPIN_MAX; it++) {
                if (__all_sync(0xffffffffu, (mv.x & mv.y & mv.z & mv.w & 1u) && (uv < POOL0 || sv != 0) && freed == UPB)) break;
                mv = ld_relaxed_v4(&g_early[bh].umax[lane * 4]);
                if (bh >= RING && bh < RED0) freed = __uint_as_float(ld_relaxed_u32(&g_st.oacc[bh - RING][(lane & 7) * 8].w));
                if (uv >= POOL0) sv = ld_relaxed_u32(&g_st.score[uv - POOL0][lane]);
            }
            PH(2);
            int un = NUNITS, vn = 0;
            draw(un, g_work, uk < NUNITS && lane == 0);
            draw(vn, g_work + 32, uq[0] >= POOL0 && lane == 0);
            const uint32_t cdraw = now_clk();
            int mx = __reduce_max_sync(0xffffffffu, max(max((int)mv.x, (int)mv.y), max((int)mv.z, (int)mv.w))) & 0xffff0000;
            mx ^= (mx >> 31) & 0x7fff0000;
            const float m = __int_as_float(mx);
            const float l2e = 1.4426950408889634f;
            const uint32_t pp = pack_bf16(exp2f((lo_f(sv) - m) * l2e), exp2f((hi_f(sv) - m) * l2e));
            uint32_t pb[8];
#pragma unroll
            for (int t = 0; t < 4; t++) {
                pb[2 * t] = __shfl_sync(0xffffffffu, pp, 8 * j + t);
                pb[2 * t + 1] = __shfl_sync(0xffffffffu, pp, 8 * j + 4 + t);
            }
            float lacc[4] = {};
            const uint32_t ones[4] = {0x3f803f80u, 0x3f803f80u, 0x3f803f80u, 0x3f803f80u};
#pragma unroll
            for (int t = 0; t < 4; t++) mma16816(lacc, ones, pb[2 * t], pb[2 * t + 1]);
            PH(3);
            mbar_wait(bar, phase); phase ^= 1;
            PH(4); ARR();
            float acc[12][4] = {};
#pragma unroll
            for (int t = 0; t < 4; t++) {
#pragma unroll
                for (int mt = 0; mt < 12; mt++) {
                    uint32_t a[4];
                    ldsm4t(a, (voff[mt >> 2] ^ ((mt & 3) << 5)) + t * 6144);
                    mma16816(acc[mt], a, pb[2 * t], pb[2 * t + 1]);
                }
            }
            un = __shfl_sync(0xffffffffu, un, 0) + (LAG + 1) * nstatic;
            vn = __shfl_sync(0xffffffffu, vn, 0);
            if (uq[0] >= POOL0) uq[0] = POOL0 + vn;
            PH(5);
            if (lane == 0) PROG(un);
            if (un < NUNITS || uq[0] < NUNITS) request_tile(buf, un < NUNITS ? &p.k : &p.v, un < NUNITS ? un : uq[0], bar, pol);
            if (un < NUNITS) load_q(un);
            if (vn == VTRIG && lane == 0) st_relaxed(g_st.tstart, (now_ns() + TRIG_NS - min((now_clk() - cdraw) * 35u >> 6, TRIG_NS)) | 1u);
            float o[6];
#pragma unroll
            for (int e = 0; e < 6; e++) {
                const int q = e % 3, c = (e / 3) * 2;
                o[e] = sel4(j, acc[q][c], acc[3 + q][c], acc[6 + q][c], acc[9 + q][c]);
            }
            if (uv < nstatic) {
                asm volatile("bar.sync 2, %0;" :: "n"((NWORK + 1) * 32) : "memory");
                TSW(3);
            }
            const int grp = 16 * j + 4 * (g & 1) + (g >> 1);
            if (bh < RED0) {
                float4* dst = &g_ring[bh % RING][uv % UPB][grp];
                st_relaxed_b128(dst, o[0], o[1], o[2], (float)(bh + 1));
                st_relaxed_b128(dst + 8, o[3], o[4], o[5], (float)(bh + 1));
            }
            const int acc_row = bh >= NBH - 4 && uv % OREP ? bh + 4 * (uv % OREP) : bh;
            if (bh >= RED0) {
                float4* dst = oacc_at(0, acc_row, grp);
                red_f4(&dst->x, o[0], o[1], o[2], 1.f);
                red_f4(&dst[8].x, o[3], o[4], o[5], 1.f);
                if (bh >= SROW0) {
                    red_f4(&other_side(dst)->x, o[0], o[1], o[2], 1.f);
                    red_f4(&other_side(dst)[8].x, o[3], o[4], o[5], 1.f);
                }
            }
            if (lane < (bh >= SROW0 ? 2 : 1)) red_f2(&lsum_at(lane, acc_row)->x, lacc[0], 1.f);
            PH(6);
            if (uq[0] >= NUNITS && un >= NUNITS) break;
            uk = un;
            if (uq[0] < NUNITS) {
                const int nb = uq[0] / UPB;
                mv = ld_relaxed_v4(&g_early[nb].umax[lane * 4]);
                freed = nb >= RING && nb < RED0 ? __uint_as_float(ld_relaxed_u32(&g_st.oacc[nb - RING][(lane & 7) * 8].w)) : UPB;
                if (uq[0] >= POOL0) sq[0] = ld_relaxed_u32(&g_st.score[uq[0] - POOL0][lane]);
            }
        }
        TSW(4 + wk);
        return;
    }

    __nv_bfloat16* xs = reinterpret_cast<__nv_bfloat16*>(smem + SM_X);
    float* red = reinterpret_cast<float*>(smem + SM_RED);
    const int frow = (lane & 7) + ((lane >> 4) << 3), fcol = (lane >> 3) & 1;
    if (cta < NQ_CTAS) {
        uint2 xr[5];
        if (warp < NB) {
#pragma unroll
            for (int i = 0; i < 5; i++) xr[i] = *reinterpret_cast<const uint2*>(p.x + warp * DM + i * 128 + lane * 4);
        }
        TS(26);
        if (warp < NB) {
            float v[20];
#pragma unroll
            for (int i = 0; i < 5; i++) {
                v[4 * i] = lo_f(xr[i].x); v[4 * i + 1] = hi_f(xr[i].x); v[4 * i + 2] = lo_f(xr[i].y); v[4 * i + 3] = hi_f(xr[i].y);
            }
            layernorm20(v);
#pragma unroll
            for (int i = 0; i < 5; i++)
                *reinterpret_cast<uint2*>(xs + warp * XPITCH + i * 128 + lane * 4) =
                    make_uint2(pack_bf16(v[4 * i], v[4 * i + 1]), pack_bf16(v[4 * i + 2], v[4 * i + 3]));
        }
        TS(27);
        aux_sync();
        mbar_wait(sb + BAR_WQ, 0);
        TS(1);
        const uint32_t xfrag = sb + SM_X + ((g & 3) * XPITCH + 2 * j) * 2;
        float acc[3][4] = {};
#pragma unroll
        for (int s = 0; s < 5; s++) {
            const int ks = warp * 5 + s;
            const uint32_t b0 = lds32(xfrag + ks * 32), b1 = lds32(xfrag + ks * 32 + 16);
            const int row = ks * 16 + frow;
#pragma unroll
            for (int mt = 0; mt < 3; mt++) {
                uint32_t a[4];
                ldsm4t(a, sb + SM_WQ + (row * 6 + 2 * mt + fcol) * 16);
                mma16816(acc[mt], a, b0, b1);
            }
        }
        if (j < 2) {
#pragma unroll
            for (int mt = 0; mt < 3; mt++) {
                *reinterpret_cast<float2*>(red + (warp * 48 + mt * 16 + g) * 4 + 2 * j) = make_float2(acc[mt][0], acc[mt][1]);
                *reinterpret_cast<float2*>(red + (warp * 48 + mt * 16 + 8 + g) * 4 + 2 * j) = make_float2(acc[mt][2], acc[mt][3]);
            }
        }
        aux_sync();
        if (tid < 96) {
            const int b = tid & 3, cp = tid >> 2;
            float s0 = 0.f, s1 = 0.f;
#pragma unroll
            for (int w = 0; w < 8; w++) { s0 += red[(w * 48 + 2 * cp) * 4 + b]; s1 += red[(w * 48 + 2 * cp + 1) * 4 + b]; }
            const int h = cta >> 2, d = (cta & 3) * 48 + 2 * cp;
            const int ch = d >> 3, jj = (d & 7) >> 1;
            st_relaxed(&g_early[b * NH + h].q[(ch >> 2) * 16 + jj * 4 + (ch & 3)], pack_neg(s0, s1));
        }
        TS(28);
    }
    if (tid < 160) *reinterpret_cast<uint2*>(smem + SM_X + 4 * HPITCH + tid * 8) = make_uint2(0x3f803f80u, 0x3f803f80u);
    fin_sync<3>();
    const int side = lds32(sb + SM_SIDE);
    mbar_wait(sb + BAR_W, 0);
    TS(7);
    uint32_t part = sb + SM_RED + (warp * 32 + 8 * j + g) * 4;

#pragma unroll 1
    for (int b = 0; b < NB; b++) {
        if (cta >= NE_CTAS) {
            uint32_t a[6][2][4];
#pragma unroll
            for (int s = 0; s < 6; s++) {
                const int row = (warp * 6 + s) * 16 + frow;
#pragma unroll
                for (int mt = 0; mt < 2; mt++) ldsm4t(a[s][mt], sb + SM_A + (row * 4 + ((2 * mt + fcol) ^ ((row >> 1) & 3))) * 16);
            }
            const int bh = b * NH + 28 + (warp >> 1);
            const float4* osrc[OREP];
            const float2* lsrc[OREP];
#pragma unroll
            for (int c = 0; c < OREP; c++) {
                const int row = b == NB - 1 ? bh + 4 * c : bh;
                osrc[c] = oacc_at(side, row, (warp & 1) * 32 + lane);
                lsrc[c] = lsum_at(side, row);
                pin(osrc[c]); pin(lsrc[c]);
            }
            if (lane == 0) wait_row_o(side, bh, UPB * 3 / (4 * OREP));
            __syncwarp();
            float4 ov;
            float2 lv;
            pin(part);
#pragma unroll 1
            for (int it = 0; it < SPIN_MAX; it++) {
                float4 oc[OREP];
                float2 lc[OREP];
#pragma unroll
                for (int c = 0; c < OREP; c++) {
                    oc[c] = ld_relaxed_f4(osrc[c]);
                    lc[c] = ld_relaxed_f2(lsrc[c]);
                }
                ov = oc[0]; lv = lc[0];
                if (b == NB - 1) {
#pragma unroll
                    for (int c = 1; c < OREP; c++) {
                        ov.x += oc[c].x; ov.y += oc[c].y; ov.z += oc[c].z; ov.w += oc[c].w; lv.x += lc[c].x; lv.y += lc[c].y;
                    }
                }
                if (__all_sync(0xffffffffu, ov.w == UPB && lv.y == UPB)) break;
            }
            CK(0, __float_as_uint(ov.x));
            const float rl = rcp_approx(lv.x);
            const float px = __shfl_xor_sync(0xffffffffu, ov.x, 4), py = __shfl_xor_sync(0xffffffffu, ov.y, 4),
                        pz = __shfl_xor_sync(0xffffffffu, ov.z, 4);
            const uint32_t w[3] = {pack_bf16(ov.x * rl, px * rl), pack_bf16(ov.y * rl, py * rl), pack_bf16(ov.z * rl, pz * rl)};
            float acc[2][2][4] = {};
#pragma unroll
            for (int s = 0; s < 6; s++) {
                const uint32_t b0 = __shfl_sync(0xffffffffu, w[s % 3], (s / 3) * 16 + j);
                const uint32_t b1 = __shfl_sync(0xffffffffu, w[s % 3], (s / 3) * 16 + 8 + j);
#pragma unroll
                for (int mt = 0; mt < 2; mt++) mma16816(acc[mt][s & 1], a[s][mt], b0, b1);
            }
            sts32f(part, sel4(j, acc[0][0][0] + acc[0][1][0], acc[0][0][2] + acc[0][1][2], acc[1][0][0] + acc[1][1][0], acc[1][0][2] + acc[1][1][2]));
            CK(1, 0);
            fin_arrive<4>();
            fin_sync<5>();
            if (cta < NE_CTAS + 4 && tid < 56) reinterpret_cast<uint4*>(&g_early[b * NH + 28 + cta - NE_CTAS])[tid] = make_uint4(0u, 0u, 0u, 0u);
            continue;
        }
        {
            const int bh = b * NH + (cta >> 2);
            if (tid == 0) wait_row_o(side, bh, UPB);
            aux_sync();
            if (warp < 5) {
                uint32_t ob[12][2];
                load_o<4>(ob, side, bh, 0, j);
                float acc[2][2][4] = {};
#pragma unroll
                for (int ks = 0; ks < 12; ks++) {
                    const int row = ks * 16 + frow;
#pragma unroll
                    for (int mt = 0; mt < 2; mt++) {
                        uint32_t a[4];
                        ldsm4t(a, sb + SM_A + warp * 12288 + (row * 4 + ((2 * mt + fcol) ^ ((row >> 1) & 3))) * 16);
                        mma16816(acc[mt][ks & 1], a, ob[ks][0], ob[ks][1]);
                    }
                }
                red_f2(&g_st.attn[b][(cta & 3) * 160 + warp * 32 + 8 * j + g].x,
                       sel4(j, acc[0][0][0] + acc[0][1][0], acc[0][0][2] + acc[0][1][2], acc[1][0][0] + acc[1][1][0], acc[1][0][2] + acc[1][1][2]), 1.f);
                TS(8);
            } else if (warp > 5 && (cta & 3) == 0 && tid - 192 < 56) {
                reinterpret_cast<uint4*>(&g_early[bh])[tid - 192] = make_uint4(0u, 0u, 0u, 0u);
            }
        }
        if (cta >= NF_CTAS) continue;

        const int kq = warp >> 1, t = warp & 1;
        uint32_t hfrag = sb + SM_X + min(g, 4) * HPITCH + (kq * 80 + 4 * j) * 4;
        uint4 hv[5] = {};
#pragma unroll
        for (int s = 0; s < 5; s++) lds128_if(hv[s], hfrag + s * 64, true);
        if (b == NB - 1) {
            asm volatile("bar.arrive 9, 288;" ::: "memory");
            mbar_wait(sb + BAR_G + kq * 8, 0);
            if (warp == NAUX - 1) TSW(9);
        }
        {
            uint32_t ga[10][4];
#pragma unroll
            for (int s = 0; s < 10; s++) {
                const int row = (kq * 10 + s) * 16 + frow;
                ldsm4t(ga[s], sb + SM_G + fcol * 20480 + (row * 2 + (t ^ ((row >> 2) & 1))) * 16);
            }
            uint32_t fpart = sb + SM_RED + 2 * j * FPITCH + kq * 128 + (g ^ t) * 16 + t * 8;
            pin(fpart); pin(hfrag);
            fin_sync<7>();
#pragma unroll
            for (int s = 0; s < 5; s++) lds128_if(hv[s], hfrag + s * 64, g == b);
            float acc[2][4] = {};
#pragma unroll
            for (int s = 0; s < 5; s++) {
                mma16816(acc[0], ga[2 * s], hv[s].x, hv[s].y);
                mma16816(acc[1], ga[2 * s + 1], hv[s].z, hv[s].w);
            }
#pragma unroll
            for (int e = 0; e < 2; e++) sts64f(fpart + e * FPITCH, acc[0][e] + acc[1][e], acc[0][2 + e] + acc[1][2 + e], 2 * j + e < 5);
        }
        CK(5, 0);
        fin_arrive<4>();
        if (gidx >= 0) {
            const uint4* asrc[3];
#pragma unroll
            for (int q = 0; q < 3; q++) {
                asrc[q] = sided<uint4>(side, X_A + (warp * 12 + 4 * q + 2 * (g >> 2) + (j >> 1)) * 128 + (g & 3) * 32 + (j & 1) * 16);
                pin(asrc[q]);
            }
            uint32_t ypart = sb + SM_RED2 + (warp * 2 + (j >> 1)) * YPITCH + (j & 1) * 160 + g * 16;
            pin(ypart);
            fin_sync<8>();
            if (b == NB - 1) {
                mbar_wait(sb + BAR_D + warp * 8, 0);
                if (warp == NAUX - 1) TSW(10);
            }
            uint32_t wb[3][2][2][4];
#pragma unroll
            for (int s = 0; s < 12; s++) {
                const int odd = (lane >> 2) & 1, c = ((lane & 2) * 2 + (s & 1) * 2 + (lane >> 4)) ^ (2 * odd);
                const int row = (warp * 12 + (s >> 1) * 2 + odd) * 16 + ((lane & 1) ? 8 + (c ^ 1) : c);
                ldsm4t(wb[s >> 2][(s >> 1) & 1][s & 1], sb + SM_D + (row * 2 + (fcol ^ ((row >> 2) & 1))) * 16);
            }
            uint4 v[3];
#pragma unroll 1
            for (int it = 0; it < SPIN_MAX; it++) {
                uint32_t lo = 0xffffffffu;
#pragma unroll
                for (int q = 0; q < 3; q++) v[q] = ld_relaxed_v4(asrc[q]);
#pragma unroll
                for (int q = 0; q < 3; q++) lo = min(min(lo, min(v[q].x, v[q].y)), min(v[q].z, v[q].w));
                if (__all_sync(0xffffffffu, lo != 0 || b < NB - 1)) break;
            }
            CK(8, v[0].x);
            float acc[2][2][4] = {};
#pragma unroll
            for (int q = 0; q < 3; q++) {
#pragma unroll
                for (int pr = 0; pr < 2; pr++) {
                    mma16816(acc[pr][0], wb[q][pr][0], v[q].x, v[q].y);
                    mma16816(acc[pr][1], wb[q][pr][1], v[q].z, v[q].w);
                }
            }
            float y[4];
#pragma unroll
            for (int e = 0; e < 4; e++) y[e] = j < 2 ? acc[0][0][e] + acc[0][1][e] : acc[1][0][e] + acc[1][1][e];
            asm volatile("st.shared.v4.f32 [%0], {%1,%2,%3,%4};" :: "r"(ypart), "f"(y[0]), "f"(y[2]), "f"(y[1]), "f"(y[3]) : "memory");
            CK(9, 0);
            fin_arrive<6>();
        }
        fin_sync<5>();
    }
}

typedef CUresult (*EncodeFn)(CUtensorMap*, CUtensorMapDataType, cuuint32_t, void*, const cuuint64_t*, const cuuint64_t*,
                             const cuuint32_t*, const cuuint32_t*, CUtensorMapInterleave, CUtensorMapSwizzle,
                             CUtensorMapL2promotion, CUtensorMapFloatOOBfill);

CUtensorMap make_map(EncodeFn enc, void* ptr, uint64_t cols, uint64_t rows, uint32_t bcols, uint32_t brows,
                     CUtensorMapSwizzle sw, CUtensorMapL2promotion promo) {
    CUtensorMap m;
    const cuuint64_t dims[2] = {cols, rows};
    const cuuint64_t strides[1] = {cols * 2};
    const cuuint32_t box[2] = {bcols, brows};
    const cuuint32_t es[2] = {1, 1};
    enc(&m, CU_TENSOR_MAP_DATA_TYPE_BFLOAT16, 2, ptr, dims, strides, box, es, CU_TENSOR_MAP_INTERLEAVE_NONE, sw, promo,
        CU_TENSOR_MAP_FLOAT_OOB_FILL_NONE);
    return m;
}

}

extern "C" void kernel_launch(void* const* d_in, const int* in_sizes, int n_in, void* d_out, int out_size) {
    (void)in_sizes; (void)n_in; (void)out_size;
    static EncodeFn enc = nullptr;
    static int sms = 0;
    if (!enc) {
        cudaDriverEntryPointQueryResult qr;
        cudaGetDriverEntryPoint("cuTensorMapEncodeTiled", (void**)&enc, cudaEnableDefault, &qr);
        int dev = 0;
        cudaGetDevice(&dev);
        cudaDeviceGetAttribute(&sms, cudaDevAttrMultiProcessorCount, dev);
        cudaFuncSetAttribute(fused_decode_kernel, cudaFuncAttributeMaxDynamicSharedMemorySize, SM_TOTAL);
    }
    if (sms < NCTAS) return;
    const CUtensorMapL2promotion WPROMO = CU_TENSOR_MAP_L2_PROMOTION_L2_128B;
    Params p;
    p.k = make_map(enc, d_in[1], 64, (uint64_t)NBH * SK * 3, 64, TILE_ROWS, CU_TENSOR_MAP_SWIZZLE_128B, CU_TENSOR_MAP_L2_PROMOTION_NONE);
    p.v = make_map(enc, d_in[2], 64, (uint64_t)NBH * SK * 3, 64, TILE_ROWS, CU_TENSOR_MAP_SWIZZLE_128B, CU_TENSOR_MAP_L2_PROMOTION_NONE);
    p.wq = make_map(enc, d_in[3], NH * DH, DM, 48, 160, CU_TENSOR_MAP_SWIZZLE_NONE, WPROMO);
    p.wo = make_map(enc, d_in[4], DM, NH * DH, 32, WO_ROWS, CU_TENSOR_MAP_SWIZZLE_64B, WPROMO);
    p.wg = make_map(enc, d_in[7], FF, DM, 16, 80, CU_TENSOR_MAP_SWIZZLE_32B, (CUtensorMapL2promotion)GPROMO);
    p.wu = make_map(enc, d_in[8], FF, DM, 16, 80, CU_TENSOR_MAP_SWIZZLE_32B, (CUtensorMapL2promotion)GPROMO);
    p.wd = make_map(enc, d_in[9], DM, FF, 16, 192, CU_TENSOR_MAP_SWIZZLE_32B, WPROMO);
    p.x = (const __nv_bfloat16*)d_in[0];
    p.wr = (const __nv_bfloat16*)d_in[6];
    p.out = (__nv_bfloat16*)d_out;
    fused_decode_kernel<<<NCTAS, NTHREADS, SM_TOTAL, cudaStreamPerThread>>>(p);
}
```

```cpp
#include <cuda_runtime.h>
#include <cuda_bf16.h>
#include <cuda.h>
#include <stdint.h>

namespace {

constexpr int NB = 4, NH = 32, SK = 8192, DH = 192, DM = 640, FF = 1536;
constexpr int NBH = NB * NH;
constexpr int TILE = 64;
constexpr int UPB = SK / TILE;
constexpr int NUNITS = NBH * UPB;
constexpr int TILE_BYTES = TILE * DH * 2;
constexpr int TILE_ROWS = TILE * 3;
constexpr int NCTAS = 132;
constexpr int NQ_CTAS = 128;
constexpr int NE_CTAS = 112;
constexpr int NF_CTAS = 96;

#define NWORK 2
#define LAG 2
#define NPOOL 640
#define RED0 116
#define RING 12
#define OREP 2
#define SROW0 124
#define NPROBE 6
#define VTRIG 300
#define TRIG_NS 4700
#define GPROMO 2
#define DCLK 150
#define DOFF 2400
#define HNAP 100
#define PAD0 1024
#define PAD1 1024
#define PAD2 2048
#define GCLK 300
#define K0_DELAY_NS 1700
#define K0_STEP_NS 900
#define WO_GAP_NS 550
#define WO_ROWS 48
#define QNAP 250
#define WO_AT_NS 3600
constexpr int NAUX = 8;
constexpr int NTHREADS = (NAUX + NWORK + 2) * 32;
constexpr int SPIN_MAX = 1 << 22;

constexpr int SM_KV = 0;
constexpr int SM_A = SM_KV + NWORK * TILE_BYTES;
constexpr int SM_WQ = SM_A + 61440;
constexpr int SM_G = SM_WQ;
constexpr int SM_X = SM_WQ + 61440;
constexpr int XPITCH = 648;
constexpr int HPITCH = 1344;
constexpr int SM_RED = SM_X + 5 * HPITCH;
constexpr int FPITCH = 544;
constexpr int SM_RED2 = SM_RED + 5 * FPITCH;
constexpr int YPITCH = 320;
constexpr int SM_MISC = SM_RED2 + 16 * YPITCH;
constexpr int BAR_KV = SM_MISC, BAR_WQ = SM_MISC + 32, BAR_W = SM_MISC + 40, SM_SIDE = SM_MISC + 48, BAR_G = SM_MISC + 64, BAR_D = SM_MISC + 96;
constexpr int SM_TOTAL = SM_MISC + 160;

struct Params {
    CUtensorMap k, v;
    CUtensorMap wq;
    CUtensorMap wo;
    CUtensorMap wg, wu;
    CUtensorMap wd;
    const __nv_bfloat16 *x, *wr;
    __nv_bfloat16* out;
};

struct Early {
    uint32_t q[96];
    uint32_t umax[UPB];
};
#define LSTRIDE 16
struct State {
    float4 oacc[SROW0][64];
    float2 attn[NB][DM];
    float2 lsum[SROW0][LSTRIDE];
    uint32_t tstart[32];
    uint32_t score[NPOOL][32];
};
constexpr int STATE_V4 = ((sizeof(State) / 32 + NQ_CTAS - 1) / NQ_CTAS) * 2;
static_assert(sizeof(State) % 32 == 0, "State is cleared in whole sectors");
static_assert(sizeof(Early) == 56 * 16, "an Early entry is cleared by 56 threads");
constexpr uint32_t X_O = 0;
constexpr uint32_t X_H = X_O + (NBH - SROW0 + 4 * (OREP - 1)) * 1280;
constexpr uint32_t X_A = X_H + NB * DM * 2;
constexpr uint32_t X_P = X_A + NB * FF * 2;
constexpr uint32_t X_END = X_P + 4096;
static_assert(X_END <= 16 * 4096 && (SROW0 <= NBH - 4 || OREP == 1) && SROW0 >= RED0, "");
struct Scratch {
    unsigned char sided[16][2][4096];
    unsigned work[64];
    unsigned cnt_z[32];
    unsigned char pad0[PAD0];
    Early early[NBH];
    unsigned char pad1[PAD1];
    State st;
    unsigned char pad2[PAD2];
    float4 ring[RING][UPB][64];
};
constexpr size_t PAGE = 2u << 20;
static_assert(sizeof(Scratch) <= PAGE, "scratch must fit one page");
__device__ __align__(128) unsigned char g_raw[2 * PAGE];
__device__ __forceinline__ Scratch* scratch() {
    return reinterpret_cast<Scratch*>((reinterpret_cast<uintptr_t>(g_raw) + PAGE - 1) & ~(uintptr_t)(PAGE - 1));
}
template <typename T> __device__ __forceinline__ T* sided(int side, uint32_t x) {
    const uint32_t pair = (x >> 8) & 15;
    return reinterpret_cast<T*>(&scratch()->sided[pair][(side ^ pair ^ (pair >> 3)) & 1][((x >> 12) << 8) + (x & 255)]);
}
template <typename T> __device__ __forceinline__ T* other_side(T* p) { return reinterpret_cast<T*>(reinterpret_cast<uintptr_t>(p) ^ 4096); }
#define g_early scratch()->early
#define g_st scratch()->st
#define g_ring scratch()->ring
#define g_cnt_z scratch()->cnt_z
#define g_work scratch()->work
#define TS(i)
#define TSW(i)
#define TS2(i)
#define TSI(n, i)
#define PH(i)
#define CK(i, dep)
#define ARR()
#define PROG(u)

__device__ __forceinline__ uint32_t s2u(const void* p) { return (uint32_t)__cvta_generic_to_shared(p); }
__device__ __forceinline__ void mbar_init(uint32_t bar, int cnt) {
    asm volatile("mbarrier.init.shared::cta.b64 [%0], %1;" :: "r"(bar), "r"(cnt) : "memory");
}
__device__ __forceinline__ void mbar_expect_tx(uint32_t bar, uint32_t bytes) {
    asm volatile("mbarrier.arrive.expect_tx.shared::cta.b64 _, [%0], %1;" :: "r"(bar), "r"(bytes) : "memory");
}
__device__ __forceinline__ void mbar_wait(uint32_t bar, uint32_t parity) {
    asm volatile("{\n.reg .pred p;\n.reg .u32 n;\nmov.u32 n, 0;\nWAIT_LOOP:\n"
                 "mbarrier.try_wait.parity.shared::cta.b64 p, [%0], %1;\n"
                 "@p bra WAIT_DONE;\nadd.u32 n, n, 1;\nsetp.lt.u32 p, n, %2;\n@p bra WAIT_LOOP;\nWAIT_DONE:\n}"
                 :: "r"(bar), "r"(parity), "n"(SPIN_MAX) : "memory");
}
__device__ __forceinline__ void tma_tile(uint32_t dst, const CUtensorMap* tm, int row, uint32_t bar, uint64_t pol) {
    asm volatile("cp.async.bulk.tensor.2d.shared::cluster.global.mbarrier::complete_tx::bytes.L2::cache_hint "
                 "[%0], [%1, {%3, %4}], [%2], %5;"
                 :: "r"(dst), "l"(tm), "r"(bar), "r"(0), "r"(row), "l"(pol) : "memory");
}
__device__ __forceinline__ void request_tile(uint32_t dst, const CUtensorMap* tm, int unit, uint32_t bar, uint64_t pol) {
    asm volatile("{\n.reg .pred p;\nelect.sync _|p, 0xffffffff;\n"
                 "@p mbarrier.arrive.expect_tx.shared::cta.b64 _, [%2], %6;\n"
                 "@p cp.async.bulk.tensor.2d.shared::cluster.global.mbarrier::complete_tx::bytes.L2::cache_hint "
                 "[%0], [%1, {%3, %4}], [%2], %5;\n}"
                 :: "r"(dst), "l"(tm), "r"(bar), "r"(0), "r"(unit * TILE_ROWS), "l"(pol), "n"(TILE_BYTES) : "memory");
}
__device__ __forceinline__ uint32_t now_ns() { uint32_t t; asm volatile("mov.u32 %0, %%globaltimer_lo;" : "=r"(t)); return t; }
__device__ __forceinline__ uint32_t now_clk() { uint32_t t; asm volatile("mov.u32 %0, %%clock;" : "=r"(t)); return t; }
__device__ __forceinline__ void wait_clk(uint32_t t) { while (__any_sync(0xffffffffu, (int)(now_clk() - t) < 0)) {} }
constexpr uint64_t EVICT_FIRST = 0x12F0000000000000ull, EVICT_NORMAL = 0x1000000000000000ull;
__device__ __forceinline__ void request_box(uint32_t dst, const CUtensorMap* tm, int col, int row, uint32_t bar, uint64_t pol) {
    asm volatile("{\n.reg .pred p;\nelect.sync _|p, 0xffffffff;\n"
                 "@p cp.async.bulk.tensor.2d.shared::cluster.global.mbarrier::complete_tx::bytes.L2::cache_hint [%0], [%1, {%3, %4}], [%2], %5;\n}"
                 :: "r"(dst), "l"(tm), "r"(bar), "r"(col), "r"(row), "l"(pol) : "memory");
}
__device__ __forceinline__ uint32_t lds32(uint32_t addr) {
    uint32_t v;
    asm volatile("ld.shared.u32 %0, [%1];" : "=r"(v) : "r"(addr) : "memory");
    return v;
}
__device__ __forceinline__ void ldsm4(uint32_t (&r)[4], uint32_t addr) {
    asm volatile("ldmatrix.sync.aligned.m8n8.x4.shared.b16 {%0,%1,%2,%3}, [%4];"
                 : "=r"(r[0]), "=r"(r[1]), "=r"(r[2]), "=r"(r[3]) : "r"(addr) : "memory");
}
__device__ __forceinline__ void ldsm4t(uint32_t (&r)[4], uint32_t addr) {
    asm volatile("ldmatrix.sync.aligned.m8n8.x4.trans.shared.b16 {%0,%1,%2,%3}, [%4];"
                 : "=r"(r[0]), "=r"(r[1]), "=r"(r[2]), "=r"(r[3]) : "r"(addr) : "memory");
}
__device__ __forceinline__ void mma16816(float (&c)[4], const uint32_t (&a)[4], uint32_t b0, uint32_t b1) {
    asm volatile("mma.sync.aligned.m16n8k16.row.col.f32.bf16.bf16.f32 {%0,%1,%2,%3}, {%4,%5,%6,%7}, {%8,%9}, {%0,%1,%2,%3};"
                 : "+f"(c[0]), "+f"(c[1]), "+f"(c[2]), "+f"(c[3])
                 : "r"(a[0]), "r"(a[1]), "r"(a[2]), "r"(a[3]), "r"(b0), "r"(b1));
}
__device__ __forceinline__ uint4 ld_relaxed_v4(const void* p) {
    uint4 v;
    asm volatile("ld.relaxed.gpu.global.v4.u32 {%0,%1,%2,%3}, [%4];" : "=r"(v.x), "=r"(v.y), "=r"(v.z), "=r"(v.w) : "l"(p) : "memory");
    return v;
}
__device__ __forceinline__ float4 ld_relaxed_f4(const void* p) {
    float4 v;
    asm volatile("ld.relaxed.gpu.global.v4.f32 {%0,%1,%2,%3}, [%4];" : "=f"(v.x), "=f"(v.y), "=f"(v.z), "=f"(v.w) : "l"(p) : "memory");
    return v;
}
__device__ __forceinline__ float2 ld_relaxed_f2(const void* p) {
    float2 v;
    asm volatile("ld.relaxed.gpu.global.v2.f32 {%0,%1}, [%2];" : "=f"(v.x), "=f"(v.y) : "l"(p) : "memory");
    return v;
}
__device__ __forceinline__ float4 ld_relaxed_b128(const void* p) {
    float4 v;
    asm volatile("{\n.reg .b128 t;\n.reg .b64 a, b;\nld.relaxed.gpu.global.b128 t, [%4];\nmov.b128 {a, b}, t;\n"
                 "mov.b64 {%0, %1}, a;\nmov.b64 {%2, %3}, b;\n}" : "=f"(v.x), "=f"(v.y), "=f"(v.z), "=f"(v.w) : "l"(p) : "memory");
    return v;
}
__device__ __forceinline__ void st_relaxed_b128(void* p, float x, float y, float z, float w) {
    asm volatile("{\n.reg .b128 t;\n.reg .b64 a, b;\nmov.b64 a, {%1, %2};\nmov.b64 b, {%3, %4};\nmov.b128 t, {a, b};\n"
                 "st.relaxed.gpu.global.b128 [%0], t;\n}" :: "l"(p), "f"(x), "f"(y), "f"(z), "f"(w) : "memory");
}
__device__ __forceinline__ unsigned ld_acquire(const unsigned* p) {
    unsigned v;
    asm volatile("ld.acquire.gpu.global.u32 %0, [%1];" : "=r"(v) : "l"(p) : "memory");
    return v;
}
__device__ __forceinline__ void st_relaxed(void* p, uint32_t v) {
    asm volatile("st.relaxed.gpu.global.u32 [%0], %1;" :: "l"(p), "r"(v) : "memory");
}
__device__ __forceinline__ void red_f2(float* p, float a, float b) {
    asm volatile("red.relaxed.gpu.global.add.v2.f32 [%0], {%1,%2};" :: "l"(p), "f"(a), "f"(b) : "memory");
}
__device__ __forceinline__ void red_f4(float* p, float a, float b, float c, float d) {
    asm volatile("red.relaxed.gpu.global.add.v4.f32 [%0], {%1,%2,%3,%4};" :: "l"(p), "f"(a), "f"(b), "f"(c), "f"(d) : "memory");
}
__device__ __forceinline__ void draw(int& ticket, unsigned* ctr, bool pred) {
    asm volatile("{\n.reg .pred p;\nsetp.ne.u32 p, %2, 0;\n@p atom.relaxed.gpu.global.inc.u32 %0, [%1], 0x7fffffff;\n}"
                 : "+r"(ticket) : "l"(ctr), "r"((uint32_t)pred) : "memory");
}
__device__ __forceinline__ void red_release(unsigned* p) {
    asm volatile("red.release.gpu.global.add.u32 [%0], 1;" :: "l"(p) : "memory");
}
__device__ __forceinline__ uint32_t ld_relaxed_u32(const void* p) {
    uint32_t v;
    asm volatile("ld.relaxed.gpu.global.u32 %0, [%1];" : "=r"(v) : "l"(p) : "memory");
    return v;
}
__device__ __forceinline__ float rcp_approx(float v) {
    float r;
    asm("rcp.approx.ftz.f32 %0, %1;" : "=f"(r) : "f"(v));
    return r;
}
__device__ __forceinline__ float sigmoid_approx(float v) {
    float e;
    asm("ex2.approx.ftz.f32 %0, %1;" : "=f"(e) : "f"(v * -1.4426950408889634f));
    return rcp_approx(1.0f + e);
}
__device__ __forceinline__ float sqrt_approx(float v) {
    float r;
    asm("sqrt.approx.ftz.f32 %0, %1;" : "=f"(r) : "f"(v));
    return r;
}
__device__ __forceinline__ uint2 ld_relaxed_v2(const void* p) {
    uint2 v;
    asm volatile("ld.relaxed.gpu.global.v2.u32 {%0,%1}, [%2];" : "=r"(v.x), "=r"(v.y) : "l"(p) : "memory");
    return v;
}
__device__ __forceinline__ void wait_count(const unsigned* p, unsigned target) {
#pragma unroll 1
    for (int it = 0; it < SPIN_MAX; it++) {
        if (ld_acquire(p) >= target) break;
        __nanosleep(400);
    }
}
__device__ __forceinline__ float4* oacc_at(int side, int row, int grp) {
    return row >= SROW0 ? sided<float4>(side, X_O + (row - SROW0) * 1280 + grp * 16) : &g_st.oacc[row][grp];
}
__device__ __forceinline__ float2* lsum_at(int side, int row) {
    return row >= SROW0 ? sided<float2>(side, X_O + (row - SROW0) * 1280 + 1024) : g_st.lsum[row];
}
__device__ __forceinline__ void wait_row(int side, int bh, float n) {
    const float2* l = lsum_at(side, bh);
#pragma unroll 1
    for (int it = 0; it < SPIN_MAX; it++) {
        const float c = ld_relaxed_f2(l).y;
        if (c >= n) break;
        if (c == 0.f) __nanosleep(600);
    }
}
__device__ __forceinline__ void wait_row_o(int side, int bh, float n) {
    wait_row(side, bh, n);
    if (bh >= RED0) return;
#pragma unroll 1
    for (int it = 0; it < SPIN_MAX; it++) {
        if (__uint_as_float(ld_relaxed_u32(&g_st.oacc[bh][0].w)) == UPB) break;
        __nanosleep(300);
    }
}
__device__ __forceinline__ void spin_ns(int ns) {
    const long long t0 = clock64();
    while (clock64() - t0 < (long long)ns * 2) {}
}
__device__ __forceinline__ uint32_t pack_bf16(float lo, float hi) {
    uint32_t r;
    asm("cvt.rn.bf16x2.f32 %0, %1, %2;" : "=r"(r) : "f"(hi), "f"(lo));
    return r;
}
__device__ __forceinline__ float bf16r(float v) { return __uint_as_float(pack_bf16(0.f, v)); }
__device__ __forceinline__ uint32_t pack_neg(float lo, float hi) {
    const uint32_t w = pack_bf16(-lo, -hi);
    return w ? w : 0x80008000u;
}
__device__ __forceinline__ float lo_f(uint32_t v) { return __uint_as_float(v << 16); }
__device__ __forceinline__ float hi_f(uint32_t v) { return __uint_as_float(v & 0xffff0000u); }
__device__ __forceinline__ float warp_sum(float v) {
#pragma unroll
    for (int o = 16; o; o >>= 1) v += __shfl_xor_sync(0xffffffffu, v, o);
    return v;
}
__device__ __forceinline__ void layernorm20(float (&v)[20]) {
    float s = 0.f;
#pragma unroll
    for (int i = 0; i < 20; i++) s += v[i];
    const float mean = warp_sum(s) * (1.0f / DM);
    float q = 0.f;
#pragma unroll
    for (int i = 0; i < 20; i++) { const float d = v[i] - mean; q += d * d; }
    const float var = bf16r(warp_sum(q) * (1.0f / DM));
    const float m = bf16r(mean);
    const float rden = 1.0f / bf16r(sqrtf(bf16r(var + 1e-5f)));
#pragma unroll
    for (int i = 0; i < 20; i++) v[i] = bf16r(bf16r(v[i] - m) * rden);
}

__device__ __forceinline__ float sel4(int j, float a, float b, float c, float d) {
    float lo, hi, r;
    asm("{\n.reg .pred p;\nsetp.ne.s32 p, %3, 0;\nselp.f32 %0, %2, %1, p;\n}" : "=f"(lo) : "f"(a), "f"(b), "r"(j & 1));
    asm("{\n.reg .pred p;\nsetp.ne.s32 p, %3, 0;\nselp.f32 %0, %2, %1, p;\n}" : "=f"(hi) : "f"(c), "f"(d), "r"(j & 1));
    asm("{\n.reg .pred p;\nsetp.ne.s32 p, %3, 0;\nselp.f32 %0, %2, %1, p;\n}" : "=f"(r) : "f"(lo), "f"(hi), "r"(j & 2));
    return r;
}
template <typename T> __device__ __forceinline__ void pin(T*& p) { asm volatile("" : "+l"(p)); }
__device__ __forceinline__ void pin(uint32_t& v) { asm volatile("" : "+r"(v)); }
__device__ __forceinline__ void pin(float& v) { asm volatile("" : "+f"(v)); }
__device__ __forceinline__ uint32_t after(uint32_t n, float v) {
    asm volatile("{\n.reg .pred p;\nsetp.eq.u32 p, %1, 0x7fc1a5a5;\n@p add.u32 %0, %0, 32;\n}" : "+r"(n) : "r"(__float_as_uint(v)));
    return n;
}
__device__ __forceinline__ float2 lds64f(uint32_t addr) {
    float2 v;
    asm volatile("ld.shared.v2.f32 {%0,%1}, [%2];" : "=f"(v.x), "=f"(v.y) : "r"(addr) : "memory");
    return v;
}
__device__ __forceinline__ float4 lds128f(uint32_t addr) {
    float4 v;
    asm volatile("ld.shared.v4.f32 {%0,%1,%2,%3}, [%4];" : "=f"(v.x), "=f"(v.y), "=f"(v.z), "=f"(v.w) : "r"(addr) : "memory");
    return v;
}
__device__ __forceinline__ void sts64f(uint32_t addr, float a, float b, bool pred) {
    asm volatile("{\n.reg .pred p;\nsetp.ne.u32 p, %3, 0;\n@p st.shared.v2.f32 [%0], {%1,%2};\n}" :: "r"(addr), "f"(a), "f"(b), "r"((uint32_t)pred) : "memory");
}
__device__ __forceinline__ void lds128_if(uint4& v, uint32_t addr, bool pred) {
    asm volatile("{\n.reg .pred p;\nsetp.ne.u32 p, %5, 0;\n@p ld.shared.v4.u32 {%0,%1,%2,%3}, [%4];\n}"
                 : "+r"(v.x), "+r"(v.y), "+r"(v.z), "+r"(v.w) : "r"(addr), "r"((uint32_t)pred) : "memory");
}
__device__ __forceinline__ void sts32f(uint32_t addr, float v) { asm volatile("st.shared.f32 [%0], %1;" :: "r"(addr), "f"(v) : "memory"); }
template <int ID> __device__ __forceinline__ void fin_arrive() { asm volatile("bar.arrive %0, 288;" :: "n"(ID) : "memory"); }
template <int ID> __device__ __forceinline__ void fin_sync() { asm volatile("bar.sync %0, 288;" :: "n"(ID) : "memory"); }
template <int ID> __device__ __forceinline__ void fin_sync(uint32_t n) { asm volatile("bar.sync %0, %1;" :: "n"(ID), "r"(n) : "memory"); }
__device__ __forceinline__ float2 sum8(uint32_t addr) {
    float2 t[8];
#pragma unroll
    for (int w = 0; w < 8; w++) t[w] = lds64f(addr + w * 128);
    return make_float2(((t[0].x + t[1].x) + (t[2].x + t[3].x)) + ((t[4].x + t[5].x) + (t[6].x + t[7].x)),
                       ((t[0].y + t[1].y) + (t[2].y + t[3].y)) + ((t[4].y + t[5].y) + (t[6].y + t[7].y)));
}
__device__ __forceinline__ float4 sum4x4(uint32_t addr) {
    float4 t[4];
#pragma unroll
    for (int w = 0; w < 4; w++) t[w] = lds128f(addr + w * 128);
    return make_float4((t[0].x + t[1].x) + (t[2].x + t[3].x), (t[0].y + t[1].y) + (t[2].y + t[3].y),
                       (t[0].z + t[1].z) + (t[2].z + t[3].z), (t[0].w + t[1].w) + (t[2].w + t[3].w));
}
template <int NJ>
__device__ __forceinline__ void load_o(uint32_t (&ob)[3 * NJ][2], int side, int bh, int J0, int j) {
    float4 v[NJ][4];
    float2 l;
#pragma unroll 1
    for (int it = 0; it < SPIN_MAX; it++) {
#pragma unroll
        for (int J = 0; J < NJ; J++) {
#pragma unroll
            for (int e = 0; e < 4; e++) v[J][e] = ld_relaxed_f4(oacc_at(side, bh, (J0 + J) * 16 + j) + e * 4);
        }
        l = ld_relaxed_f2(lsum_at(side, bh));
        bool ok = l.y == UPB;
#pragma unroll
        for (int J = 0; J < NJ; J++) {
#pragma unroll
            for (int e = 0; e < 4; e++) ok &= v[J][e].w == UPB;
        }
        if (__all_sync(0xffffffffu, ok)) break;
    }
    const float rl = __fdividef(1.0f, l.x);
#pragma unroll
    for (int J = 0; J < NJ; J++) {
        ob[3 * J][0] = pack_bf16(v[J][0].x * rl, v[J][1].x * rl);     ob[3 * J][1] = pack_bf16(v[J][2].x * rl, v[J][3].x * rl);
        ob[3 * J + 1][0] = pack_bf16(v[J][0].y * rl, v[J][1].y * rl); ob[3 * J + 1][1] = pack_bf16(v[J][2].y * rl, v[J][3].y * rl);
        ob[3 * J + 2][0] = pack_bf16(v[J][0].z * rl, v[J][1].z * rl); ob[3 * J + 2][1] = pack_bf16(v[J][2].z * rl, v[J][3].z * rl);
    }
}
__device__ __forceinline__ void aux_sync() { asm volatile("bar.sync 1, 256;" ::: "memory"); }

__global__ void __launch_bounds__(NTHREADS, 1)
fused_decode_kernel(const __grid_constant__ Params p) {
    extern __shared__ __align__(1024) unsigned char smem[];
    const uint32_t sb = s2u(smem);
    const int tid = threadIdx.x, warp = __shfl_sync(0xffffffffu, tid >> 5, 0), lane = tid & 31;
    const int cta = blockIdx.x;
    constexpr int grid = NCTAS;
    const int g = lane >> 2, j = lane & 3;
    const bool is_f = cta < NF_CTAS, is_l = cta >= NE_CTAS;
    const int gidx = !is_f ? cta - NF_CTAS + 4 : cta < 4 ? cta : -1;
    const uint32_t sm_d = sb + (is_f ? SM_A : SM_G);

    TS(0);
    if (warp == 4 && cta < NQ_CTAS) {
        asm volatile("{\n.reg .pred p;\nelect.sync _|p, 0xffffffff;\n"
                     "@p mbarrier.init.shared::cta.b64 [%0], 1;\n"
                     "@p fence.mbarrier_init.release.cluster;\n"
                     "@p mbarrier.arrive.expect_tx.shared::cta.b64 _, [%0], 61440;\n}" :: "r"(sb + BAR_WQ) : "memory");
#pragma unroll
        for (int i = 0; i < 4; i++) request_box(sb + SM_WQ + i * 15360, &p.wq, cta * 48, i * 160, sb + BAR_WQ, EVICT_NORMAL);
    }
    if (tid == 160) {
#pragma unroll
        for (int w = 0; w < NWORK; w++) mbar_init(sb + BAR_KV + w * 8, 1);
        mbar_init(sb + BAR_W, 1);
#pragma unroll
        for (int w = 0; w < 12; w++) mbar_init(sb + BAR_G + w * 8, 1);
        asm volatile("fence.mbarrier_init.release.cluster;" ::: "memory");
    }
    __syncthreads();
    if (warp == NAUX + NWORK + 1) {
        uint32_t t = now_clk() + 2 * WO_AT_NS;
        if (lane == 0) mbar_expect_tx(sb + BAR_W, cta < NE_CTAS ? 61440 : 49152);
        const int col = cta < NE_CTAS ? (cta & 3) * 160 : (cta - NE_CTAS) * 32, row = cta < NE_CTAS ? (cta >> 2) * DH : 28 * DH;
#pragma unroll 1
        for (int r = 0; r < DH; r += WO_ROWS) {
            wait_clk(t);
#pragma unroll 1
            for (int i = 0; i < (cta < NE_CTAS ? 5 : 4); i++)
                request_box(sb + SM_A + i * 12288 + r * 64, &p.wo, cta < NE_CTAS ? col + i * 32 : col, (cta < NE_CTAS ? row : row + i * DH) + r, sb + BAR_W, EVICT_FIRST);
            t += 2 * WO_GAP_NS;
        }
        if (lane < 12) mbar_expect_tx(sb + BAR_G + lane * 8, lane < 4 ? 10240 : 6144);
        asm volatile("bar.sync 9, 288;" ::: "memory");
        asm volatile("fence.proxy.async.shared::cta;" ::: "memory");
        auto request_down = [&](uint32_t t) {
#pragma unroll 1
            for (int i = 0; i < 8; i++, t += DCLK) {
                wait_clk(t);
                request_box(sm_d + i * 6144, &p.wd, gidx * 16, i * 192, sb + BAR_D + i * 8, EVICT_NORMAL);
            }
        };
        if (is_f && gidx >= 0) request_down(now_clk());
#pragma unroll 1
        for (int it = 0; it < SPIN_MAX; it++) {
            t = ld_relaxed_u32(g_st.tstart);
            if (__all_sync(0xffffffffu, t != 0)) break;
            __nanosleep(400);
        }
#pragma unroll 1
        for (int it = 0; it < SPIN_MAX; it++) if (__all_sync(0xffffffffu, t - now_ns() > 2 * TRIG_NS)) break;
        TSW(11);
        t = now_clk();
        if (!is_f) {
            request_down(t + DOFF);
            return;
        }
#pragma unroll 1
        for (int i = 0; i < 8; i++, t += GCLK) {
            wait_clk(t);
            request_box(sb + SM_G + i * 2560, &p.wg, cta * 16, i * 80, sb + BAR_G + (i >> 1) * 8, EVICT_NORMAL);
            request_box(sb + SM_G + 20480 + i * 2560, &p.wu, cta * 16, i * 80, sb + BAR_G + (i >> 1) * 8, EVICT_NORMAL);
        }
        return;
    }
    if (warp == NAUX + NWORK) {
        if (cta < NQ_CTAS) {
#pragma unroll
            for (int i = lane; i < STATE_V4; i += 32)
                if (cta * STATE_V4 + i < (int)(sizeof(State) / 16)) reinterpret_cast<uint4*>(&g_st)[cta * STATE_V4 + i] = make_uint4(0u, 0u, 0u, 0u);
            if (cta * 512 < X_END) {
                uint4* z = sided<uint4>(0, cta * 512 + lane * 16);
                *z = make_uint4(0u, 0u, 0u, 0u);
                *other_side(z) = make_uint4(0u, 0u, 0u, 0u);
            }
            __syncwarp();
            if (lane == 0) red_release(g_cnt_z);
        }
        if (lane == 0) { TS2(2); wait_count(g_cnt_z, NQ_CTAS); TS2(29); }
        __syncwarp();
        asm volatile("bar.arrive 2, %0;" :: "n"((NWORK + 1) * 32) : "memory");
        uint32_t rtt[2] = {0xffffffffu, 0xffffffffu};
        if (lane == 0) {
#pragma unroll 1
            for (int r = 0; r < 2 * NPROBE; r++) {
                int v = 0;
                uint32_t t1 = 0;
                unsigned* ctr = sided<unsigned>(r & 1, X_P + ((cta * 32 + (r >> 1) * 768) & 4095));
                pin(ctr);
                const uint32_t t0 = now_clk();
                draw(v, ctr, true);
                asm volatile("{\n.reg .pred q;\nsetp.ge.s32 q, %1, 0;\n@q mov.u32 %0, %%clock;\n}" : "+r"(t1) : "r"(v) : "memory");
                if (r & 1) rtt[1] = min(rtt[1], t1 - t0); else rtt[0] = min(rtt[0], t1 - t0);
            }
            sts32f(sb + SM_SIDE, __int_as_float(rtt[1] < rtt[0]));
        }
        const int side = __shfl_sync(0xffffffffu, rtt[1] < rtt[0], 0);
        fin_arrive<3>();
        int job = cta;
        auto sum_rows = [&](int row_end) {
#pragma unroll 1
            for (; job < 8 * min(row_end, RED0); job += NCTAS) {
                const int row = job >> 3, grp = (job & 7) * 8 + (lane & 7);
                if (lane == 0) wait_row(side, row, UPB);
                __syncwarp();
                const float4* src = &g_ring[row % RING][lane >> 3][grp];
                float sx = 0.f, sy = 0.f, sz = 0.f;
#pragma unroll 1
                for (int i = 0; i < 2; i++, src += 64 * 64) {
                    float4 v[16];
#pragma unroll 1
                    for (int it = 0; it < SPIN_MAX; it++) {
                        bool ok = true;
#pragma unroll
                        for (int k = 0; k < 16; k++) v[k] = ld_relaxed_b128(src + k * 4 * 64);
#pragma unroll
                        for (int k = 0; k < 16; k++) ok &= v[k].w == (float)(row + 1);
                        if (__all_sync(0xffffffffu, ok)) break;
                    }
#pragma unroll
                    for (int k = 0; k < 16; k++) { sx += v[k].x; sy += v[k].y; sz += v[k].z; }
                }
#pragma unroll
                for (int o = 8; o < 32; o <<= 1) {
                    sx += __shfl_xor_sync(0xffffffffu, sx, o); sy += __shfl_xor_sync(0xffffffffu, sy, o); sz += __shfl_xor_sync(0xffffffffu, sz, o);
                }
                if (lane < 8) st_relaxed_b128(&g_st.oacc[row][grp], sx, sy, sz, UPB);
            }
        };
        {
            uint32_t wr[10];
            float wsum = 0.f;
#pragma unroll
            for (int i = 0; i < 10; i++) {
                const int w = 4 * lane + 128 * (i >> 2) + (i & 3) - (i >= 8 ? 2 * lane : 0);
                wr[i] = *reinterpret_cast<const uint32_t*>(p.wr + (w >> 4) * 32 + (w & 3) * 8 + ((w >> 1) & 6));
                wsum += lo_f(wr[i]) + hi_f(wr[i]);
            }
            wsum = warp_sum(wsum);
            const int lb = lane >> 3, lc = lane & 7;
            uint32_t part = sb + SM_RED + lb * FPITCH + lc * 16, cpart = sb + SM_RED + 4 * FPITCH + lc * 16;
            uint32_t ypart = sb + SM_RED2 + (lb >> 1) * 160 + lc * 16 + (lb & 1) * 8;
            uint32_t* dst = sided<uint32_t>(side ^ 1, X_A + cta * 128 + (lane ^ (cta & 1) * 2) * 4);
            uint32_t* dst2 = other_side(dst);
            __nv_bfloat16* out = p.out + lb * DM + gidx * 16 + lc;
            float nmean_l = 0.f, rden_l = 0.f, sig_l = 0.f;
#pragma unroll 1
            for (int b = 0; b < NB; b++) {
                const uint32_t hx = X_H + b * (DM * 2), hrow = sb + SM_X + b * HPITCH;
                const uint4 *src0 = sided<uint4>(side, hx + 16 * lane), *src1 = sided<uint4>(side, hx + 512 + 16 * lane);
                const uint2* src2 = sided<uint2>(side, hx + 1024 + 8 * lane);
                sum_rows((b + 1) * NH);
                pin(dst); pin(dst2); pin(src0); pin(src1); pin(src2); pin(part); pin(cpart); pin(ypart); pin(out);
                if (lane == 0) wait_row(side, b * NH + (is_l ? 28 : NH - 1), 1);
                __syncwarp();
                if (is_l) {
                    const int col = (cta - NE_CTAS) * 32 + 2 * (lane & 15);
                    uint32_t lpart = sb + SM_RED + (lane & 15) * 8;
                    const uint32_t xv = *reinterpret_cast<const uint32_t*>(p.x + b * DM + col);
                    uint32_t* hdst = sided<uint32_t>(lane >> 4, hx + 4 * ((col >> 5) * 16 + (col & 6) * 2 + ((col >> 3) & 3)));
                    float4 early;
#pragma unroll 1
                    for (int it = 0; it < SPIN_MAX; it++) {
                        early = ld_relaxed_f4(&g_st.attn[b][col]);
                        if (__all_sync(0xffffffffu, early.y == NE_CTAS / 4 && early.w == NE_CTAS / 4)) break;
                    }
                    float x0 = lo_f(xv), x1 = hi_f(xv);
                    pin(hdst); pin(lpart); pin(x0); pin(x1);
                    fin_sync<4>();
                    CK(2, lds32(sb + SM_RED));
                    const float2 late = sum8(lpart);
                    st_relaxed(hdst, pack_neg(x0 + bf16r(early.x + late.x), x1 + bf16r(early.z + late.y)));
                    CK(3, 0);
                    if (lane == 0) TS2(15);
                }
                uint4 h0, h1;
                uint2 h2;
#pragma unroll 1
                for (int it = 0; it < SPIN_MAX; it++) {
                    h0 = ld_relaxed_v4(src0);
                    h1 = ld_relaxed_v4(src1);
                    h2 = ld_relaxed_v2(src2);
                    asm volatile("st.shared.v4.u32 [%0], {%1,%2,%3,%4};" :: "r"(hrow + lane * 16), "r"(h0.x), "r"(h0.y), "r"(h0.z), "r"(h0.w) : "memory");
                    asm volatile("st.shared.v4.u32 [%0], {%1,%2,%3,%4};" :: "r"(hrow + 512 + lane * 16), "r"(h1.x), "r"(h1.y), "r"(h1.z), "r"(h1.w) : "memory");
                    asm volatile("st.shared.v2.u32 [%0], {%1,%2};" :: "r"(hrow + 1024 + lane * 8), "r"(h2.x), "r"(h2.y) : "memory");
                    const uint32_t lo = min(min(min(h0.x, h0.y), min(h0.z, h0.w)), min(min(min(h1.x, h1.y), min(h1.z, h1.w)), min(h2.x, h2.y)));
                    const bool ok = __all_sync(0xffffffffu, lo != 0) || it == SPIN_MAX - 1;
                    asm volatile("{\n.reg .pred p;\nsetp.ne.u32 p, %0, 0;\n@p bar.arrive 7, 288;\n}" :: "r"((uint32_t)(ok && is_f)) : "memory");
                    if (ok) break;
                    if (!is_f) __nanosleep(HNAP);
                }
                CK(4, h0.x);
                if (lane == 0 && is_f) TS2(12);
                const uint32_t hw[10] = {h0.x, h0.y, h0.z, h0.w, h1.x, h1.y, h1.z, h1.w, h2.x, h2.y};
                float ma[4] = {}, mb[4] = {};
#pragma unroll
                for (int i = 0; i < 5; i++) {
                    const uint32_t a[4] = {hw[2 * i], 0x3f803f80u, hw[2 * i + 1], 0x3f803f80u};
                    mma16816((i & 1) ? mb : ma, a, hw[2 * i], hw[2 * i + 1]);
                }
                float m1 = (ma[2] + mb[2]) + (ma[3] + mb[3]), m2 = (g & 1) ? ma[1] + mb[1] : ma[0] + mb[0];
                m2 += __shfl_xor_sync(0xffffffffu, m2, 4);
                m1 = (m1 + __shfl_xor_sync(0xffffffffu, m1, 1)) + (__shfl_xor_sync(0xffffffffu, m1, 2) + __shfl_xor_sync(0xffffffffu, m1, 3));
                m2 = (__shfl_sync(0xffffffffu, m2, 0) + __shfl_sync(0xffffffffu, m2, 9)) + (__shfl_sync(0xffffffffu, m2, 18) + __shfl_sync(0xffffffffu, m2, 27));
                CK(5, __float_as_uint(m2));
                asm volatile("{\n.reg .pred p;\nsetp.ne.u32 p, %0, 0;\n@p bar.sync 4, 288;\n}" :: "r"((uint32_t)is_f) : "memory");
                CK(6, lds32(part));
                const float4 d = sum4x4(part), cs = sum4x4(cpart);
                m1 *= 1.0f / DM;
                const float nmean = bf16r(m1);
                const float var = bf16r(fmaxf(fmaf(-m1, m1, m2 * (1.0f / DM)), 0.f));
                const float rden = rcp_approx(bf16r(sqrt_approx(bf16r(var + 1e-5f))));
                if (lb == b) { nmean_l = nmean; rden_l = rden; }
                const float g0 = bf16r(fmaf(nmean_l, cs.x, -d.x) * rden_l), g1 = bf16r(fmaf(nmean_l, cs.z, -d.z) * rden_l);
                const float u0 = bf16r(fmaf(nmean_l, cs.y, -d.y) * rden_l), u1 = bf16r(fmaf(nmean_l, cs.w, -d.w) * rden_l);
                const uint32_t av = pack_neg(bf16r(g0 * sigmoid_approx(g0)) * u0, bf16r(g1 * sigmoid_approx(g1)) * u1);
                asm volatile("{\n.reg .pred p;\nsetp.eq.u32 p, %3, 3;\n@p st.relaxed.gpu.global.u32 [%0], %2;\n@p st.relaxed.gpu.global.u32 [%1], %2;\n}"
                             :: "l"(dst), "l"(dst2), "r"(av), "r"(is_f ? b : 0) : "memory");
                CK(7, 0);
                if (lane == 0 && is_f) TS2(14);
                if (gidx >= 0) {
                    fin_arrive<8>();
                    __syncwarp();
                    const float2 hw2 = lds64f(sb + SM_X + lb * HPITCH + ((gidx >> 1) * 16 + (lc & 6) * 2 + (gidx & 1) * 2) * 4);
                    const float nh0 = (lc & 1) ? hi_f(__float_as_uint(hw2.x)) : lo_f(__float_as_uint(hw2.x));
                    const float nh1 = (lc & 1) ? hi_f(__float_as_uint(hw2.y)) : lo_f(__float_as_uint(hw2.y));
                    float rr = 0.f;
#pragma unroll
                    for (int i = 0; i < 10; i++) rr = fmaf(lo_f(hw[i]), lo_f(wr[i]), fmaf(hi_f(hw[i]), hi_f(wr[i]), rr));
                    const float sig = bf16r(sigmoid_approx(bf16r((nmean * wsum - warp_sum(rr)) * rden)));
                    if (lb == b) sig_l = sig;
                    const float ln0 = bf16r(bf16r(nmean_l - nh0) * rden_l), ln1 = bf16r(bf16r(nmean_l - nh1) * rden_l);
                    fin_sync<6>(after(after(after(288, sig_l), ln0), ln1));
                    CK(10, lds32(ypart));
                    float2 t[16];
#pragma unroll
                    for (int i = 0; i < 16; i++) t[i] = lds64f(ypart + i * YPITCH);
#pragma unroll
                    for (int o = 1; o < 16; o <<= 1) {
#pragma unroll
                        for (int i = 0; i < 16; i += 2 * o) { t[i].x += t[i + o].x; t[i].y += t[i + o].y; }
                    }
                    const uint32_t ov = pack_bf16(bf16r(ln0 + bf16r(bf16r(-t[0].x) * sig_l)) - nh0, bf16r(ln1 + bf16r(bf16r(-t[0].y) * sig_l)) - nh1);
                    asm volatile("{\n.reg .pred p;\n.reg .b16 lo, hi;\nsetp.eq.u32 p, %2, 3;\nmov.b32 {lo, hi}, %1;\n"
                                 "@p st.global.u16 [%0], lo;\n@p st.global.u16 [%0 + 16], hi;\n}" :: "l"(out), "r"(ov), "r"(b) : "memory");
                    CK(11, 0);
                    if (lane == 0) TS2(13);
                }
                fin_sync<5>();
            }
            if (cta == 0 && lane == 0) { g_work[0] = 0; g_work[32] = 0; g_cnt_z[0] = 0; }
        }
        return;
    }
    if (warp >= NAUX) {
        const int wk = warp - NAUX;
        const uint32_t bar = sb + BAR_KV + wk * 8;
        const uint32_t buf = sb + SM_KV + wk * TILE_BYTES;
        uint64_t pol;
        asm volatile("createpolicy.fractional.L2::evict_first.b64 %0, 1.0;" : "=l"(pol));
        const int nstatic = NWORK * grid;
        constexpr int POOL0 = NUNITS - NPOOL;
        int uk = wk * grid + cta;
        if (lane == 0) {
            spin_ns(K0_DELAY_NS + wk * K0_STEP_NS);
            mbar_expect_tx(bar, TILE_BYTES);
            tma_tile(buf, &p.k, uk * TILE_ROWS, bar, pol);
        }
        __syncwarp();
        uint32_t koff[3], voff[3];
        {
            const int r = lane & 7, hf = (lane >> 3) & 1;
            const int kkey = hf ? 8 + (r ^ 1) : r;
            const int vh = lane >> 4;
            const int vkey = ((r & 1) ? 8 : 0) + (vh ? (r ^ 1) : r);
#pragma unroll
            for (int b = 0; b < 3; b++) {
                const int rk = 3 * kkey + b, rv = 3 * vkey + b;
                koff[b] = buf + rk * 128 + (((lane >> 4) ^ (rk & 7)) << 4);
                voff[b] = buf + rv * 128 + ((hf ^ (rv & 7)) << 4);
            }
        }
        uint32_t phase = 0;
        uint4 qf[6];
        auto load_q = [&](int u) {
            const uint32_t* q = &g_early[u / UPB].q[j * 4];
#pragma unroll
            for (int i = 0; i < 6; i++) qf[i] = ld_relaxed_v4(q + i * 16);
        };
        load_q(uk);
        int uq[LAG];
        uint32_t sq[LAG];
#pragma unroll
        for (int i = 0; i < LAG; i++) { uq[i] = -1; sq[i] = 0; }
        uint4 mv = make_uint4(0u, 0u, 0u, 0u);
        float freed = UPB;
        while (true) {
            const int uv = uq[0];
            uint32_t sv = sq[0];
#pragma unroll
            for (int i = 0; i + 1 < LAG; i++) { uq[i] = uq[i + 1]; sq[i] = sq[i + 1]; }
            uq[LAG - 1] = uk;
            if (uk < NUNITS) {
                PH(7);
#pragma unroll 1
                for (int it = 0; it < SPIN_MAX; it++) {
                    uint32_t lo = 0xffffffffu;
#pragma unroll
                    for (int i = 0; i < 6; i++) lo = min(min(lo, min(qf[i].x, qf[i].y)), min(qf[i].z, qf[i].w));
                    if (__all_sync(0xffffffffu, lo != 0)) break;
                    __nanosleep(QNAP);
                    load_q(uk);
                }
                mbar_wait(bar, phase); phase ^= 1;
                PH(0); ARR();
                TSI(0, 16); TSI(1, 18);
                float acc[2][4][4] = {};
#pragma unroll
                for (int ks = 0; ks < 12; ks++) {
                    const uint4 qq = qf[ks >> 1];
                    const uint32_t b0 = (ks & 1) ? qq.z : qq.x, b1 = (ks & 1) ? qq.w : qq.y;
#pragma unroll
                    for (int mt = 0; mt < 4; mt++) {
                        uint32_t a[4];
                        ldsm4(a, (koff[ks >> 2] ^ ((ks & 3) << 5)) + mt * 6144);
                        mma16816(acc[ks & 1][mt], a, b0, b1);
                    }
                }
                PH(1);
                TSI(0, 17); TSI(1, 19);
                if (uv < NUNITS) request_tile(buf, uv >= 0 ? &p.v : &p.k, uv >= 0 ? uv : uk + nstatic, bar, pol);
                const float sa = sel4(j, acc[0][0][0], acc[0][1][0], acc[0][2][0], acc[0][3][0]) + sel4(j, acc[1][0][0], acc[1][1][0], acc[1][2][0], acc[1][3][0]);
                const float sc = sel4(j, acc[0][0][2], acc[0][1][2], acc[0][2][2], acc[0][3][2]) + sel4(j, acc[1][0][2], acc[1][1][2], acc[1][2][2], acc[1][3][2]);
                const uint32_t raw = pack_bf16(sa, sc);
                const float scale = -0.07216878364870322f;
                const uint32_t sk = pack_bf16(lo_f(raw) * scale, hi_f(raw) * scale);
                sq[LAG - 1] = sk;
                if (uk >= POOL0) st_relaxed(&g_st.score[uk - POOL0][lane], sk ? sk : 0x80008000u);
                int a = (int)(sk << 16), b = (int)(sk & 0xffff0000u);
                a ^= (a >> 31) & 0x7fff0000; b ^= (b >> 31) & 0x7fff0000;
                const int mx = __reduce_max_sync(0xffffffffu, max(a, b));
                if (lane == 0) st_relaxed(&g_early[uk / UPB].umax[uk % UPB], (uint32_t)mx | 1u);
            }
            if (uv < 0) {
                uk += nstatic;
                load_q(uk);
                continue;
            }
            if (uv >= NUNITS) break;
            const int bh = uv / UPB;
#pragma unroll 1
            for (int it = 0; it < SPIN_MAX; it++) {
                if (__all_sync(0xffffffffu, (mv.x & mv.y & mv.z & mv.w & 1u) && (uv < POOL0 || sv != 0) && freed == UPB)) break;
                mv = ld_relaxed_v4(&g_early[bh].umax[lane * 4]);
                if (bh >= RING && bh < RED0) freed = __uint_as_float(ld_relaxed_u32(&g_st.oacc[bh - RING][(lane & 7) * 8].w));
                if (uv >= POOL0) sv = ld_relaxed_u32(&g_st.score[uv - POOL0][lane]);
            }
            PH(2);
            int un = NUNITS, vn = 0;
            draw(un, g_work, uk < NUNITS && lane == 0);
            draw(vn, g_work + 32, uq[0] >= POOL0 && lane == 0);
            const uint32_t cdraw = now_clk();
            int mx = __reduce_max_sync(0xffffffffu, max(max((int)mv.x, (int)mv.y), max((int)mv.z, (int)mv.w))) & 0xffff0000;
            mx ^= (mx >> 31) & 0x7fff0000;
            const float m = __int_as_float(mx);
            const float l2e = 1.4426950408889634f;
            const uint32_t pp = pack_bf16(exp2f((lo_f(sv) - m) * l2e), exp2f((hi_f(sv) - m) * l2e));
            uint32_t pb[8];
#pragma unroll
            for (int t = 0; t < 4; t++) {
                pb[2 * t] = __shfl_sync(0xffffffffu, pp, 8 * j + t);
                pb[2 * t + 1] = __shfl_sync(0xffffffffu, pp, 8 * j + 4 + t);
            }
            float lacc[4] = {};
            const uint32_t ones[4] = {0x3f803f80u, 0x3f803f80u, 0x3f803f80u, 0x3f803f80u};
#pragma unroll
            for (int t = 0; t < 4; t++) mma16816(lacc, ones, pb[2 * t], pb[2 * t + 1]);
            PH(3);
            mbar_wait(bar, phase); phase ^= 1;
            PH(4); ARR();
            float acc[12][4] = {};
#pragma unroll
            for (int t = 0; t < 4; t++) {
#pragma unroll
                for (int mt = 0; mt < 12; mt++) {
                    uint32_t a[4];
                    ldsm4t(a, (voff[mt >> 2] ^ ((mt & 3) << 5)) + t * 6144);
                    mma16816(acc[mt], a, pb[2 * t], pb[2 * t + 1]);
                }
            }
            un = __shfl_sync(0xffffffffu, un, 0) + (LAG + 1) * nstatic;
            vn = __shfl_sync(0xffffffffu, vn, 0);
            if (uq[0] >= POOL0) uq[0] = POOL0 + vn;
            PH(5);
            if (lane == 0) PROG(un);
            if (un < NUNITS || uq[0] < NUNITS) request_tile(buf, un < NUNITS ? &p.k : &p.v, un < NUNITS ? un : uq[0], bar, pol);
            if (un < NUNITS) load_q(un);
            if (vn == VTRIG && lane == 0) st_relaxed(g_st.tstart, (now_ns() + TRIG_NS - min((now_clk() - cdraw) * 35u >> 6, TRIG_NS)) | 1u);
            float o[6];
#pragma unroll
            for (int e = 0; e < 6; e++) {
                const int q = e % 3, c = (e / 3) * 2;
                o[e] = sel4(j, acc[q][c], acc[3 + q][c], acc[6 + q][c], acc[9 + q][c]);
            }
            if (uv < nstatic) {
                asm volatile("bar.sync 2, %0;" :: "n"((NWORK + 1) * 32) : "memory");
                TSW(3);
            }
            const int grp = 16 * j + 4 * (g & 1) + (g >> 1);
            if (bh < RED0) {
                float4* dst = &g_ring[bh % RING][uv % UPB][grp];
                st_relaxed_b128(dst, o[0], o[1], o[2], (float)(bh + 1));
                st_relaxed_b128(dst + 8, o[3], o[4], o[5], (float)(bh + 1));
            }
            const int acc_row = bh >= NBH - 4 && uv % OREP ? bh + 4 * (uv % OREP) : bh;
            if (bh >= RED0) {
                float4* dst = oacc_at(0, acc_row, grp);
                red_f4(&dst->x, o[0], o[1], o[2], 1.f);
                red_f4(&dst[8].x, o[3], o[4], o[5], 1.f);
                if (bh >= SROW0) {
                    red_f4(&other_side(dst)->x, o[0], o[1], o[2], 1.f);
                    red_f4(&other_side(dst)[8].x, o[3], o[4], o[5], 1.f);
                }
            }
            if (lane < (bh >= SROW0 ? 2 : 1)) red_f2(&lsum_at(lane, acc_row)->x, lacc[0], 1.f);
            PH(6);
            if (uq[0] >= NUNITS && un >= NUNITS) break;
            uk = un;
            if (uq[0] < NUNITS) {
                const int nb = uq[0] / UPB;
                mv = ld_relaxed_v4(&g_early[nb].umax[lane * 4]);
                freed = nb >= RING && nb < RED0 ? __uint_as_float(ld_relaxed_u32(&g_st.oacc[nb - RING][(lane & 7) * 8].w)) : UPB;
                if (uq[0] >= POOL0) sq[0] = ld_relaxed_u32(&g_st.score[uq[0] - POOL0][lane]);
            }
        }
        TSW(4 + wk);
        return;
    }

    __nv_bfloat16* xs = reinterpret_cast<__nv_bfloat16*>(smem + SM_X);
    float* red = reinterpret_cast<float*>(smem + SM_RED);
    const int frow = (lane & 7) + ((lane >> 4) << 3), fcol = (lane >> 3) & 1;
    if (cta < NQ_CTAS) {
        uint2 xr[5];
        if (warp < NB) {
#pragma unroll
            for (int i = 0; i < 5; i++) xr[i] = *reinterpret_cast<const uint2*>(p.x + warp * DM + i * 128 + lane * 4);
        }
        TS(26);
        if (warp < NB) {
            float v[20];
#pragma unroll
            for (int i = 0; i < 5; i++) {
                v[4 * i] = lo_f(xr[i].x); v[4 * i + 1] = hi_f(xr[i].x); v[4 * i + 2] = lo_f(xr[i].y); v[4 * i + 3] = hi_f(xr[i].y);
            }
            layernorm20(v);
#pragma unroll
            for (int i = 0; i < 5; i++)
                *reinterpret_cast<uint2*>(xs + warp * XPITCH + i * 128 + lane * 4) =
                    make_uint2(pack_bf16(v[4 * i], v[4 * i + 1]), pack_bf16(v[4 * i + 2], v[4 * i + 3]));
        }
        TS(27);
        aux_sync();
        mbar_wait(sb + BAR_WQ, 0);
        TS(1);
        const uint32_t xfrag = sb + SM_X + ((g & 3) * XPITCH + 2 * j) * 2;
        float acc[3][4] = {};
#pragma unroll
        for (int s = 0; s < 5; s++) {
            const int ks = warp * 5 + s;
            const uint32_t b0 = lds32(xfrag + ks * 32), b1 = lds32(xfrag + ks * 32 + 16);
            const int row = ks * 16 + frow;
#pragma unroll
            for (int mt = 0; mt < 3; mt++) {
                uint32_t a[4];
                ldsm4t(a, sb + SM_WQ + (row * 6 + 2 * mt + fcol) * 16);
                mma16816(acc[mt], a, b0, b1);
            }
        }
        if (j < 2) {
#pragma unroll
            for (int mt = 0; mt < 3; mt++) {
                *reinterpret_cast<float2*>(red + (warp * 48 + mt * 16 + g) * 4 + 2 * j) = make_float2(acc[mt][0], acc[mt][1]);
                *reinterpret_cast<float2*>(red + (warp * 48 + mt * 16 + 8 + g) * 4 + 2 * j) = make_float2(acc[mt][2], acc[mt][3]);
            }
        }
        aux_sync();
        if (tid < 96) {
            const int b = tid & 3, cp = tid >> 2;
            float s0 = 0.f, s1 = 0.f;
#pragma unroll
            for (int w = 0; w < 8; w++) { s0 += red[(w * 48 + 2 * cp) * 4 + b]; s1 += red[(w * 48 + 2 * cp + 1) * 4 + b]; }
            const int h = cta >> 2, d = (cta & 3) * 48 + 2 * cp;
            const int ch = d >> 3, jj = (d & 7) >> 1;
            st_relaxed(&g_early[b * NH + h].q[(ch >> 2) * 16 + jj * 4 + (ch & 3)], pack_neg(s0, s1));
        }
        TS(28);
    }
    if (tid < 160) *reinterpret_cast<uint2*>(smem + SM_X + 4 * HPITCH + tid * 8) = make_uint2(0x3f803f80u, 0x3f803f80u);
    fin_sync<3>();
    const int side = lds32(sb + SM_SIDE);
    mbar_wait(sb + BAR_W, 0);
    TS(7);
    uint32_t part = sb + SM_RED + (warp * 32 + 8 * j + g) * 4;

#pragma unroll 1
    for (int b = 0; b < NB; b++) {
        if (b == NB - 1 && !is_f) asm volatile("bar.arrive 9, 288;" ::: "memory");
        if (is_l) {
            uint32_t a[6][2][4];
#pragma unroll
            for (int s = 0; s < 6; s++) {
                const int row = (warp * 6 + s) * 16 + frow;
#pragma unroll
                for (int mt = 0; mt < 2; mt++) ldsm4t(a[s][mt], sb + SM_A + (row * 4 + ((2 * mt + fcol) ^ ((row >> 1) & 3))) * 16);
            }
            const int bh = b * NH + 28 + (warp >> 1);
            const float4* osrc[OREP];
            const float2* lsrc[OREP];
#pragma unroll
            for (int c = 0; c < OREP; c++) {
                const int row = b == NB - 1 ? bh + 4 * c : bh;
                osrc[c] = oacc_at(side, row, (warp & 1) * 32 + lane);
                lsrc[c] = lsum_at(side, row);
                pin(osrc[c]); pin(lsrc[c]);
            }
            if (lane == 0) wait_row_o(side, bh, UPB * 3 / (4 * OREP));
            __syncwarp();
            float4 ov;
            float2 lv;
            pin(part);
#pragma unroll 1
            for (int it = 0; it < SPIN_MAX; it++) {
                float4 oc[OREP];
                float2 lc[OREP];
#pragma unroll
                for (int c = 0; c < OREP; c++) {
                    oc[c] = ld_relaxed_f4(osrc[c]);
                    lc[c] = ld_relaxed_f2(lsrc[c]);
                }
                ov = oc[0]; lv = lc[0];
                if (b == NB - 1) {
#pragma unroll
                    for (int c = 1; c < OREP; c++) {
                        ov.x += oc[c].x; ov.y += oc[c].y; ov.z += oc[c].z; ov.w += oc[c].w; lv.x += lc[c].x; lv.y += lc[c].y;
                    }
                }
                if (__all_sync(0xffffffffu, ov.w == UPB && lv.y == UPB)) break;
            }
            CK(0, __float_as_uint(ov.x));
            const float rl = rcp_approx(lv.x);
            const float px = __shfl_xor_sync(0xffffffffu, ov.x, 4), py = __shfl_xor_sync(0xffffffffu, ov.y, 4),
                        pz = __shfl_xor_sync(0xffffffffu, ov.z, 4);
            const uint32_t w[3] = {pack_bf16(ov.x * rl, px * rl), pack_bf16(ov.y * rl, py * rl), pack_bf16(ov.z * rl, pz * rl)};
            float acc[2][2][4] = {};
#pragma unroll
            for (int s = 0; s < 6; s++) {
                const uint32_t b0 = __shfl_sync(0xffffffffu, w[s % 3], (s / 3) * 16 + j);
                const uint32_t b1 = __shfl_sync(0xffffffffu, w[s % 3], (s / 3) * 16 + 8 + j);
#pragma unroll
                for (int mt = 0; mt < 2; mt++) mma16816(acc[mt][s & 1], a[s][mt], b0, b1);
            }
            sts32f(part, sel4(j, acc[0][0][0] + acc[0][1][0], acc[0][0][2] + acc[0][1][2], acc[1][0][0] + acc[1][1][0], acc[1][0][2] + acc[1][1][2]));
            CK(1, 0);
            fin_arrive<4>();
            if (cta == NE_CTAS && lane < 28) reinterpret_cast<uint4*>(&g_early[bh])[(warp & 1) * 28 + lane] = make_uint4(0u, 0u, 0u, 0u);
        } else {
            const int bh = b * NH + (cta >> 2);
            if (tid == 0) wait_row_o(side, bh, UPB);
            aux_sync();
            if (warp < 5) {
                uint32_t ob[12][2];
                load_o<4>(ob, side, bh, 0, j);
                float acc[2][2][4] = {};
#pragma unroll
                for (int ks = 0; ks < 12; ks++) {
                    const int row = ks * 16 + frow;
#pragma unroll
                    for (int mt = 0; mt < 2; mt++) {
                        uint32_t a[4];
                        ldsm4t(a, sb + SM_A + warp * 12288 + (row * 4 + ((2 * mt + fcol) ^ ((row >> 1) & 3))) * 16);
                        mma16816(acc[mt][ks & 1], a, ob[ks][0], ob[ks][1]);
                    }
                }
                red_f2(&g_st.attn[b][(cta & 3) * 160 + warp * 32 + 8 * j + g].x,
                       sel4(j, acc[0][0][0] + acc[0][1][0], acc[0][0][2] + acc[0][1][2], acc[1][0][0] + acc[1][1][0], acc[1][0][2] + acc[1][1][2]), 1.f);
                TS(8);
            } else if (warp > 5 && (cta & 3) == 0 && tid - 192 < 56) {
                reinterpret_cast<uint4*>(&g_early[bh])[tid - 192] = make_uint4(0u, 0u, 0u, 0u);
            }
        }
        if (b == NB - 1 && is_f) asm volatile("bar.arrive 9, 288;" ::: "memory");

        uint32_t wb[3][2][2][4];
        if (b == NB - 1 && gidx >= 0) {
            mbar_wait(sb + BAR_D + warp * 8, 0);
            if (warp == NAUX - 1 && !is_f) TSW(10);
        }
#pragma unroll
        for (int s = 0; s < 12; s++) {
            const int odd = (lane >> 2) & 1, c = ((lane & 2) * 2 + (s & 1) * 2 + (lane >> 4)) ^ (2 * odd);
            const int row = (warp * 12 + (s >> 1) * 2 + odd) * 16 + ((lane & 1) ? 8 + (c ^ 1) : c);
            ldsm4t(wb[s >> 2][(s >> 1) & 1][s & 1], sm_d + (row * 2 + (fcol ^ ((row >> 2) & 1))) * 16);
        }
        if (is_f) {
            const int kq = warp >> 1, t = warp & 1;
            uint32_t hfrag = sb + SM_X + min(g, 4) * HPITCH + (kq * 80 + 4 * j) * 4;
            uint4 hv[5] = {};
#pragma unroll
            for (int s = 0; s < 5; s++) lds128_if(hv[s], hfrag + s * 64, true);
            if (b == NB - 1) {
                mbar_wait(sb + BAR_G + kq * 8, 0);
                if (warp == NAUX - 1) TSW(9);
            }
            uint32_t ga[10][4];
#pragma unroll
            for (int s = 0; s < 10; s++) {
                const int row = (kq * 10 + s) * 16 + frow;
                ldsm4t(ga[s], sb + SM_G + fcol * 20480 + (row * 2 + (t ^ ((row >> 2) & 1))) * 16);
            }
            uint32_t fpart = sb + SM_RED + 2 * j * FPITCH + kq * 128 + (g ^ t) * 16 + t * 8;
            pin(fpart); pin(hfrag);
            fin_sync<7>();
#pragma unroll
            for (int s = 0; s < 5; s++) lds128_if(hv[s], hfrag + s * 64, g == b);
            float acc[2][4] = {};
#pragma unroll
            for (int s = 0; s < 5; s++) {
                mma16816(acc[0], ga[2 * s], hv[s].x, hv[s].y);
                mma16816(acc[1], ga[2 * s + 1], hv[s].z, hv[s].w);
            }
#pragma unroll
            for (int e = 0; e < 2; e++) sts64f(fpart + e * FPITCH, acc[0][e] + acc[1][e], acc[0][2 + e] + acc[1][2 + e], 2 * j + e < 5);
            CK(5, 0);
            fin_arrive<4>();
        }
        if (gidx >= 0) {
            const uint4* asrc[3];
#pragma unroll
            for (int q = 0; q < 3; q++) {
                asrc[q] = sided<uint4>(side, X_A + (warp * 12 + 4 * q + 2 * (g >> 2) + (j >> 1)) * 128 + (g & 3) * 32 + (j & 1) * 16);
                pin(asrc[q]);
            }
            uint32_t ypart = sb + SM_RED2 + (warp * 2 + (j >> 1)) * YPITCH + (j & 1) * 160 + g * 16;
            pin(ypart);
            fin_sync<8>();
            uint4 v[3];
#pragma unroll 1
            for (int it = 0; it < SPIN_MAX; it++) {
                uint32_t lo = 0xffffffffu;
#pragma unroll
                for (int q = 0; q < 3; q++) v[q] = ld_relaxed_v4(asrc[q]);
#pragma unroll
                for (int q = 0; q < 3; q++) lo = min(min(lo, min(v[q].x, v[q].y)), min(v[q].z, v[q].w));
                if (__all_sync(0xffffffffu, lo != 0 || b < NB - 1)) break;
            }
            CK(8, v[0].x);
            float acc[2][2][4] = {};
#pragma unroll
            for (int q = 0; q < 3; q++) {
#pragma unroll
                for (int pr = 0; pr < 2; pr++) {
                    mma16816(acc[pr][0], wb[q][pr][0], v[q].x, v[q].y);
                    mma16816(acc[pr][1], wb[q][pr][1], v[q].z, v[q].w);
                }
            }
            float y[4];
#pragma unroll
            for (int e = 0; e < 4; e++) y[e] = j < 2 ? acc[0][0][e] + acc[0][1][e] : acc[1][0][e] + acc[1][1][e];
            asm volatile("st.shared.v4.f32 [%0], {%1,%2,%3,%4};" :: "r"(ypart), "f"(y[0]), "f"(y[2]), "f"(y[1]), "f"(y[3]) : "memory");
            CK(9, 0);
            fin_arrive<6>();
        }
        fin_sync<5>();
    }
}

typedef CUresult (*EncodeFn)(CUtensorMap*, CUtensorMapDataType, cuuint32_t, void*, const cuuint64_t*, const cuuint64_t*,
                             const cuuint32_t*, const cuuint32_t*, CUtensorMapInterleave, CUtensorMapSwizzle,
                             CUtensorMapL2promotion, CUtensorMapFloatOOBfill);

CUtensorMap make_map(EncodeFn enc, void* ptr, uint64_t cols, uint64_t rows, uint32_t bcols, uint32_t brows,
                     CUtensorMapSwizzle sw, CUtensorMapL2promotion promo) {
    CUtensorMap m;
    const cuuint64_t dims[2] = {cols, rows};
    const cuuint64_t strides[1] = {cols * 2};
    const cuuint32_t box[2] = {bcols, brows};
    const cuuint32_t es[2] = {1, 1};
    enc(&m, CU_TENSOR_MAP_DATA_TYPE_BFLOAT16, 2, ptr, dims, strides, box, es, CU_TENSOR_MAP_INTERLEAVE_NONE, sw, promo,
        CU_TENSOR_MAP_FLOAT_OOB_FILL_NONE);
    return m;
}

}

extern "C" void kernel_launch(void* const* d_in, const int* in_sizes, int n_in, void* d_out, int out_size) {
    (void)in_sizes; (void)n_in; (void)out_size;
    static EncodeFn enc = nullptr;
    static int sms = 0;
    if (!enc) {
        cudaDriverEntryPointQueryResult qr;
        cudaGetDriverEntryPoint("cuTensorMapEncodeTiled", (void**)&enc, cudaEnableDefault, &qr);
        int dev = 0;
        cudaGetDevice(&dev);
        cudaDeviceGetAttribute(&sms, cudaDevAttrMultiProcessorCount, dev);
        cudaFuncSetAttribute(fused_decode_kernel, cudaFuncAttributeMaxDynamicSharedMemorySize, SM_TOTAL);
    }
    if (sms < NCTAS) return;
    const CUtensorMapL2promotion WPROMO = CU_TENSOR_MAP_L2_PROMOTION_L2_128B;
    Params p;
    p.k = make_map(enc, d_in[1], 64, (uint64_t)NBH * SK * 3, 64, TILE_ROWS, CU_TENSOR_MAP_SWIZZLE_128B, CU_TENSOR_MAP_L2_PROMOTION_NONE);
    p.v = make_map(enc, d_in[2], 64, (uint64_t)NBH * SK * 3, 64, TILE_ROWS, CU_TENSOR_MAP_SWIZZLE_128B, CU_TENSOR_MAP_L2_PROMOTION_NONE);
    p.wq = make_map(enc, d_in[3], NH * DH, DM, 48, 160, CU_TENSOR_MAP_SWIZZLE_NONE, WPROMO);
    p.wo = make_map(enc, d_in[4], DM, NH * DH, 32, WO_ROWS, CU_TENSOR_MAP_SWIZZLE_64B, WPROMO);
    p.wg = make_map(enc, d_in[7], FF, DM, 16, 80, CU_TENSOR_MAP_SWIZZLE_32B, (CUtensorMapL2promotion)GPROMO);
    p.wu = make_map(enc, d_in[8], FF, DM, 16, 80, CU_TENSOR_MAP_SWIZZLE_32B, (CUtensorMapL2promotion)GPROMO);
    p.wd = make_map(enc, d_in[9], DM, FF, 16, 192, CU_TENSOR_MAP_SWIZZLE_32B, WPROMO);
    p.x = (const __nv_bfloat16*)d_in[0];
    p.wr = (const __nv_bfloat16*)d_in[6];
    p.out = (__nv_bfloat16*)d_out;
    fused_decode_kernel<<<NCTAS, NTHREADS, SM_TOTAL, cudaStreamPerThread>>>(p);
}
```

```cpp
#include <cuda_runtime.h>
#include <cuda_bf16.h>
#include <cuda.h>
#include <stdint.h>

namespace {

constexpr int NB = 4, NH = 32, SK = 8192, DH = 192, DM = 640, FF = 1536;
constexpr int NBH = NB * NH;
constexpr int TILE = 64;
constexpr int UPB = SK / TILE;
constexpr int NUNITS = NBH * UPB;
constexpr int TILE_BYTES = TILE * DH * 2;
constexpr int TILE_ROWS = TILE * 3;
constexpr int NCTAS = 132;
constexpr int NQ_CTAS = 128;
constexpr int NE_CTAS = 112;
constexpr int NF_CTAS = 96;

#define NWORK 2
#define LAG 2
#define NPOOL 640
#define RED0 116
#define RING 12
#define OREP 1
#define SROW0 124
#define NPROBE 6
#define VTRIG 400
#define TRIG_NS 2000
#define GPROMO 2
#define DCLK 150
#define DOFF 2900
#define HNAP 100
#define PAD0 1024
#define PAD1 1024
#define PAD2 2048
#define JIT 1
#define FARFIRST 1
#define OPRE 0
#define ONAP 0
#define NSS 0
#define FWAIT 32
#define SPREAD 1
#define GCLK 370
#define K0_DELAY_NS 1700
#define K0_STEP_NS 900
#define WO_GAP_NS 550
#define WO_ROWS 48
#define QNAP 250
#define WO_AT_NS 3600
constexpr int NAUX = 8;
constexpr int NTHREADS = (NAUX + NWORK + 2) * 32;
constexpr int SPIN_MAX = 1 << 22;

constexpr int SM_KV = 0;
constexpr int SM_A = SM_KV + NWORK * TILE_BYTES;
constexpr int SM_WQ = SM_A + 61440;
constexpr int SM_G = SM_WQ;
constexpr int SM_X = SM_WQ + 61440;
constexpr int XPITCH = 648;
constexpr int HPITCH = 1344;
constexpr int SM_RED = SM_X + 5 * HPITCH;
constexpr int FPITCH = 544;
constexpr int SM_RED2 = SM_RED + 5 * FPITCH;
constexpr int YPITCH = 320;
constexpr int SM_MISC = SM_RED2 + 16 * YPITCH;
constexpr int BAR_KV = SM_MISC, BAR_WQ = SM_MISC + 32, BAR_W = SM_MISC + 40, SM_SIDE = SM_MISC + 48, BAR_G = SM_MISC + 64, BAR_D = SM_MISC + 96;
constexpr int SM_TOTAL = SM_MISC + 160;

struct Params {
    CUtensorMap k, v;
    CUtensorMap wq;
    CUtensorMap wo;
    CUtensorMap wg, wu;
    CUtensorMap wd;
    const __nv_bfloat16 *x, *wr;
    __nv_bfloat16* out;
};

struct Early {
    uint32_t q[96];
    uint32_t umax[UPB];
};
#define LSTRIDE 16
struct State {
    float4 oacc[SROW0][64];
    float2 attn[NB][DM];
    float2 lsum[SROW0][LSTRIDE];
    uint32_t tstart[32];
    uint32_t score[NPOOL - NSS][32];
};
constexpr int STATE_V4 = ((sizeof(State) / 32 + NQ_CTAS - 1) / NQ_CTAS) * 2;
static_assert(sizeof(State) % 32 == 0, "State is cleared in whole sectors");
static_assert(sizeof(Early) == 56 * 16, "an Early entry is cleared by 56 threads");
constexpr uint32_t X_O = 0;
constexpr uint32_t X_L = X_O + 4 * OREP * 1024;
constexpr uint32_t X_H = X_L + 4 * OREP * 128;
constexpr uint32_t X_A = X_H + NB * DM * 2;
constexpr uint32_t X_P = X_A + NB * FF * 2;
constexpr uint32_t X_S = X_P + 4096;
constexpr uint32_t X_END = X_S + NSS * 128;
static_assert(X_END <= 16 * 4096 && SROW0 == NBH - 4, "");
struct Scratch {
    unsigned char sided[16][2][4096];
    unsigned work[64];
    unsigned cnt_z[32];
    unsigned char pad0[PAD0];
    Early early[NBH];
    unsigned char pad1[PAD1];
    State st;
    unsigned char pad2[PAD2];
    float4 ring[RING][UPB][64];
};
constexpr size_t PAGE = 2u << 20;
static_assert(sizeof(Scratch) <= PAGE, "scratch must fit one page");
__device__ __align__(128) unsigned char g_raw[2 * PAGE];
__device__ __forceinline__ Scratch* scratch() {
    return reinterpret_cast<Scratch*>((reinterpret_cast<uintptr_t>(g_raw) + PAGE - 1) & ~(uintptr_t)(PAGE - 1));
}
template <typename T> __device__ __forceinline__ T* sided(int side, uint32_t x) {
    const uint32_t pair = (x >> 10) & 15;
    return reinterpret_cast<T*>(&scratch()->sided[pair][(side ^ pair ^ (pair >> 3)) & 1]
                                    [(x & 127) + ((x & 128) << 1) + ((x & 768) << 2) + ((x >> 7) & 128) + ((x >> 6) & 512)]);
}
template <typename T> __device__ __forceinline__ T* other_side(T* p) { return reinterpret_cast<T*>(reinterpret_cast<uintptr_t>(p) ^ 4096); }
#define g_early scratch()->early
#define g_st scratch()->st
#define g_ring scratch()->ring
#define g_cnt_z scratch()->cnt_z
#define g_work scratch()->work
#define TS(i)
#define TSW(i)
#define TS2(i)
#define TSI(n, i)
#define PH(i)
#define CK(i, dep)
#define ARR()
#define PROG(u)

__device__ __forceinline__ uint32_t s2u(const void* p) { return (uint32_t)__cvta_generic_to_shared(p); }
__device__ __forceinline__ void mbar_init(uint32_t bar, int cnt) {
    asm volatile("mbarrier.init.shared::cta.b64 [%0], %1;" :: "r"(bar), "r"(cnt) : "memory");
}
__device__ __forceinline__ void mbar_expect_tx(uint32_t bar, uint32_t bytes) {
    asm volatile("mbarrier.arrive.expect_tx.shared::cta.b64 _, [%0], %1;" :: "r"(bar), "r"(bytes) : "memory");
}
__device__ __forceinline__ void mbar_wait(uint32_t bar, uint32_t parity) {
    asm volatile("{\n.reg .pred p;\n.reg .u32 n;\nmov.u32 n, 0;\nWAIT_LOOP:\n"
                 "mbarrier.try_wait.parity.shared::cta.b64 p, [%0], %1;\n"
                 "@p bra WAIT_DONE;\nadd.u32 n, n, 1;\nsetp.lt.u32 p, n, %2;\n@p bra WAIT_LOOP;\nWAIT_DONE:\n}"
                 :: "r"(bar), "r"(parity), "n"(SPIN_MAX) : "memory");
}
__device__ __forceinline__ void tma_tile(uint32_t dst, const CUtensorMap* tm, int row, uint32_t bar, uint64_t pol) {
    asm volatile("cp.async.bulk.tensor.2d.shared::cluster.global.mbarrier::complete_tx::bytes.L2::cache_hint "
                 "[%0], [%1, {%3, %4}], [%2], %5;"
                 :: "r"(dst), "l"(tm), "r"(bar), "r"(0), "r"(row), "l"(pol) : "memory");
}
__device__ __forceinline__ void request_tile(uint32_t dst, const CUtensorMap* tm, int unit, uint32_t bar, uint64_t pol) {
    asm volatile("{\n.reg .pred p;\nelect.sync _|p, 0xffffffff;\n"
                 "@p mbarrier.arrive.expect_tx.shared::cta.b64 _, [%2], %6;\n"
                 "@p cp.async.bulk.tensor.2d.shared::cluster.global.mbarrier::complete_tx::bytes.L2::cache_hint "
                 "[%0], [%1, {%3, %4}], [%2], %5;\n}"
                 :: "r"(dst), "l"(tm), "r"(bar), "r"(0), "r"(unit * TILE_ROWS), "l"(pol), "n"(TILE_BYTES) : "memory");
}
__device__ __forceinline__ uint32_t now_ns() { uint32_t t; asm volatile("mov.u32 %0, %%globaltimer_lo;" : "=r"(t)); return t; }
__device__ __forceinline__ uint32_t now_clk() { uint32_t t; asm volatile("mov.u32 %0, %%clock;" : "=r"(t)); return t; }
__device__ __forceinline__ void wait_clk(uint32_t t) { while (__any_sync(0xffffffffu, (int)(now_clk() - t) < 0)) {} }
constexpr uint64_t EVICT_FIRST = 0x12F0000000000000ull, EVICT_NORMAL = 0x1000000000000000ull;
__device__ __forceinline__ void request_box(uint32_t dst, const CUtensorMap* tm, int col, int row, uint32_t bar, uint64_t pol) {
    asm volatile("{\n.reg .pred p;\nelect.sync _|p, 0xffffffff;\n"
                 "@p cp.async.bulk.tensor.2d.shared::cluster.global.mbarrier::complete_tx::bytes.L2::cache_hint [%0], [%1, {%3, %4}], [%2], %5;\n}"
                 :: "r"(dst), "l"(tm), "r"(bar), "r"(col), "r"(row), "l"(pol) : "memory");
}
__device__ __forceinline__ uint32_t lds32(uint32_t addr) {
    uint32_t v;
    asm volatile("ld.shared.u32 %0, [%1];" : "=r"(v) : "r"(addr) : "memory");
    return v;
}
__device__ __forceinline__ void ldsm4(uint32_t (&r)[4], uint32_t addr) {
    asm volatile("ldmatrix.sync.aligned.m8n8.x4.shared.b16 {%0,%1,%2,%3}, [%4];"
                 : "=r"(r[0]), "=r"(r[1]), "=r"(r[2]), "=r"(r[3]) : "r"(addr) : "memory");
}
__device__ __forceinline__ void ldsm4t(uint32_t (&r)[4], uint32_t addr) {
    asm volatile("ldmatrix.sync.aligned.m8n8.x4.trans.shared.b16 {%0,%1,%2,%3}, [%4];"
                 : "=r"(r[0]), "=r"(r[1]), "=r"(r[2]), "=r"(r[3]) : "r"(addr) : "memory");
}
__device__ __forceinline__ void mma16816(float (&c)[4], const uint32_t (&a)[4], uint32_t b0, uint32_t b1) {
    asm volatile("mma.sync.aligned.m16n8k16.row.col.f32.bf16.bf16.f32 {%0,%1,%2,%3}, {%4,%5,%6,%7}, {%8,%9}, {%0,%1,%2,%3};"
                 : "+f"(c[0]), "+f"(c[1]), "+f"(c[2]), "+f"(c[3])
                 : "r"(a[0]), "r"(a[1]), "r"(a[2]), "r"(a[3]), "r"(b0), "r"(b1));
}
__device__ __forceinline__ uint4 ld_relaxed_v4(const void* p) {
    uint4 v;
    asm volatile("ld.relaxed.gpu.global.v4.u32 {%0,%1,%2,%3}, [%4];" : "=r"(v.x), "=r"(v.y), "=r"(v.z), "=r"(v.w) : "l"(p) : "memory");
    return v;
}
__device__ __forceinline__ float4 ld_relaxed_f4(const void* p) {
    float4 v;
    asm volatile("ld.relaxed.gpu.global.v4.f32 {%0,%1,%2,%3}, [%4];" : "=f"(v.x), "=f"(v.y), "=f"(v.z), "=f"(v.w) : "l"(p) : "memory");
    return v;
}
__device__ __forceinline__ float2 ld_relaxed_f2(const void* p) {
    float2 v;
    asm volatile("ld.relaxed.gpu.global.v2.f32 {%0,%1}, [%2];" : "=f"(v.x), "=f"(v.y) : "l"(p) : "memory");
    return v;
}
__device__ __forceinline__ float4 ld_relaxed_b128(const void* p) {
    float4 v;
    asm volatile("{\n.reg .b128 t;\n.reg .b64 a, b;\nld.relaxed.gpu.global.b128 t, [%4];\nmov.b128 {a, b}, t;\n"
                 "mov.b64 {%0, %1}, a;\nmov.b64 {%2, %3}, b;\n}" : "=f"(v.x), "=f"(v.y), "=f"(v.z), "=f"(v.w) : "l"(p) : "memory");
    return v;
}
__device__ __forceinline__ void st_relaxed_b128(void* p, float x, float y, float z, float w) {
    asm volatile("{\n.reg .b128 t;\n.reg .b64 a, b;\nmov.b64 a, {%1, %2};\nmov.b64 b, {%3, %4};\nmov.b128 t, {a, b};\n"
                 "st.relaxed.gpu.global.b128 [%0], t;\n}" :: "l"(p), "f"(x), "f"(y), "f"(z), "f"(w) : "memory");
}
__device__ __forceinline__ unsigned ld_acquire(const unsigned* p) {
    unsigned v;
    asm volatile("ld.acquire.gpu.global.u32 %0, [%1];" : "=r"(v) : "l"(p) : "memory");
    return v;
}
__device__ __forceinline__ void st_relaxed(void* p, uint32_t v) {
    asm volatile("st.relaxed.gpu.global.u32 [%0], %1;" :: "l"(p), "r"(v) : "memory");
}
__device__ __forceinline__ void red_f2(float* p, float a, float b) {
    asm volatile("red.relaxed.gpu.global.add.v2.f32 [%0], {%1,%2};" :: "l"(p), "f"(a), "f"(b) : "memory");
}
__device__ __forceinline__ void red_f4(float* p, float a, float b, float c, float d) {
    asm volatile("red.relaxed.gpu.global.add.v4.f32 [%0], {%1,%2,%3,%4};" :: "l"(p), "f"(a), "f"(b), "f"(c), "f"(d) : "memory");
}
__device__ __forceinline__ void draw(int& ticket, unsigned* ctr, bool pred) {
    asm volatile("{\n.reg .pred p;\nsetp.ne.u32 p, %2, 0;\n@p atom.relaxed.gpu.global.inc.u32 %0, [%1], 0x7fffffff;\n}"
                 : "+r"(ticket) : "l"(ctr), "r"((uint32_t)pred) : "memory");
}
__device__ __forceinline__ void red_release(unsigned* p) {
    asm volatile("red.release.gpu.global.add.u32 [%0], 1;" :: "l"(p) : "memory");
}
__device__ __forceinline__ uint32_t ld_relaxed_u32(const void* p) {
    uint32_t v;
    asm volatile("ld.relaxed.gpu.global.u32 %0, [%1];" : "=r"(v) : "l"(p) : "memory");
    return v;
}
__device__ __forceinline__ float rcp_approx(float v) {
    float r;
    asm("rcp.approx.ftz.f32 %0, %1;" : "=f"(r) : "f"(v));
    return r;
}
__device__ __forceinline__ float sigmoid_approx(float v) {
    float e;
    asm("ex2.approx.ftz.f32 %0, %1;" : "=f"(e) : "f"(v * -1.4426950408889634f));
    return rcp_approx(1.0f + e);
}
__device__ __forceinline__ float sqrt_approx(float v) {
    float r;
    asm("sqrt.approx.ftz.f32 %0, %1;" : "=f"(r) : "f"(v));
    return r;
}
__device__ __forceinline__ uint2 ld_relaxed_v2(const void* p) {
    uint2 v;
    asm volatile("ld.relaxed.gpu.global.v2.u32 {%0,%1}, [%2];" : "=r"(v.x), "=r"(v.y) : "l"(p) : "memory");
    return v;
}
__device__ __forceinline__ void wait_count(const unsigned* p, unsigned target) {
#pragma unroll 1
    for (int it = 0; it < SPIN_MAX; it++) {
        if (ld_acquire(p) >= target) break;
        __nanosleep(400);
    }
}
__device__ __forceinline__ float4* oacc_at(int side, int row, int grp) {
    return row >= SROW0 ? sided<float4>(side, X_O + (row - SROW0) * 1024 + grp * 16) : &g_st.oacc[row][grp];
}
__device__ __forceinline__ float2* lsum_at(int side, int row) {
    return row >= SROW0 ? sided<float2>(side, X_L + (row - SROW0) * 128) : g_st.lsum[row];
}
__device__ __forceinline__ uint32_t* score_at(int side, int u, int lane) {
    return u >= NUNITS - NSS ? sided<uint32_t>(side, X_S + (u - (NUNITS - NSS)) * 128 + lane * 4) : &g_st.score[u - (NUNITS - NPOOL)][lane];
}
__device__ __forceinline__ void wait_row(int side, int bh, float n) {
    const float2* l = lsum_at(side, bh);
#pragma unroll 1
    for (int it = 0; it < SPIN_MAX; it++) {
        const float c = ld_relaxed_f2(l).y;
        if (c >= n) break;
        if (c == 0.f) __nanosleep(600);
    }
}
__device__ __forceinline__ void wait_row_o(int side, int bh, float n) {
    wait_row(side, bh, n);
    if (bh >= RED0) return;
#pragma unroll 1
    for (int it = 0; it < SPIN_MAX; it++) {
        if (__uint_as_float(ld_relaxed_u32(&g_st.oacc[bh][0].w)) == UPB) break;
        __nanosleep(300);
    }
}
__device__ __forceinline__ void spin_ns(int ns) {
    const long long t0 = clock64();
    while (clock64() - t0 < (long long)ns * 2) {}
}
__device__ __forceinline__ uint32_t pack_bf16(float lo, float hi) {
    uint32_t r;
    asm("cvt.rn.bf16x2.f32 %0, %1, %2;" : "=r"(r) : "f"(hi), "f"(lo));
    return r;
}
__device__ __forceinline__ float bf16r(float v) { return __uint_as_float(pack_bf16(0.f, v)); }
__device__ __forceinline__ uint32_t pack_neg(float lo, float hi) {
    const uint32_t w = pack_bf16(-lo, -hi);
    return w ? w : 0x80008000u;
}
__device__ __forceinline__ float lo_f(uint32_t v) { return __uint_as_float(v << 16); }
__device__ __forceinline__ float hi_f(uint32_t v) { return __uint_as_float(v & 0xffff0000u); }
__device__ __forceinline__ float warp_sum(float v) {
#pragma unroll
    for (int o = 16; o; o >>= 1) v += __shfl_xor_sync(0xffffffffu, v, o);
    return v;
}
__device__ __forceinline__ void layernorm20(float (&v)[20]) {
    float s = 0.f;
#pragma unroll
    for (int i = 0; i < 20; i++) s += v[i];
    const float mean = warp_sum(s) * (1.0f / DM);
    float q = 0.f;
#pragma unroll
    for (int i = 0; i < 20; i++) { const float d = v[i] - mean; q += d * d; }
    const float var = bf16r(warp_sum(q) * (1.0f / DM));
    const float m = bf16r(mean);
    const float rden = 1.0f / bf16r(sqrtf(bf16r(var + 1e-5f)));
#pragma unroll
    for (int i = 0; i < 20; i++) v[i] = bf16r(bf16r(v[i] - m) * rden);
}

__device__ __forceinline__ float sel4(int j, float a, float b, float c, float d) {
    float lo, hi, r;
    asm("{\n.reg .pred p;\nsetp.ne.s32 p, %3, 0;\nselp.f32 %0, %2, %1, p;\n}" : "=f"(lo) : "f"(a), "f"(b), "r"(j & 1));
    asm("{\n.reg .pred p;\nsetp.ne.s32 p, %3, 0;\nselp.f32 %0, %2, %1, p;\n}" : "=f"(hi) : "f"(c), "f"(d), "r"(j & 1));
    asm("{\n.reg .pred p;\nsetp.ne.s32 p, %3, 0;\nselp.f32 %0, %2, %1, p;\n}" : "=f"(r) : "f"(lo), "f"(hi), "r"(j & 2));
    return r;
}
template <typename T> __device__ __forceinline__ void pin(T*& p) { asm volatile("" : "+l"(p)); }
__device__ __forceinline__ void pin(uint32_t& v) { asm volatile("" : "+r"(v)); }
__device__ __forceinline__ void pin(float& v) { asm volatile("" : "+f"(v)); }
__device__ __forceinline__ uint32_t after(uint32_t n, float v) {
    asm volatile("{\n.reg .pred p;\nsetp.eq.u32 p, %1, 0x7fc1a5a5;\n@p add.u32 %0, %0, 32;\n}" : "+r"(n) : "r"(__float_as_uint(v)));
    return n;
}
__device__ __forceinline__ float2 lds64f(uint32_t addr) {
    float2 v;
    asm volatile("ld.shared.v2.f32 {%0,%1}, [%2];" : "=f"(v.x), "=f"(v.y) : "r"(addr) : "memory");
    return v;
}
__device__ __forceinline__ float4 lds128f(uint32_t addr) {
    float4 v;
    asm volatile("ld.shared.v4.f32 {%0,%1,%2,%3}, [%4];" : "=f"(v.x), "=f"(v.y), "=f"(v.z), "=f"(v.w) : "r"(addr) : "memory");
    return v;
}
__device__ __forceinline__ void sts64f(uint32_t addr, float a, float b, bool pred) {
    asm volatile("{\n.reg .pred p;\nsetp.ne.u32 p, %3, 0;\n@p st.shared.v2.f32 [%0], {%1,%2};\n}" :: "r"(addr), "f"(a), "f"(b), "r"((uint32_t)pred) : "memory");
}
__device__ __forceinline__ void lds128_if(uint4& v, uint32_t addr, bool pred) {
    asm volatile("{\n.reg .pred p;\nsetp.ne.u32 p, %5, 0;\n@p ld.shared.v4.u32 {%0,%1,%2,%3}, [%4];\n}"
                 : "+r"(v.x), "+r"(v.y), "+r"(v.z), "+r"(v.w) : "r"(addr), "r"((uint32_t)pred) : "memory");
}
__device__ __forceinline__ void sts32f(uint32_t addr, float v) { asm volatile("st.shared.f32 [%0], %1;" :: "r"(addr), "f"(v) : "memory"); }
template <int ID> __device__ __forceinline__ void fin_arrive() { asm volatile("bar.arrive %0, 288;" :: "n"(ID) : "memory"); }
template <int ID> __device__ __forceinline__ void fin_sync() { asm volatile("bar.sync %0, 288;" :: "n"(ID) : "memory"); }
template <int ID> __device__ __forceinline__ void fin_sync(uint32_t n) { asm volatile("bar.sync %0, %1;" :: "n"(ID), "r"(n) : "memory"); }
__device__ __forceinline__ float2 sum8(uint32_t addr) {
    float2 t[8];
#pragma unroll
    for (int w = 0; w < 8; w++) t[w] = lds64f(addr + w * 128);
    return make_float2(((t[0].x + t[1].x) + (t[2].x + t[3].x)) + ((t[4].x + t[5].x) + (t[6].x + t[7].x)),
                       ((t[0].y + t[1].y) + (t[2].y + t[3].y)) + ((t[4].y + t[5].y) + (t[6].y + t[7].y)));
}
__device__ __forceinline__ float4 sum4x4(uint32_t addr) {
    float4 t[4];
#pragma unroll
    for (int w = 0; w < 4; w++) t[w] = lds128f(addr + w * 128);
    return make_float4((t[0].x + t[1].x) + (t[2].x + t[3].x), (t[0].y + t[1].y) + (t[2].y + t[3].y),
                       (t[0].z + t[1].z) + (t[2].z + t[3].z), (t[0].w + t[1].w) + (t[2].w + t[3].w));
}
template <int NJ>
__device__ __forceinline__ void load_o(uint32_t (&ob)[3 * NJ][2], int bh, int J0, int j) {
    float4 v[NJ][4];
    float2 l;
#pragma unroll 1
    for (int it = 0; it < SPIN_MAX; it++) {
#pragma unroll
        for (int J = 0; J < NJ; J++) {
#pragma unroll
            for (int e = 0; e < 4; e++) v[J][e] = ld_relaxed_f4(&g_st.oacc[bh][(J0 + J) * 16 + e * 4 + j]);
        }
        l = ld_relaxed_f2(g_st.lsum[bh]);
        bool ok = l.y == UPB;
#pragma unroll
        for (int J = 0; J < NJ; J++) {
#pragma unroll
            for (int e = 0; e < 4; e++) ok &= v[J][e].w == UPB;
        }
        if (__all_sync(0xffffffffu, ok)) break;
    }
    const float rl = __fdividef(1.0f, l.x);
#pragma unroll
    for (int J = 0; J < NJ; J++) {
        ob[3 * J][0] = pack_bf16(v[J][0].x * rl, v[J][1].x * rl);     ob[3 * J][1] = pack_bf16(v[J][2].x * rl, v[J][3].x * rl);
        ob[3 * J + 1][0] = pack_bf16(v[J][0].y * rl, v[J][1].y * rl); ob[3 * J + 1][1] = pack_bf16(v[J][2].y * rl, v[J][3].y * rl);
        ob[3 * J + 2][0] = pack_bf16(v[J][0].z * rl, v[J][1].z * rl); ob[3 * J + 2][1] = pack_bf16(v[J][2].z * rl, v[J][3].z * rl);
    }
}
__device__ __forceinline__ void aux_sync() { asm volatile("bar.sync 1, 256;" ::: "memory"); }

__global__ void __launch_bounds__(NTHREADS, 1)
fused_decode_kernel(const __grid_constant__ Params p) {
    extern __shared__ __align__(1024) unsigned char smem[];
    const uint32_t sb = s2u(smem);
    const int tid = threadIdx.x, warp = __shfl_sync(0xffffffffu, tid >> 5, 0), lane = tid & 31;
    const int cta = blockIdx.x;
    constexpr int grid = NCTAS;
    const int g = lane >> 2, j = lane & 3;
    const bool is_f = cta < NF_CTAS, is_l = cta >= NE_CTAS;
    const int gidx = !is_f ? cta - NF_CTAS + 4 : cta < 4 ? cta : -1;
    const uint32_t sm_d = sb + (is_f ? SM_A : SM_G);

    TS(0);
    if (warp == 4 && cta < NQ_CTAS) {
        asm volatile("{\n.reg .pred p;\nelect.sync _|p, 0xffffffff;\n"
                     "@p mbarrier.init.shared::cta.b64 [%0], 1;\n"
                     "@p fence.mbarrier_init.release.cluster;\n"
                     "@p mbarrier.arrive.expect_tx.shared::cta.b64 _, [%0], 61440;\n}" :: "r"(sb + BAR_WQ) : "memory");
#pragma unroll
        for (int i = 0; i < 4; i++) request_box(sb + SM_WQ + i * 15360, &p.wq, cta * 48, i * 160, sb + BAR_WQ, EVICT_NORMAL);
    }
    if (tid == 160) {
#pragma unroll
        for (int w = 0; w < NWORK; w++) mbar_init(sb + BAR_KV + w * 8, 1);
        mbar_init(sb + BAR_W, 1);
#pragma unroll
        for (int w = 0; w < 12; w++) mbar_init(sb + BAR_G + w * 8, 1);
        asm volatile("fence.mbarrier_init.release.cluster;" ::: "memory");
    }
    __syncthreads();
    if (warp == NAUX + NWORK + 1) {
        uint32_t t = now_clk() + 2 * WO_AT_NS;
        if (lane == 0) mbar_expect_tx(sb + BAR_W, cta < NE_CTAS ? 61440 : 49152);
        const int col = cta < NE_CTAS ? (cta & 3) * 160 : (cta - NE_CTAS) * 32, row = cta < NE_CTAS ? (cta >> 2) * DH : 28 * DH;
#pragma unroll 1
        for (int r = 0; r < DH; r += WO_ROWS) {
            wait_clk(t);
#pragma unroll 1
            for (int i = 0; i < (cta < NE_CTAS ? 5 : 4); i++)
                request_box(sb + SM_A + i * 12288 + r * 64, &p.wo, cta < NE_CTAS ? col + i * 32 : col, (cta < NE_CTAS ? row : row + i * DH) + r, sb + BAR_W, EVICT_FIRST);
            t += 2 * WO_GAP_NS;
        }
        if (lane < 12) mbar_expect_tx(sb + BAR_G + lane * 8, lane < 4 ? 10240 : 6144);
        asm volatile("bar.sync 9, 288;" ::: "memory");
        asm volatile("fence.proxy.async.shared::cta;" ::: "memory");
        auto request_down = [&](uint32_t t) {
#pragma unroll 1
            for (int i = 0; i < 8; i++, t += DCLK) {
                wait_clk(t);
                request_box(sm_d + i * 6144, &p.wd, gidx * 16, i * 192, sb + BAR_D + i * 8, EVICT_NORMAL);
            }
        };
        if (is_f && gidx >= 0) request_down(now_clk());
#pragma unroll 1
        for (int it = 0; it < SPIN_MAX; it++) {
            t = ld_relaxed_u32(g_st.tstart);
            if (__all_sync(0xffffffffu, t != 0)) break;
            __nanosleep(400);
        }
#pragma unroll 1
        for (int it = 0; it < SPIN_MAX; it++) if (__all_sync(0xffffffffu, t - now_ns() > 2 * TRIG_NS)) break;
        TSW(11);
        t = now_clk();
        if (!is_f) {
            request_down(t + DOFF);
            return;
        }
#pragma unroll 1
        for (int i = 0; i < 8; i++, t += GCLK) {
            wait_clk(t);
            request_box(sb + SM_G + i * 2560, &p.wg, cta * 16, i * 80, sb + BAR_G + (i >> 1) * 8, EVICT_NORMAL);
            request_box(sb + SM_G + 20480 + i * 2560, &p.wu, cta * 16, i * 80, sb + BAR_G + (i >> 1) * 8, EVICT_NORMAL);
        }
        return;
    }
    if (warp == NAUX + NWORK) {
        if (cta < NQ_CTAS) {
#pragma unroll
            for (int i = lane; i < STATE_V4; i += 32)
                if (cta * STATE_V4 + i < (int)(sizeof(State) / 16)) reinterpret_cast<uint4*>(&g_st)[cta * STATE_V4 + i] = make_uint4(0u, 0u, 0u, 0u);
            if (cta * 512 < X_END) {
                uint4* z = sided<uint4>(0, cta * 512 + lane * 16);
                *z = make_uint4(0u, 0u, 0u, 0u);
                *other_side(z) = make_uint4(0u, 0u, 0u, 0u);
            }
            __syncwarp();
            if (lane == 0) red_release(g_cnt_z);
        }
        if (lane == 0) { TS2(2); wait_count(g_cnt_z, NQ_CTAS); TS2(29); }
        __syncwarp();
        asm volatile("bar.arrive 2, %0;" :: "n"((NWORK + 1) * 32) : "memory");
        uint32_t rtt[2] = {0xffffffffu, 0xffffffffu};
        if (lane == 0) {
#pragma unroll 1
            for (int r = 0; r < 2 * NPROBE; r++) {
                int v = 0;
                uint32_t t1 = 0;
                unsigned* ctr = sided<unsigned>(r & 1, X_P + ((cta * 32 + (r >> 1) * 768) & 4095));
                pin(ctr);
                const uint32_t t0 = now_clk();
                draw(v, ctr, true);
                asm volatile("{\n.reg .pred q;\nsetp.ge.s32 q, %1, 0;\n@q mov.u32 %0, %%clock;\n}" : "+r"(t1) : "r"(v) : "memory");
                if (r & 1) rtt[1] = min(rtt[1], t1 - t0); else rtt[0] = min(rtt[0], t1 - t0);
            }
            sts32f(sb + SM_SIDE, __int_as_float(rtt[1] < rtt[0]));
        }
        const int side = __shfl_sync(0xffffffffu, rtt[1] < rtt[0], 0);
        fin_arrive<3>();
        int job = cta;
        auto sum_rows = [&](int row_end) {
#pragma unroll 1
            for (; job < 8 * min(row_end, RED0); job += NCTAS) {
                const int row = job >> 3, grp = (job & 7) * 8 + (lane & 7);
                if (lane == 0) wait_row(side, row, UPB);
                __syncwarp();
                const float4* src = &g_ring[row % RING][lane >> 3][grp];
                float sx = 0.f, sy = 0.f, sz = 0.f;
#pragma unroll 1
                for (int i = 0; i < 2; i++, src += 64 * 64) {
                    float4 v[16];
#pragma unroll 1
                    for (int it = 0; it < SPIN_MAX; it++) {
                        bool ok = true;
#pragma unroll
                        for (int k = 0; k < 16; k++) v[k] = ld_relaxed_b128(src + k * 4 * 64);
#pragma unroll
                        for (int k = 0; k < 16; k++) ok &= v[k].w == (float)(row + 1);
                        if (__all_sync(0xffffffffu, ok)) break;
                    }
#pragma unroll
                    for (int k = 0; k < 16; k++) { sx += v[k].x; sy += v[k].y; sz += v[k].z; }
                }
#pragma unroll
                for (int o = 8; o < 32; o <<= 1) {
                    sx += __shfl_xor_sync(0xffffffffu, sx, o); sy += __shfl_xor_sync(0xffffffffu, sy, o); sz += __shfl_xor_sync(0xffffffffu, sz, o);
                }
                if (lane < 8) st_relaxed_b128(&g_st.oacc[row][grp], sx, sy, sz, UPB);
            }
        };
        {
            uint32_t wr[10];
            float wsum = 0.f;
#pragma unroll
            for (int i = 0; i < 10; i++) {
                const int w = 4 * lane + 128 * (i >> 2) + (i & 3) - (i >= 8 ? 2 * lane : 0);
                wr[i] = *reinterpret_cast<const uint32_t*>(p.wr + (w >> 4) * 32 + (w & 3) * 8 + ((w >> 1) & 6));
                wsum += lo_f(wr[i]) + hi_f(wr[i]);
            }
            wsum = warp_sum(wsum);
            const int lb = lane >> 3, lc = lane & 7;
            uint32_t part = sb + SM_RED + lb * FPITCH + lc * 16, cpart = sb + SM_RED + 4 * FPITCH + lc * 16;
            uint32_t ypart = sb + SM_RED2 + (lb >> 1) * 160 + lc * 16 + (lb & 1) * 8;
            uint32_t* dst = sided<uint32_t>(side ^ 1, X_A + cta * 128 + (lane ^ (cta & 1) * 2) * 4);
            uint32_t* dst2 = other_side(dst);
            __nv_bfloat16* out = p.out + lb * DM + gidx * 16 + lc;
            float nmean_l = 0.f, rden_l = 0.f, sig_l = 0.f;
#pragma unroll 1
            for (int b = 0; b < NB; b++) {
                const uint32_t hx = X_H + b * (DM * 2), hrow = sb + SM_X + b * HPITCH;
                const uint4 *src0 = sided<uint4>(side, hx + 16 * lane), *src1 = sided<uint4>(side, hx + 512 + 16 * lane);
                const uint2* src2 = sided<uint2>(side, hx + 1024 + 8 * lane);
                sum_rows((b + 1) * NH);
                pin(dst); pin(dst2); pin(src0); pin(src1); pin(src2); pin(part); pin(cpart); pin(ypart); pin(out);
                if (lane == 0) wait_row(side, b * NH + (is_l ? 28 : NH - 1), is_l ? 1 : FWAIT);
                __syncwarp();
                if (is_l) {
                    const int col = (cta - NE_CTAS) * 32 + 2 * (lane & 15);
                    uint32_t lpart = sb + SM_RED + (lane & 15) * 8;
                    const uint32_t xv = *reinterpret_cast<const uint32_t*>(p.x + b * DM + col);
                    uint32_t* hdst = sided<uint32_t>(lane >> 4, hx + 4 * ((col >> 5) * 16 + (col & 6) * 2 + ((col >> 3) & 3)));
                    float4 early;
#pragma unroll 1
                    for (int it = 0; it < SPIN_MAX; it++) {
                        early = ld_relaxed_f4(&g_st.attn[b][col]);
                        if (__all_sync(0xffffffffu, early.y == NE_CTAS / 4 && early.w == NE_CTAS / 4)) break;
                    }
                    if (lane == 0) TS2(23);
                    float x0 = lo_f(xv), x1 = hi_f(xv);
                    pin(hdst); pin(lpart); pin(x0); pin(x1);
                    fin_sync<4>();
                    CK(2, lds32(sb + SM_RED));
                    const float2 late = sum8(lpart);
                    st_relaxed(hdst, pack_neg(x0 + bf16r(early.x + late.x), x1 + bf16r(early.z + late.y)));
                    CK(3, 0);
                    if (lane == 0) TS2(15);
                }
                uint4 h0, h1;
                uint2 h2;
#pragma unroll 1
                for (int it = 0; it < SPIN_MAX; it++) {
                    h0 = ld_relaxed_v4(src0);
                    h1 = ld_relaxed_v4(src1);
                    h2 = ld_relaxed_v2(src2);
                    asm volatile("st.shared.v4.u32 [%0], {%1,%2,%3,%4};" :: "r"(hrow + lane * 16), "r"(h0.x), "r"(h0.y), "r"(h0.z), "r"(h0.w) : "memory");
                    asm volatile("st.shared.v4.u32 [%0], {%1,%2,%3,%4};" :: "r"(hrow + 512 + lane * 16), "r"(h1.x), "r"(h1.y), "r"(h1.z), "r"(h1.w) : "memory");
                    asm volatile("st.shared.v2.u32 [%0], {%1,%2};" :: "r"(hrow + 1024 + lane * 8), "r"(h2.x), "r"(h2.y) : "memory");
                    const uint32_t lo = min(min(min(h0.x, h0.y), min(h0.z, h0.w)), min(min(min(h1.x, h1.y), min(h1.z, h1.w)), min(h2.x, h2.y)));
                    const bool ok = __all_sync(0xffffffffu, lo != 0) || it == SPIN_MAX - 1;
                    asm volatile("{\n.reg .pred p;\nsetp.ne.u32 p, %0, 0;\n@p bar.arrive 7, 288;\n}" :: "r"((uint32_t)(ok && is_f)) : "memory");
                    if (ok) break;
                    if (!is_f) __nanosleep(HNAP);
                }
                CK(4, h0.x);
                if (lane == 0 && is_f) TS2(12);
                const uint32_t hw[10] = {h0.x, h0.y, h0.z, h0.w, h1.x, h1.y, h1.z, h1.w, h2.x, h2.y};
                float ma[4] = {}, mb[4] = {};
#pragma unroll
                for (int i = 0; i < 5; i++) {
                    const uint32_t a[4] = {hw[2 * i], 0x3f803f80u, hw[2 * i + 1], 0x3f803f80u};
                    mma16816((i & 1) ? mb : ma, a, hw[2 * i], hw[2 * i + 1]);
                }
                float m1 = (ma[2] + mb[2]) + (ma[3] + mb[3]), m2 = (g & 1) ? ma[1] + mb[1] : ma[0] + mb[0];
                m2 += __shfl_xor_sync(0xffffffffu, m2, 4);
                m1 = (m1 + __shfl_xor_sync(0xffffffffu, m1, 1)) + (__shfl_xor_sync(0xffffffffu, m1, 2) + __shfl_xor_sync(0xffffffffu, m1, 3));
                m2 = (__shfl_sync(0xffffffffu, m2, 0) + __shfl_sync(0xffffffffu, m2, 9)) + (__shfl_sync(0xffffffffu, m2, 18) + __shfl_sync(0xffffffffu, m2, 27));
                CK(5, __float_as_uint(m2));
                asm volatile("{\n.reg .pred p;\nsetp.ne.u32 p, %0, 0;\n@p bar.sync 4, 288;\n}" :: "r"((uint32_t)is_f) : "memory");
                CK(6, lds32(part));
                const float4 d = sum4x4(part), cs = sum4x4(cpart);
                m1 *= 1.0f / DM;
                const float nmean = bf16r(m1);
                const float var = bf16r(fmaxf(fmaf(-m1, m1, m2 * (1.0f / DM)), 0.f));
                const float rden = rcp_approx(bf16r(sqrt_approx(bf16r(var + 1e-5f))));
                if (lb == b) { nmean_l = nmean; rden_l = rden; }
                const float g0 = bf16r(fmaf(nmean_l, cs.x, -d.x) * rden_l), g1 = bf16r(fmaf(nmean_l, cs.z, -d.z) * rden_l);
                const float u0 = bf16r(fmaf(nmean_l, cs.y, -d.y) * rden_l), u1 = bf16r(fmaf(nmean_l, cs.w, -d.w) * rden_l);
                const uint32_t av = pack_neg(bf16r(g0 * sigmoid_approx(g0)) * u0, bf16r(g1 * sigmoid_approx(g1)) * u1);
                asm volatile("{\n.reg .pred p;\nsetp.eq.u32 p, %3, 3;\n@p st.relaxed.gpu.global.u32 [%0], %2;\n@p st.relaxed.gpu.global.u32 [%1], %2;\n}"
                             :: "l"(dst), "l"(dst2), "r"(av), "r"(is_f ? b : 0) : "memory");
                CK(7, 0);
                if (lane == 0 && is_f) TS2(14);
                if (gidx >= 0) {
                    fin_arrive<8>();
                    __syncwarp();
                    const float2 hw2 = lds64f(sb + SM_X + lb * HPITCH + ((gidx >> 1) * 16 + (lc & 6) * 2 + (gidx & 1) * 2) * 4);
                    const float nh0 = (lc & 1) ? hi_f(__float_as_uint(hw2.x)) : lo_f(__float_as_uint(hw2.x));
                    const float nh1 = (lc & 1) ? hi_f(__float_as_uint(hw2.y)) : lo_f(__float_as_uint(hw2.y));
                    float rr = 0.f;
#pragma unroll
                    for (int i = 0; i < 10; i++) rr = fmaf(lo_f(hw[i]), lo_f(wr[i]), fmaf(hi_f(hw[i]), hi_f(wr[i]), rr));
                    const float sig = bf16r(sigmoid_approx(bf16r((nmean * wsum - warp_sum(rr)) * rden)));
                    if (lb == b) sig_l = sig;
                    const float ln0 = bf16r(bf16r(nmean_l - nh0) * rden_l), ln1 = bf16r(bf16r(nmean_l - nh1) * rden_l);
                    fin_sync<6>(after(after(after(288, sig_l), ln0), ln1));
                    CK(10, lds32(ypart));
                    float2 t[16];
#pragma unroll
                    for (int i = 0; i < 16; i++) t[i] = lds64f(ypart + i * YPITCH);
#pragma unroll
                    for (int o = 1; o < 16; o <<= 1) {
#pragma unroll
                        for (int i = 0; i < 16; i += 2 * o) { t[i].x += t[i + o].x; t[i].y += t[i + o].y; }
                    }
                    const uint32_t ov = pack_bf16(bf16r(ln0 + bf16r(bf16r(-t[0].x) * sig_l)) - nh0, bf16r(ln1 + bf16r(bf16r(-t[0].y) * sig_l)) - nh1);
                    asm volatile("{\n.reg .pred p;\n.reg .b16 lo, hi;\nsetp.eq.u32 p, %2, 3;\nmov.b32 {lo, hi}, %1;\n"
                                 "@p st.global.u16 [%0], lo;\n@p st.global.u16 [%0 + 16], hi;\n}" :: "l"(out), "r"(ov), "r"(b) : "memory");
                    CK(11, 0);
                    if (lane == 0) TS2(13);
                }
                fin_sync<5>();
            }
            if (cta == 0 && lane == 0) { g_work[0] = 0; g_work[32] = 0; g_cnt_z[0] = 0; }
        }
        return;
    }
    if (warp >= NAUX) {
        const int wk = warp - NAUX;
        const uint32_t bar = sb + BAR_KV + wk * 8;
        const uint32_t buf = sb + SM_KV + wk * TILE_BYTES;
        uint64_t pol;
        asm volatile("createpolicy.fractional.L2::evict_first.b64 %0, 1.0;" : "=l"(pol));
        const int nstatic = NWORK * grid;
        constexpr int POOL0 = NUNITS - NPOOL;
        int uk = wk * grid + cta;
        if (lane == 0) {
            spin_ns(K0_DELAY_NS + wk * K0_STEP_NS);
            mbar_expect_tx(bar, TILE_BYTES);
            tma_tile(buf, &p.k, uk * TILE_ROWS, bar, pol);
        }
        __syncwarp();
        uint32_t koff[3], voff[3];
        {
            const int r = lane & 7, hf = (lane >> 3) & 1;
            const int kkey = hf ? 8 + (r ^ 1) : r;
            const int vh = lane >> 4;
            const int vkey = ((r & 1) ? 8 : 0) + (vh ? (r ^ 1) : r);
#pragma unroll
            for (int b = 0; b < 3; b++) {
                const int rk = 3 * kkey + b, rv = 3 * vkey + b;
                koff[b] = buf + rk * 128 + (((lane >> 4) ^ (rk & 7)) << 4);
                voff[b] = buf + rv * 128 + ((hf ^ (rv & 7)) << 4);
            }
        }
        uint32_t phase = 0;
        uint4 qf[6];
        auto load_q = [&](int u) {
            const uint32_t* q = &g_early[u / UPB].q[j * 4];
#pragma unroll
            for (int i = 0; i < 6; i++) qf[i] = ld_relaxed_v4(q + i * 16);
        };
        load_q(uk);
        int uq[LAG];
        uint32_t sq[LAG];
#pragma unroll
        for (int i = 0; i < LAG; i++) { uq[i] = -1; sq[i] = 0; }
        uint4 mv = make_uint4(0u, 0u, 0u, 0u);
        float freed = UPB;
        while (true) {
            const int uv = uq[0];
            uint32_t sv = sq[0];
#pragma unroll
            for (int i = 0; i + 1 < LAG; i++) { uq[i] = uq[i + 1]; sq[i] = sq[i + 1]; }
            uq[LAG - 1] = uk;
            if (uk < NUNITS) {
                PH(7);
#pragma unroll 1
                for (int it = 0; it < SPIN_MAX; it++) {
                    uint32_t lo = 0xffffffffu;
#pragma unroll
                    for (int i = 0; i < 6; i++) lo = min(min(lo, min(qf[i].x, qf[i].y)), min(qf[i].z, qf[i].w));
                    if (__all_sync(0xffffffffu, lo != 0)) break;
                    __nanosleep(QNAP);
                    load_q(uk);
                }
                mbar_wait(bar, phase); phase ^= 1;
                PH(0); ARR();
                TSI(0, 16); TSI(1, 18);
                float acc[2][4][4] = {};
#pragma unroll
                for (int ks = 0; ks < 12; ks++) {
                    const uint4 qq = qf[ks >> 1];
                    const uint32_t b0 = (ks & 1) ? qq.z : qq.x, b1 = (ks & 1) ? qq.w : qq.y;
#pragma unroll
                    for (int mt = 0; mt < 4; mt++) {
                        uint32_t a[4];
                        ldsm4(a, (koff[ks >> 2] ^ ((ks & 3) << 5)) + mt * 6144);
                        mma16816(acc[ks & 1][mt], a, b0, b1);
                    }
                }
                PH(1);
                TSI(0, 17); TSI(1, 19);
                if (uv < NUNITS) request_tile(buf, uv >= 0 ? &p.v : &p.k, uv >= 0 ? uv : uk + nstatic, bar, pol);
                const float sa = sel4(j, acc[0][0][0], acc[0][1][0], acc[0][2][0], acc[0][3][0]) + sel4(j, acc[1][0][0], acc[1][1][0], acc[1][2][0], acc[1][3][0]);
                const float sc = sel4(j, acc[0][0][2], acc[0][1][2], acc[0][2][2], acc[0][3][2]) + sel4(j, acc[1][0][2], acc[1][1][2], acc[1][2][2], acc[1][3][2]);
                const uint32_t raw = pack_bf16(sa, sc);
                const float scale = -0.07216878364870322f;
                const uint32_t sk = pack_bf16(lo_f(raw) * scale, hi_f(raw) * scale);
                sq[LAG - 1] = sk;
                if (uk >= POOL0) {
                    uint32_t* sdst = score_at(0, uk, lane);
                    st_relaxed(sdst, sk ? sk : 0x80008000u);
                    if (uk >= NUNITS - NSS) st_relaxed(other_side(sdst), sk ? sk : 0x80008000u);
                }
                int a = (int)(sk << 16), b = (int)(sk & 0xffff0000u);
                a ^= (a >> 31) & 0x7fff0000; b ^= (b >> 31) & 0x7fff0000;
                const int mx = __reduce_max_sync(0xffffffffu, max(a, b));
                if (lane == 0) st_relaxed(&g_early[uk / UPB].umax[uk % UPB], (uint32_t)mx | 1u);
            }
            if (uv < 0) {
                uk += nstatic;
                load_q(uk);
                continue;
            }
            if (uv >= NUNITS) break;
            const int bh = uv / UPB;
#pragma unroll 1
            for (int it = 0; it < SPIN_MAX; it++) {
                if (__all_sync(0xffffffffu, (mv.x & mv.y & mv.z & mv.w & 1u) && (uv < POOL0 || sv != 0) && freed == UPB)) break;
                mv = ld_relaxed_v4(&g_early[bh].umax[lane * 4]);
                if (bh >= RING && bh < RED0) freed = __uint_as_float(ld_relaxed_u32(&g_st.oacc[bh - RING][(lane & 7) * 8].w));
                if (uv >= POOL0) sv = ld_relaxed_u32(score_at(lds32(sb + SM_SIDE), uv, lane));
            }
            PH(2);
            int un = NUNITS, vn = 0;
            draw(un, g_work, uk < NUNITS && lane == 0);
            int mx = __reduce_max_sync(0xffffffffu, max(max((int)mv.x, (int)mv.y), max((int)mv.z, (int)mv.w))) & 0xffff0000;
            mx ^= (mx >> 31) & 0x7fff0000;
            const float m = __int_as_float(mx);
            const float l2e = 1.4426950408889634f;
            const uint32_t pp = pack_bf16(exp2f((lo_f(sv) - m) * l2e), exp2f((hi_f(sv) - m) * l2e));
            uint32_t pb[8];
#pragma unroll
            for (int t = 0; t < 4; t++) {
                pb[2 * t] = __shfl_sync(0xffffffffu, pp, 8 * j + t);
                pb[2 * t + 1] = __shfl_sync(0xffffffffu, pp, 8 * j + 4 + t);
            }
            float lacc[4] = {};
            const uint32_t ones[4] = {0x3f803f80u, 0x3f803f80u, 0x3f803f80u, 0x3f803f80u};
#pragma unroll
            for (int t = 0; t < 4; t++) mma16816(lacc, ones, pb[2 * t], pb[2 * t + 1]);
            if (uv < nstatic) {
                asm volatile("bar.sync 2, %0;" :: "n"((NWORK + 1) * 32) : "memory");
                TSW(3);
            }
            const int grp = 16 * j + 4 * (g & 1) + (g >> 1);
            const int acc_row = bh >= NBH - 4 && uv % OREP ? bh + 4 * (uv % OREP) : bh;
            float4* dst = bh < RED0 ? &g_ring[bh % RING][uv % UPB][grp] : oacc_at(FARFIRST ? lds32(sb + SM_SIDE) ^ 1 : 0, acc_row, grp);
            float4* dst2 = other_side(dst);
            float2* ldst = lsum_at(lane & 1, acc_row);
            if (bh >= SROW0 && lane < 2) red_f2(&ldst->x, lacc[0], 1.f);
            float tag = bh < RED0 ? (float)(bh + 1) : 1.f;
            un = __shfl_sync(0xffffffffu, un, 0) + (LAG + 1) * nstatic;
            uint32_t pooled = uq[0] >= POOL0 && lane == 0;
            pin(dst); pin(dst2); pin(ldst); pin(tag); pin(voff[0]); pin(voff[1]); pin(voff[2]); pin(pooled);
            PH(3);
            mbar_wait(bar, phase); phase ^= 1;
            PH(4); ARR();
            draw(vn, g_work + 32, pooled);
            float acc[12][4] = {};
#pragma unroll
            for (int t = 0; t < 4; t++) {
#pragma unroll
                for (int mt = 0; mt < 12; mt++) {
                    uint32_t a[4];
                    ldsm4t(a, (voff[mt >> 2] ^ ((mt & 3) << 5)) + t * 6144);
                    mma16816(acc[mt], a, pb[2 * t], pb[2 * t + 1]);
                }
            }
            PH(5);
            if (lane == 0) PROG(un);
            if (un < NUNITS) request_tile(buf, &p.k, un, bar, pol);
            float o[6];
#pragma unroll
            for (int e = 0; e < 6; e++) {
                const int q = e % 3, c = (e / 3) * 2;
                o[e] = sel4(j, acc[q][c], acc[3 + q][c], acc[6 + q][c], acc[9 + q][c]);
            }
            if (bh >= SROW0) {
                red_f4(&dst->x, o[0], o[1], o[2], tag);
                red_f4(&dst[SPREAD ? 16 : 8].x, o[3], o[4], o[5], tag);
                red_f4(&dst2->x, o[0], o[1], o[2], tag);
                red_f4(&dst2[SPREAD ? 16 : 8].x, o[3], o[4], o[5], tag);
            } else {
                if (bh >= RED0) {
                    red_f4(&dst->x, o[0], o[1], o[2], tag);
                    red_f4(&dst[8].x, o[3], o[4], o[5], tag);
                } else {
                    st_relaxed_b128(dst, o[0], o[1], o[2], tag);
                    st_relaxed_b128(dst + 8, o[3], o[4], o[5], tag);
                }
                if (lane == 0) red_f2(&ldst->x, lacc[0], 1.f);
            }
            if (uq[0] >= POOL0) {
                vn = __shfl_sync(0xffffffffu, vn, 0);
                uq[0] = POOL0 + vn;
                if (vn == VTRIG && lane == 0) st_relaxed(g_st.tstart, (now_ns() + TRIG_NS) | 1u);
            }
            if (un < NUNITS) load_q(un);
            else if (uq[0] < NUNITS) request_tile(buf, &p.v, uq[0], bar, pol);
            PH(6);
            if (uq[0] >= NUNITS && un >= NUNITS) break;
            uk = un;
            if (uq[0] < NUNITS) {
                const int nb = uq[0] / UPB;
                mv = ld_relaxed_v4(&g_early[nb].umax[lane * 4]);
                freed = nb >= RING && nb < RED0 ? __uint_as_float(ld_relaxed_u32(&g_st.oacc[nb - RING][(lane & 7) * 8].w)) : UPB;
                if (uq[0] >= POOL0) sq[0] = ld_relaxed_u32(score_at(lds32(sb + SM_SIDE), uq[0], lane));
            }
        }
        return;
    }

    __nv_bfloat16* xs = reinterpret_cast<__nv_bfloat16*>(smem + SM_X);
    float* red = reinterpret_cast<float*>(smem + SM_RED);
    const int frow = (lane & 7) + ((lane >> 4) << 3), fcol = (lane >> 3) & 1;
    if (cta < NQ_CTAS) {
        uint2 xr[5];
        if (warp < NB) {
#pragma unroll
            for (int i = 0; i < 5; i++) xr[i] = *reinterpret_cast<const uint2*>(p.x + warp * DM + i * 128 + lane * 4);
        }
        TS(26);
        if (warp < NB) {
            float v[20];
#pragma unroll
            for (int i = 0; i < 5; i++) {
                v[4 * i] = lo_f(xr[i].x); v[4 * i + 1] = hi_f(xr[i].x); v[4 * i + 2] = lo_f(xr[i].y); v[4 * i + 3] = hi_f(xr[i].y);
            }
            layernorm20(v);
#pragma unroll
            for (int i = 0; i < 5; i++)
                *reinterpret_cast<uint2*>(xs + warp * XPITCH + i * 128 + lane * 4) =
                    make_uint2(pack_bf16(v[4 * i], v[4 * i + 1]), pack_bf16(v[4 * i + 2], v[4 * i + 3]));
        }
        TS(27);
        aux_sync();
        mbar_wait(sb + BAR_WQ, 0);
        TS(1);
        const uint32_t xfrag = sb + SM_X + ((g & 3) * XPITCH + 2 * j) * 2;
        float acc[3][4] = {};
#pragma unroll
        for (int s = 0; s < 5; s++) {
            const int ks = warp * 5 + s;
            const uint32_t b0 = lds32(xfrag + ks * 32), b1 = lds32(xfrag + ks * 32 + 16);
            const int row = ks * 16 + frow;
#pragma unroll
            for (int mt = 0; mt < 3; mt++) {
                uint32_t a[4];
                ldsm4t(a, sb + SM_WQ + (row * 6 + 2 * mt + fcol) * 16);
                mma16816(acc[mt], a, b0, b1);
            }
        }
        if (j < 2) {
#pragma unroll
            for (int mt = 0; mt < 3; mt++) {
                *reinterpret_cast<float2*>(red + (warp * 48 + mt * 16 + g) * 4 + 2 * j) = make_float2(acc[mt][0], acc[mt][1]);
                *reinterpret_cast<float2*>(red + (warp * 48 + mt * 16 + 8 + g) * 4 + 2 * j) = make_float2(acc[mt][2], acc[mt][3]);
            }
        }
        aux_sync();
        if (tid < 96) {
            const int b = tid & 3, cp = tid >> 2;
            float s0 = 0.f, s1 = 0.f;
#pragma unroll
            for (int w = 0; w < 8; w++) { s0 += red[(w * 48 + 2 * cp) * 4 + b]; s1 += red[(w * 48 + 2 * cp + 1) * 4 + b]; }
            const int h = cta >> 2, d = (cta & 3) * 48 + 2 * cp;
            const int ch = d >> 3, jj = (d & 7) >> 1;
            st_relaxed(&g_early[b * NH + h].q[(ch >> 2) * 16 + jj * 4 + (ch & 3)], pack_neg(s0, s1));
        }
        TS(28);
    }
    if (tid < 160) *reinterpret_cast<uint2*>(smem + SM_X + 4 * HPITCH + tid * 8) = make_uint2(0x3f803f80u, 0x3f803f80u);
    fin_sync<3>();
    const int side = lds32(sb + SM_SIDE);
    mbar_wait(sb + BAR_W, 0);
    TS(7);
    uint32_t part = sb + SM_RED + (warp * 32 + 8 * j + g) * 4;

#pragma unroll 1
    for (int b = 0; b < NB; b++) {
        if (b == NB - 1 && !is_f) asm volatile("bar.arrive 9, 288;" ::: "memory");
        if (is_l) {
            uint32_t a[6][2][4];
#pragma unroll
            for (int s = 0; s < 6; s++) {
                const int row = (warp * 6 + s) * 16 + frow;
#pragma unroll
                for (int mt = 0; mt < 2; mt++) ldsm4t(a[s][mt], sb + SM_A + (row * 4 + ((2 * mt + fcol) ^ ((row >> 1) & 3))) * 16);
            }
            const int bh = b * NH + 28 + (warp >> 1);
            const float4* osrc[OREP];
            const float2* lsrc[OREP];
#pragma unroll
            for (int c = 0; c < OREP; c++) {
                const int row = b == NB - 1 ? bh + 4 * c : bh;
                osrc[c] = oacc_at(side, row, (warp & 1) * 32 + lane);
                lsrc[c] = lsum_at(side, row);
                pin(osrc[c]); pin(lsrc[c]);
            }
            if (lane == 0) wait_row_o(side, bh, 1);
            __syncwarp();
            float2 lv;
#pragma unroll 1
            for (int it = 0; it < SPIN_MAX; it++) {
                lv = ld_relaxed_f2(lsrc[0]);
#pragma unroll
                for (int c = 1; c < OREP; c++) {
                    const float2 lc = ld_relaxed_f2(lsrc[c]);
                    if (b == NB - 1) { lv.x += lc.x; lv.y += lc.y; }
                }
                if (__all_sync(0xffffffffu, lv.y == UPB)) break;
            }
            if (warp == 7) TSW(25);
            float rl = rcp_approx(lv.x);
            float4 ov;
            pin(part); pin(rl);
            if (OPRE && lane == 0) {
#pragma unroll 1
                for (int it = 0; it < SPIN_MAX; it++) {
                    if (__uint_as_float(ld_relaxed_u32(&osrc[0]->w)) >= UPB * OPRE / (16 * OREP)) break;
                    if (ONAP) __nanosleep(ONAP);
                }
            }
            __syncwarp();
#pragma unroll 1
            for (int it = 0; it < SPIN_MAX; it++) {
                float4 oc[OREP];
#pragma unroll
                for (int c = 0; c < OREP; c++) oc[c] = ld_relaxed_f4(osrc[c]);
                ov = oc[0];
                if (b == NB - 1) {
#pragma unroll
                    for (int c = 1; c < OREP; c++) { ov.x += oc[c].x; ov.y += oc[c].y; ov.z += oc[c].z; ov.w += oc[c].w; }
                }
                if (__all_sync(0xffffffffu, ov.w == UPB)) break;
            }
            CK(0, __float_as_uint(ov.x));
            const float px = __shfl_xor_sync(0xffffffffu, ov.x, 4), py = __shfl_xor_sync(0xffffffffu, ov.y, 4),
                        pz = __shfl_xor_sync(0xffffffffu, ov.z, 4);
            const uint32_t w[3] = {pack_bf16(ov.x * rl, px * rl), pack_bf16(ov.y * rl, py * rl), pack_bf16(ov.z * rl, pz * rl)};
            float acc[2][2][4] = {};
#pragma unroll
            for (int s = 0; s < 6; s++) {
                const uint32_t b0 = __shfl_sync(0xffffffffu, w[s % 3], (s / 3) * 16 + j);
                const uint32_t b1 = __shfl_sync(0xffffffffu, w[s % 3], (s / 3) * 16 + 8 + j);
#pragma unroll
                for (int mt = 0; mt < 2; mt++) mma16816(acc[mt][s & 1], a[s][mt], b0, b1);
            }
            sts32f(part, sel4(j, acc[0][0][0] + acc[0][1][0], acc[0][0][2] + acc[0][1][2], acc[1][0][0] + acc[1][1][0], acc[1][0][2] + acc[1][1][2]));
            CK(1, 0);
            fin_arrive<4>();
            if (warp == 7) TSW(30);
            if (warp == 5) TSW(31);
            if (cta == NE_CTAS && lane < 28) reinterpret_cast<uint4*>(&g_early[bh])[(warp & 1) * 28 + lane] = make_uint4(0u, 0u, 0u, 0u);
        } else {
            const int bh = b * NH + (cta >> 2);
            if (tid == 0) wait_row_o(side, bh, UPB);
            aux_sync();
            if (warp < 5) {
                uint32_t ob[12][2];
                load_o<4>(ob, bh, 0, j);
                float acc[2][2][4] = {};
#pragma unroll
                for (int ks = 0; ks < 12; ks++) {
                    const int row = ks * 16 + frow;
#pragma unroll
                    for (int mt = 0; mt < 2; mt++) {
                        uint32_t a[4];
                        ldsm4t(a, sb + SM_A + warp * 12288 + (row * 4 + ((2 * mt + fcol) ^ ((row >> 1) & 3))) * 16);
                        mma16816(acc[mt][ks & 1], a, ob[ks][0], ob[ks][1]);
                    }
                }
                red_f2(&g_st.attn[b][(cta & 3) * 160 + warp * 32 + 8 * j + g].x,
                       sel4(j, acc[0][0][0] + acc[0][1][0], acc[0][0][2] + acc[0][1][2], acc[1][0][0] + acc[1][1][0], acc[1][0][2] + acc[1][1][2]), 1.f);
                TS(8);
            } else if (warp > 5 && (cta & 3) == 0 && tid - 192 < 56) {
                reinterpret_cast<uint4*>(&g_early[bh])[tid - 192] = make_uint4(0u, 0u, 0u, 0u);
            }
        }
        if (b == NB - 1 && is_f) asm volatile("bar.arrive 9, 288;" ::: "memory");

        uint32_t wb[3][2][2][4];
        if (b == NB - 1 && gidx >= 0) {
            mbar_wait(sb + BAR_D + warp * 8, 0);
            if (warp == NAUX - 1 && !is_f) TSW(10);
        }
#pragma unroll
        for (int s = 0; s < 12; s++) {
            const int odd = (lane >> 2) & 1, c = ((lane & 2) * 2 + (s & 1) * 2 + (lane >> 4)) ^ (2 * odd);
            const int row = (warp * 12 + (s >> 1) * 2 + odd) * 16 + ((lane & 1) ? 8 + (c ^ 1) : c);
            ldsm4t(wb[s >> 2][(s >> 1) & 1][s & 1], sm_d + (row * 2 + (fcol ^ ((row >> 2) & 1))) * 16);
        }
        if (is_f) {
            const int kq = warp >> 1, t = warp & 1;
            uint32_t hfrag = sb + SM_X + min(g, 4) * HPITCH + (kq * 80 + 4 * j) * 4;
            uint4 hv[5] = {};
#pragma unroll
            for (int s = 0; s < 5; s++) lds128_if(hv[s], hfrag + s * 64, true);
            if (b == NB - 1) {
                mbar_wait(sb + BAR_G + kq * 8, 0);
                if (warp == NAUX - 1) TSW(9);
            }
            uint32_t ga[10][4];
#pragma unroll
            for (int s = 0; s < 10; s++) {
                const int row = (kq * 10 + s) * 16 + frow;
                ldsm4t(ga[s], sb + SM_G + fcol * 20480 + (row * 2 + (t ^ ((row >> 2) & 1))) * 16);
            }
            uint32_t fpart = sb + SM_RED + 2 * j * FPITCH + kq * 128 + (g ^ t) * 16 + t * 8;
            pin(fpart); pin(hfrag);
            fin_sync<7>();
#pragma unroll
            for (int s = 0; s < 5; s++) lds128_if(hv[s], hfrag + s * 64, g == b);
            float acc[2][4] = {};
#pragma unroll
            for (int s = 0; s < 5; s++) {
                mma16816(acc[0], ga[2 * s], hv[s].x, hv[s].y);
                mma16816(acc[1], ga[2 * s + 1], hv[s].z, hv[s].w);
            }
#pragma unroll
            for (int e = 0; e < 2; e++) sts64f(fpart + e * FPITCH, acc[0][e] + acc[1][e], acc[0][2 + e] + acc[1][2 + e], 2 * j + e < 5);
            CK(5, 0);
            fin_arrive<4>();
        }
        if (gidx >= 0) {
            const uint4* asrc[3];
#pragma unroll
            for (int q = 0; q < 3; q++) {
                asrc[q] = sided<uint4>(side, X_A + (warp * 12 + 4 * q + 2 * (g >> 2) + (j >> 1)) * 128 + (g & 3) * 32 + (j & 1) * 16);
                pin(asrc[q]);
            }
            uint32_t ypart = sb + SM_RED2 + (warp * 2 + (j >> 1)) * YPITCH + (j & 1) * 160 + g * 16;
            pin(ypart);
            fin_sync<8>();
            uint4 v[3];
#pragma unroll 1
            for (int it = 0; it < SPIN_MAX; it++) {
                uint32_t lo = 0xffffffffu;
#pragma unroll
                for (int q = 0; q < 3; q++) v[q] = ld_relaxed_v4(asrc[q]);
#pragma unroll
                for (int q = 0; q < 3; q++) lo = min(min(lo, min(v[q].x, v[q].y)), min(v[q].z, v[q].w));
                if (__all_sync(0xffffffffu, lo != 0 || b < NB - 1)) break;
            }
            CK(8, v[0].x);
            float acc[2][2][4] = {};
#pragma unroll
            for (int q = 0; q < 3; q++) {
#pragma unroll
                for (int pr = 0; pr < 2; pr++) {
                    mma16816(acc[pr][0], wb[q][pr][0], v[q].x, v[q].y);
                    mma16816(acc[pr][1], wb[q][pr][1], v[q].z, v[q].w);
                }
            }
            float y[4];
#pragma unroll
            for (int e = 0; e < 4; e++) y[e] = j < 2 ? acc[0][0][e] + acc[0][1][e] : acc[1][0][e] + acc[1][1][e];
            asm volatile("st.shared.v4.f32 [%0], {%1,%2,%3,%4};" :: "r"(ypart), "f"(y[0]), "f"(y[2]), "f"(y[1]), "f"(y[3]) : "memory");
            CK(9, 0);
            fin_arrive<6>();
        }
        fin_sync<5>();
    }
}

typedef CUresult (*EncodeFn)(CUtensorMap*, CUtensorMapDataType, cuuint32_t, void*, const cuuint64_t*, const cuuint64_t*,
                             const cuuint32_t*, const cuuint32_t*, CUtensorMapInterleave, CUtensorMapSwizzle,
                             CUtensorMapL2promotion, CUtensorMapFloatOOBfill);

CUtensorMap make_map(EncodeFn enc, void* ptr, uint64_t cols, uint64_t rows, uint32_t bcols, uint32_t brows,
                     CUtensorMapSwizzle sw, CUtensorMapL2promotion promo) {
    CUtensorMap m;
    const cuuint64_t dims[2] = {cols, rows};
    const cuuint64_t strides[1] = {cols * 2};
    const cuuint32_t box[2] = {bcols, brows};
    const cuuint32_t es[2] = {1, 1};
    enc(&m, CU_TENSOR_MAP_DATA_TYPE_BFLOAT16, 2, ptr, dims, strides, box, es, CU_TENSOR_MAP_INTERLEAVE_NONE, sw, promo,
        CU_TENSOR_MAP_FLOAT_OOB_FILL_NONE);
    return m;
}

}

extern "C" void kernel_launch(void* const* d_in, const int* in_sizes, int n_in, void* d_out, int out_size) {
    (void)in_sizes; (void)n_in; (void)out_size;
    static EncodeFn enc = nullptr;
    static int sms = 0;
    if (!enc) {
        cudaDriverEntryPointQueryResult qr;
        cudaGetDriverEntryPoint("cuTensorMapEncodeTiled", (void**)&enc, cudaEnableDefault, &qr);
        int dev = 0;
        cudaGetDevice(&dev);
        cudaDeviceGetAttribute(&sms, cudaDevAttrMultiProcessorCount, dev);
        cudaFuncSetAttribute(fused_decode_kernel, cudaFuncAttributeMaxDynamicSharedMemorySize, SM_TOTAL);
    }
    if (sms < NCTAS) return;
    const CUtensorMapL2promotion WPROMO = CU_TENSOR_MAP_L2_PROMOTION_L2_128B;
    Params p;
    p.k = make_map(enc, d_in[1], 64, (uint64_t)NBH * SK * 3, 64, TILE_ROWS, CU_TENSOR_MAP_SWIZZLE_128B, CU_TENSOR_MAP_L2_PROMOTION_NONE);
    p.v = make_map(enc, d_in[2], 64, (uint64_t)NBH * SK * 3, 64, TILE_ROWS, CU_TENSOR_MAP_SWIZZLE_128B, CU_TENSOR_MAP_L2_PROMOTION_NONE);
    p.wq = make_map(enc, d_in[3], NH * DH, DM, 48, 160, CU_TENSOR_MAP_SWIZZLE_NONE, WPROMO);
    p.wo = make_map(enc, d_in[4], DM, NH * DH, 32, WO_ROWS, CU_TENSOR_MAP_SWIZZLE_64B, WPROMO);
    p.wg = make_map(enc, d_in[7], FF, DM, 16, 80, CU_TENSOR_MAP_SWIZZLE_32B, (CUtensorMapL2promotion)GPROMO);
    p.wu = make_map(enc, d_in[8], FF, DM, 16, 80, CU_TENSOR_MAP_SWIZZLE_32B, (CUtensorMapL2promotion)GPROMO);
    p.wd = make_map(enc, d_in[9], DM, FF, 16, 192, CU_TENSOR_MAP_SWIZZLE_32B, WPROMO);
    p.x = (const __nv_bfloat16*)d_in[0];
    p.wr = (const __nv_bfloat16*)d_in[6];
    p.out = (__nv_bfloat16*)d_out;
    fused_decode_kernel<<<NCTAS, NTHREADS, SM_TOTAL, cudaStreamPerThread>>>(p);
}
```

```cpp
#include <cuda_runtime.h>
#include <cuda_bf16.h>
#include <cuda.h>
#include <stdint.h>

namespace {

constexpr int NB = 4, NH = 32, SK = 8192, DH = 192, DM = 640, FF = 1536;
constexpr int NBH = NB * NH;
constexpr int TILE = 64;
constexpr int UPB = SK / TILE;
constexpr int NUNITS = NBH * UPB;
constexpr int TILE_BYTES = TILE * DH * 2;
constexpr int TILE_ROWS = TILE * 3;
constexpr int NCTAS = 132;
constexpr int NQ_CTAS = 128;
constexpr int NE_CTAS = 112;

#define NWORK 2
#define LAG 2
#define NPOOL 640
#define RED0 116
#define RING 12
#define OREP 1
#define SROW0 124
#define NPROBE 6
#define VTRIG 400
#define TRIG_NS 2100
#define GPROMO 2
#define DCLK 150
#define DOFF 2300
#define HNAP 100
#define PAD0 1024
#define PAD1 1024
#define PAD2 1792
#define JIT 1
#define FARFIRST 1
#define OPRE 0
#define ONAP 0
#define NSS 0
#define FWAIT 32
#define SPREAD 1
#define GDLY 0
#define GPRED 1
#define GCLK 250
#define K0_DELAY_NS 1700
#define K0_STEP_NS 900
#define WO_GAP_NS 550
#define WO_ROWS 48
#define QNAP 250
#define WO_AT_NS 3600
constexpr int NAUX = 8;
constexpr int NTHREADS = (NAUX + NWORK + 2) * 32;
constexpr int SPIN_MAX = 1 << 22;

constexpr int SM_KV = 0;
constexpr int SM_A = SM_KV + NWORK * TILE_BYTES;
constexpr int SM_WQ = SM_A + 61440;
constexpr int SM_G = SM_WQ;
constexpr int SM_X = SM_G + 81920;
constexpr int XPITCH = 648;
constexpr int HPITCH = 1344;
constexpr int SM_RED = SM_X + 5 * HPITCH;
constexpr int FPITCH = 1040;
constexpr int SM_RED2 = SM_RED;
constexpr int YPITCH = 320;
constexpr int SM_MISC = SM_RED + 6144;
constexpr int BAR_KV = SM_MISC, BAR_WQ = SM_MISC + 32, BAR_W = SM_MISC + 40, SM_SIDE = SM_MISC + 48, BAR_G = SM_MISC + 64, SM_MOM = SM_MISC + 128;
constexpr int SM_TOTAL = SM_MISC + 160;

struct Params {
    CUtensorMap k, v;
    CUtensorMap wq;
    CUtensorMap wo;
    CUtensorMap wg, wu;
    CUtensorMap wd;
    const __nv_bfloat16 *x, *wr;
    __nv_bfloat16* out;
};

struct Early {
    uint32_t q[96];
    uint32_t umax[UPB];
};
#define LSTRIDE 16
struct State {
    float4 oacc[SROW0][64];
    float2 attn[NB][DM];
    float2 lsum[SROW0][LSTRIDE];
    unsigned pool[64];
    uint32_t tstart[32];
    uint32_t score[NPOOL - NSS][32];
};
constexpr int STATE_V4 = ((sizeof(State) / 32 + NQ_CTAS - 1) / NQ_CTAS) * 2;
static_assert(sizeof(State) % 32 == 0, "State is cleared in whole sectors");
static_assert(sizeof(Early) == 56 * 16, "an Early entry is cleared by 56 threads");
constexpr uint32_t X_O = 0;
constexpr uint32_t X_L = X_O + 4 * OREP * 1024;
constexpr uint32_t X_H = X_L + 4 * OREP * 128;
constexpr uint32_t X_A = X_H + NB * DM * 2;
constexpr uint32_t X_P = X_A + NB * FF * 2;
constexpr uint32_t X_S = X_P + 4096;
constexpr uint32_t X_END = X_S + NSS * 128;
static_assert(X_END <= 16 * 4096 && SROW0 == NBH - 4, "");
struct Scratch {
    unsigned char sided[16][2][4096];
    unsigned work[64];
    unsigned cnt_z[32];
    unsigned char pad0[PAD0];
    Early early[NBH];
    unsigned char pad1[PAD1];
    State st;
    unsigned char pad2[PAD2];
    float4 ring[RING][UPB][64];
};
constexpr size_t PAGE = 2u << 20;
static_assert(sizeof(Scratch) <= PAGE, "scratch must fit one page");
__device__ __align__(128) unsigned char g_raw[2 * PAGE];
__device__ __forceinline__ Scratch* scratch() {
    return reinterpret_cast<Scratch*>((reinterpret_cast<uintptr_t>(g_raw) + PAGE - 1) & ~(uintptr_t)(PAGE - 1));
}
template <typename T> __device__ __forceinline__ T* sided(int side, uint32_t x) {
    const uint32_t pair = (x >> 10) & 15;
    return reinterpret_cast<T*>(&scratch()->sided[pair][(side ^ pair ^ (pair >> 3)) & 1]
                                    [(x & 127) + ((x & 128) << 1) + ((x & 768) << 2) + ((x >> 7) & 128) + ((x >> 6) & 512)]);
}
template <typename T> __device__ __forceinline__ T* other_side(T* p) { return reinterpret_cast<T*>(reinterpret_cast<uintptr_t>(p) ^ 4096); }
#define g_early scratch()->early
#define g_st scratch()->st
#define g_ring scratch()->ring
#define g_cnt_z scratch()->cnt_z
#define g_work scratch()->work
#define TS(i)
#define TSW(i)
#define TS2(i)
#define TSI(n, i)
#define PH(i)
#define CK(i, dep)
#define ARR()
#define PROG(u)

__device__ __forceinline__ uint32_t s2u(const void* p) { return (uint32_t)__cvta_generic_to_shared(p); }
__device__ __forceinline__ void mbar_init(uint32_t bar, int cnt) {
    asm volatile("mbarrier.init.shared::cta.b64 [%0], %1;" :: "r"(bar), "r"(cnt) : "memory");
}
__device__ __forceinline__ void mbar_expect_tx(uint32_t bar, uint32_t bytes) {
    asm volatile("mbarrier.arrive.expect_tx.shared::cta.b64 _, [%0], %1;" :: "r"(bar), "r"(bytes) : "memory");
}
__device__ __forceinline__ void mbar_wait(uint32_t bar, uint32_t parity) {
    asm volatile("{\n.reg .pred p;\n.reg .u32 n;\nmov.u32 n, 0;\nWAIT_LOOP:\n"
                 "mbarrier.try_wait.parity.shared::cta.b64 p, [%0], %1;\n"
                 "@p bra WAIT_DONE;\nadd.u32 n, n, 1;\nsetp.lt.u32 p, n, %2;\n@p bra WAIT_LOOP;\nWAIT_DONE:\n}"
                 :: "r"(bar), "r"(parity), "n"(SPIN_MAX) : "memory");
}
__device__ __forceinline__ void tma_tile(uint32_t dst, const CUtensorMap* tm, int row, uint32_t bar, uint64_t pol) {
    asm volatile("cp.async.bulk.tensor.2d.shared::cluster.global.mbarrier::complete_tx::bytes.L2::cache_hint "
                 "[%0], [%1, {%3, %4}], [%2], %5;"
                 :: "r"(dst), "l"(tm), "r"(bar), "r"(0), "r"(row), "l"(pol) : "memory");
}
__device__ __forceinline__ void request_tile(uint32_t dst, const CUtensorMap* tm, int unit, uint32_t bar, uint64_t pol) {
    asm volatile("{\n.reg .pred p;\nelect.sync _|p, 0xffffffff;\n"
                 "@p mbarrier.arrive.expect_tx.shared::cta.b64 _, [%2], %6;\n"
                 "@p cp.async.bulk.tensor.2d.shared::cluster.global.mbarrier::complete_tx::bytes.L2::cache_hint "
                 "[%0], [%1, {%3, %4}], [%2], %5;\n}"
                 :: "r"(dst), "l"(tm), "r"(bar), "r"(0), "r"(unit * TILE_ROWS), "l"(pol), "n"(TILE_BYTES) : "memory");
}
__device__ __forceinline__ uint32_t now_ns() { uint32_t t; asm volatile("mov.u32 %0, %%globaltimer_lo;" : "=r"(t)); return t; }
__device__ __forceinline__ uint32_t now_clk() { uint32_t t; asm volatile("mov.u32 %0, %%clock;" : "=r"(t)); return t; }
__device__ __forceinline__ void wait_clk(uint32_t t) { while (__any_sync(0xffffffffu, (int)(now_clk() - t) < 0)) {} }
constexpr uint64_t EVICT_FIRST = 0x12F0000000000000ull, EVICT_NORMAL = 0x1000000000000000ull;
__device__ __forceinline__ void request_box(uint32_t dst, const CUtensorMap* tm, int col, int row, uint32_t bar, uint64_t pol) {
    asm volatile("{\n.reg .pred p;\nelect.sync _|p, 0xffffffff;\n"
                 "@p cp.async.bulk.tensor.2d.shared::cluster.global.mbarrier::complete_tx::bytes.L2::cache_hint [%0], [%1, {%3, %4}], [%2], %5;\n}"
                 :: "r"(dst), "l"(tm), "r"(bar), "r"(col), "r"(row), "l"(pol) : "memory");
}
__device__ __forceinline__ uint32_t lds32(uint32_t addr) {
    uint32_t v;
    asm volatile("ld.shared.u32 %0, [%1];" : "=r"(v) : "r"(addr) : "memory");
    return v;
}
__device__ __forceinline__ void ldsm4(uint32_t (&r)[4], uint32_t addr) {
    asm volatile("ldmatrix.sync.aligned.m8n8.x4.shared.b16 {%0,%1,%2,%3}, [%4];"
                 : "=r"(r[0]), "=r"(r[1]), "=r"(r[2]), "=r"(r[3]) : "r"(addr) : "memory");
}
__device__ __forceinline__ void ldsm4t(uint32_t (&r)[4], uint32_t addr) {
    asm volatile("ldmatrix.sync.aligned.m8n8.x4.trans.shared.b16 {%0,%1,%2,%3}, [%4];"
                 : "=r"(r[0]), "=r"(r[1]), "=r"(r[2]), "=r"(r[3]) : "r"(addr) : "memory");
}
__device__ __forceinline__ void mma16816(float (&c)[4], const uint32_t (&a)[4], uint32_t b0, uint32_t b1) {
    asm volatile("mma.sync.aligned.m16n8k16.row.col.f32.bf16.bf16.f32 {%0,%1,%2,%3}, {%4,%5,%6,%7}, {%8,%9}, {%0,%1,%2,%3};"
                 : "+f"(c[0]), "+f"(c[1]), "+f"(c[2]), "+f"(c[3])
                 : "r"(a[0]), "r"(a[1]), "r"(a[2]), "r"(a[3]), "r"(b0), "r"(b1));
}
__device__ __forceinline__ uint4 ld_relaxed_v4(const void* p) {
    uint4 v;
    asm volatile("ld.relaxed.gpu.global.v4.u32 {%0,%1,%2,%3}, [%4];" : "=r"(v.x), "=r"(v.y), "=r"(v.z), "=r"(v.w) : "l"(p) : "memory");
    return v;
}
__device__ __forceinline__ float4 ld_relaxed_f4(const void* p) {
    float4 v;
    asm volatile("ld.relaxed.gpu.global.v4.f32 {%0,%1,%2,%3}, [%4];" : "=f"(v.x), "=f"(v.y), "=f"(v.z), "=f"(v.w) : "l"(p) : "memory");
    return v;
}
__device__ __forceinline__ float2 ld_relaxed_f2(const void* p) {
    float2 v;
    asm volatile("ld.relaxed.gpu.global.v2.f32 {%0,%1}, [%2];" : "=f"(v.x), "=f"(v.y) : "l"(p) : "memory");
    return v;
}
__device__ __forceinline__ float4 ld_relaxed_b128(const void* p) {
    float4 v;
    asm volatile("{\n.reg .b128 t;\n.reg .b64 a, b;\nld.relaxed.gpu.global.b128 t, [%4];\nmov.b128 {a, b}, t;\n"
                 "mov.b64 {%0, %1}, a;\nmov.b64 {%2, %3}, b;\n}" : "=f"(v.x), "=f"(v.y), "=f"(v.z), "=f"(v.w) : "l"(p) : "memory");
    return v;
}
__device__ __forceinline__ void st_relaxed_b128(void* p, float x, float y, float z, float w) {
    asm volatile("{\n.reg .b128 t;\n.reg .b64 a, b;\nmov.b64 a, {%1, %2};\nmov.b64 b, {%3, %4};\nmov.b128 t, {a, b};\n"
                 "st.relaxed.gpu.global.b128 [%0], t;\n}" :: "l"(p), "f"(x), "f"(y), "f"(z), "f"(w) : "memory");
}
__device__ __forceinline__ unsigned ld_acquire(const unsigned* p) {
    unsigned v;
    asm volatile("ld.acquire.gpu.global.u32 %0, [%1];" : "=r"(v) : "l"(p) : "memory");
    return v;
}
__device__ __forceinline__ void st_relaxed(void* p, uint32_t v) {
    asm volatile("st.relaxed.gpu.global.u32 [%0], %1;" :: "l"(p), "r"(v) : "memory");
}
__device__ __forceinline__ void red_f2(float* p, float a, float b) {
    asm volatile("red.relaxed.gpu.global.add.v2.f32 [%0], {%1,%2};" :: "l"(p), "f"(a), "f"(b) : "memory");
}
__device__ __forceinline__ void red_f4(float* p, float a, float b, float c, float d) {
    asm volatile("red.relaxed.gpu.global.add.v4.f32 [%0], {%1,%2,%3,%4};" :: "l"(p), "f"(a), "f"(b), "f"(c), "f"(d) : "memory");
}
__device__ __forceinline__ void draw(int& ticket, unsigned* ctr, bool pred) {
    asm volatile("{\n.reg .pred p;\nsetp.ne.u32 p, %2, 0;\n@p atom.relaxed.gpu.global.inc.u32 %0, [%1], 0x7fffffff;\n}"
                 : "+r"(ticket) : "l"(ctr), "r"((uint32_t)pred) : "memory");
}
__device__ __forceinline__ void red_release(unsigned* p) {
    asm volatile("red.release.gpu.global.add.u32 [%0], 1;" :: "l"(p) : "memory");
}
__device__ __forceinline__ uint32_t ld_relaxed_u32(const void* p) {
    uint32_t v;
    asm volatile("ld.relaxed.gpu.global.u32 %0, [%1];" : "=r"(v) : "l"(p) : "memory");
    return v;
}
__device__ __forceinline__ float rcp_approx(float v) {
    float r;
    asm("rcp.approx.ftz.f32 %0, %1;" : "=f"(r) : "f"(v));
    return r;
}
__device__ __forceinline__ float sigmoid_approx(float v) {
    float e;
    asm("ex2.approx.ftz.f32 %0, %1;" : "=f"(e) : "f"(v * -1.4426950408889634f));
    return rcp_approx(1.0f + e);
}
__device__ __forceinline__ float sqrt_approx(float v) {
    float r;
    asm("sqrt.approx.ftz.f32 %0, %1;" : "=f"(r) : "f"(v));
    return r;
}
__device__ __forceinline__ uint2 ld_relaxed_v2(const void* p) {
    uint2 v;
    asm volatile("ld.relaxed.gpu.global.v2.u32 {%0,%1}, [%2];" : "=r"(v.x), "=r"(v.y) : "l"(p) : "memory");
    return v;
}
__device__ __forceinline__ void wait_count(const unsigned* p, unsigned target) {
#pragma unroll 1
    for (int it = 0; it < SPIN_MAX; it++) {
        if (ld_acquire(p) >= target) break;
        __nanosleep(400);
    }
}
__device__ __forceinline__ float4* oacc_at(int side, int row, int grp) {
    return row >= SROW0 ? sided<float4>(side, X_O + (row - SROW0) * 1024 + grp * 16) : &g_st.oacc[row][grp];
}
__device__ __forceinline__ float2* lsum_at(int side, int row) {
    return row >= SROW0 ? sided<float2>(side, X_L + (row - SROW0) * 128) : g_st.lsum[row];
}
__device__ __forceinline__ uint32_t* score_at(int side, int u, int lane) {
    return u >= NUNITS - NSS ? sided<uint32_t>(side, X_S + (u - (NUNITS - NSS)) * 128 + lane * 4) : &g_st.score[u - (NUNITS - NPOOL)][lane];
}
__device__ __forceinline__ void wait_row(int side, int bh, float n) {
    const float2* l = lsum_at(side, bh);
#pragma unroll 1
    for (int it = 0; it < SPIN_MAX; it++) {
        const float c = ld_relaxed_f2(l).y;
        if (c >= n) break;
        if (c == 0.f) __nanosleep(600);
    }
}
__device__ __forceinline__ void wait_row_o(int side, int bh, float n) {
    wait_row(side, bh, n);
    if (bh >= RED0) return;
#pragma unroll 1
    for (int it = 0; it < SPIN_MAX; it++) {
        if (__uint_as_float(ld_relaxed_u32(&g_st.oacc[bh][0].w)) == UPB) break;
        __nanosleep(300);
    }
}
__device__ __forceinline__ void spin_ns(int ns) {
    const long long t0 = clock64();
    while (clock64() - t0 < (long long)ns * 2) {}
}
__device__ __forceinline__ uint32_t pack_bf16(float lo, float hi) {
    uint32_t r;
    asm("cvt.rn.bf16x2.f32 %0, %1, %2;" : "=r"(r) : "f"(hi), "f"(lo));
    return r;
}
__device__ __forceinline__ float bf16r(float v) { return __uint_as_float(pack_bf16(0.f, v)); }
__device__ __forceinline__ uint32_t pack_neg(float lo, float hi) {
    const uint32_t w = pack_bf16(-lo, -hi);
    return w ? w : 0x80008000u;
}
__device__ __forceinline__ float lo_f(uint32_t v) { return __uint_as_float(v << 16); }
__device__ __forceinline__ float hi_f(uint32_t v) { return __uint_as_float(v & 0xffff0000u); }
__device__ __forceinline__ float warp_sum(float v) {
#pragma unroll
    for (int o = 16; o; o >>= 1) v += __shfl_xor_sync(0xffffffffu, v, o);
    return v;
}
__device__ __forceinline__ void layernorm20(float (&v)[20]) {
    float s = 0.f;
#pragma unroll
    for (int i = 0; i < 20; i++) s += v[i];
    const float mean = warp_sum(s) * (1.0f / DM);
    float q = 0.f;
#pragma unroll
    for (int i = 0; i < 20; i++) { const float d = v[i] - mean; q += d * d; }
    const float var = bf16r(warp_sum(q) * (1.0f / DM));
    const float m = bf16r(mean);
    const float rden = 1.0f / bf16r(sqrtf(bf16r(var + 1e-5f)));
#pragma unroll
    for (int i = 0; i < 20; i++) v[i] = bf16r(bf16r(v[i] - m) * rden);
}

__device__ __forceinline__ float sel4(int j, float a, float b, float c, float d) {
    float lo, hi, r;
    asm("{\n.reg .pred p;\nsetp.ne.s32 p, %3, 0;\nselp.f32 %0, %2, %1, p;\n}" : "=f"(lo) : "f"(a), "f"(b), "r"(j & 1));
    asm("{\n.reg .pred p;\nsetp.ne.s32 p, %3, 0;\nselp.f32 %0, %2, %1, p;\n}" : "=f"(hi) : "f"(c), "f"(d), "r"(j & 1));
    asm("{\n.reg .pred p;\nsetp.ne.s32 p, %3, 0;\nselp.f32 %0, %2, %1, p;\n}" : "=f"(r) : "f"(lo), "f"(hi), "r"(j & 2));
    return r;
}
template <typename T> __device__ __forceinline__ void pin(T*& p) { asm volatile("" : "+l"(p)); }
__device__ __forceinline__ void pin(uint32_t& v) { asm volatile("" : "+r"(v)); }
__device__ __forceinline__ void pin(float& v) { asm volatile("" : "+f"(v)); }
__device__ __forceinline__ uint32_t after(uint32_t n, float v) {
    asm volatile("{\n.reg .pred p;\nsetp.eq.u32 p, %1, 0x7fc1a5a5;\n@p add.u32 %0, %0, 32;\n}" : "+r"(n) : "r"(__float_as_uint(v)));
    return n;
}
__device__ __forceinline__ float2 lds64f(uint32_t addr) {
    float2 v;
    asm volatile("ld.shared.v2.f32 {%0,%1}, [%2];" : "=f"(v.x), "=f"(v.y) : "r"(addr) : "memory");
    return v;
}
__device__ __forceinline__ float4 lds128f(uint32_t addr) {
    float4 v;
    asm volatile("ld.shared.v4.f32 {%0,%1,%2,%3}, [%4];" : "=f"(v.x), "=f"(v.y), "=f"(v.z), "=f"(v.w) : "r"(addr) : "memory");
    return v;
}
__device__ __forceinline__ void sts64f(uint32_t addr, float a, float b, bool pred) {
    asm volatile("{\n.reg .pred p;\nsetp.ne.u32 p, %3, 0;\n@p st.shared.v2.f32 [%0], {%1,%2};\n}" :: "r"(addr), "f"(a), "f"(b), "r"((uint32_t)pred) : "memory");
}
__device__ __forceinline__ void sts128f(uint32_t addr, float a, float b, float c, float d, bool pred) {
    asm volatile("{\n.reg .pred p;\nsetp.ne.u32 p, %5, 0;\n@p st.shared.v4.f32 [%0], {%1,%2,%3,%4};\n}"
                 :: "r"(addr), "f"(a), "f"(b), "f"(c), "f"(d), "r"((uint32_t)pred) : "memory");
}
__device__ __forceinline__ void lds128_if(uint4& v, uint32_t addr, bool pred) {
    asm volatile("{\n.reg .pred p;\nsetp.ne.u32 p, %5, 0;\n@p ld.shared.v4.u32 {%0,%1,%2,%3}, [%4];\n}"
                 : "+r"(v.x), "+r"(v.y), "+r"(v.z), "+r"(v.w) : "r"(addr), "r"((uint32_t)pred) : "memory");
}
__device__ __forceinline__ void sts32f(uint32_t addr, float v) { asm volatile("st.shared.f32 [%0], %1;" :: "r"(addr), "f"(v) : "memory"); }
template <int ID> __device__ __forceinline__ void fin_arrive() { asm volatile("bar.arrive %0, 288;" :: "n"(ID) : "memory"); }
template <int ID> __device__ __forceinline__ void fin_sync() { asm volatile("bar.sync %0, 288;" :: "n"(ID) : "memory"); }
template <int ID> __device__ __forceinline__ void fin_sync(uint32_t n) { asm volatile("bar.sync %0, %1;" :: "n"(ID), "r"(n) : "memory"); }
__device__ __forceinline__ float2 sum8(uint32_t addr) {
    float2 t[8];
#pragma unroll
    for (int w = 0; w < 8; w++) t[w] = lds64f(addr + w * 128);
    return make_float2(((t[0].x + t[1].x) + (t[2].x + t[3].x)) + ((t[4].x + t[5].x) + (t[6].x + t[7].x)),
                       ((t[0].y + t[1].y) + (t[2].y + t[3].y)) + ((t[4].y + t[5].y) + (t[6].y + t[7].y)));
}
__device__ __forceinline__ float4 sum4x4(uint32_t addr) {
    float4 t[4];
#pragma unroll
    for (int w = 0; w < 4; w++) t[w] = lds128f(addr + w * 256);
    return make_float4((t[0].x + t[1].x) + (t[2].x + t[3].x), (t[0].y + t[1].y) + (t[2].y + t[3].y),
                       (t[0].z + t[1].z) + (t[2].z + t[3].z), (t[0].w + t[1].w) + (t[2].w + t[3].w));
}
template <int NJ>
__device__ __forceinline__ void load_o(uint32_t (&ob)[3 * NJ][2], int bh, int J0, int j) {
    float4 v[NJ][4];
    float2 l;
#pragma unroll 1
    for (int it = 0; it < SPIN_MAX; it++) {
#pragma unroll
        for (int J = 0; J < NJ; J++) {
#pragma unroll
            for (int e = 0; e < 4; e++) v[J][e] = ld_relaxed_f4(&g_st.oacc[bh][(J0 + J) * 16 + e * 4 + j]);
        }
        l = ld_relaxed_f2(g_st.lsum[bh]);
        bool ok = l.y == UPB;
#pragma unroll
        for (int J = 0; J < NJ; J++) {
#pragma unroll
            for (int e = 0; e < 4; e++) ok &= v[J][e].w == UPB;
        }
        if (__all_sync(0xffffffffu, ok)) break;
    }
    const float rl = __fdividef(1.0f, l.x);
#pragma unroll
    for (int J = 0; J < NJ; J++) {
        ob[3 * J][0] = pack_bf16(v[J][0].x * rl, v[J][1].x * rl);     ob[3 * J][1] = pack_bf16(v[J][2].x * rl, v[J][3].x * rl);
        ob[3 * J + 1][0] = pack_bf16(v[J][0].y * rl, v[J][1].y * rl); ob[3 * J + 1][1] = pack_bf16(v[J][2].y * rl, v[J][3].y * rl);
        ob[3 * J + 2][0] = pack_bf16(v[J][0].z * rl, v[J][1].z * rl); ob[3 * J + 2][1] = pack_bf16(v[J][2].z * rl, v[J][3].z * rl);
    }
}
__device__ __forceinline__ void aux_sync() { asm volatile("bar.sync 1, 256;" ::: "memory"); }

__global__ void __launch_bounds__(NTHREADS, 1)
fused_decode_kernel(const __grid_constant__ Params p) {
    extern __shared__ __align__(1024) unsigned char smem[];
    const uint32_t sb = s2u(smem);
    const int tid = threadIdx.x, warp = __shfl_sync(0xffffffffu, tid >> 5, 0), lane = tid & 31;
    const int cta = blockIdx.x;
    constexpr int grid = NCTAS;
    const int g = lane >> 2, j = lane & 3;
    const bool is_l = cta >= NE_CTAS, is_f = cta < 96 && !(cta & 1), is_g = cta < 80 && (cta & 1);
    const int fidx = cta >> 1;

    TS(0);
    if (warp == 4 && cta < NQ_CTAS) {
        asm volatile("{\n.reg .pred p;\nelect.sync _|p, 0xffffffff;\n"
                     "@p mbarrier.init.shared::cta.b64 [%0], 1;\n"
                     "@p fence.mbarrier_init.release.cluster;\n"
                     "@p mbarrier.arrive.expect_tx.shared::cta.b64 _, [%0], 61440;\n}" :: "r"(sb + BAR_WQ) : "memory");
#pragma unroll
        for (int i = 0; i < 4; i++) request_box(sb + SM_WQ + i * 15360, &p.wq, cta * 48, i * 160, sb + BAR_WQ, EVICT_NORMAL);
    }
    if (tid == 160) {
#pragma unroll
        for (int w = 0; w < NWORK; w++) mbar_init(sb + BAR_KV + w * 8, 1);
        mbar_init(sb + BAR_W, 1);
#pragma unroll
        for (int w = 0; w < 8; w++) mbar_init(sb + BAR_G + w * 8, 1);
        asm volatile("fence.mbarrier_init.release.cluster;" ::: "memory");
    }
    __syncthreads();
    if (warp == NAUX + NWORK + 1) {
        uint32_t t = now_clk() + 2 * WO_AT_NS;
        if (lane == 0) mbar_expect_tx(sb + BAR_W, cta < NE_CTAS ? 61440 : 49152);
        const int col = cta < NE_CTAS ? (cta & 3) * 160 : (cta - NE_CTAS) * 32, row = cta < NE_CTAS ? (cta >> 2) * DH : 28 * DH;
#pragma unroll 1
        for (int r = 0; r < DH; r += WO_ROWS) {
            wait_clk(t);
#pragma unroll 1
            for (int i = 0; i < (cta < NE_CTAS ? 5 : 4); i++)
                request_box(sb + SM_A + i * 12288 + r * 64, &p.wo, cta < NE_CTAS ? col + i * 32 : col, (cta < NE_CTAS ? row : row + i * DH) + r, sb + BAR_W, EVICT_FIRST);
            t += 2 * WO_GAP_NS;
        }
        if (!is_f && !is_g) return;
        if (lane < 8) mbar_expect_tx(sb + BAR_G + lane * 8, is_f ? 10240 : 6144);
        asm volatile("bar.sync 9, 288;" ::: "memory");
        asm volatile("fence.proxy.async.shared::cta;" ::: "memory");
#pragma unroll 1
        for (int it = 0; it < SPIN_MAX; it++) {
            t = ld_relaxed_u32(g_st.tstart);
            if (__all_sync(0xffffffffu, t != 0)) break;
            __nanosleep(400);
        }
#pragma unroll 1
        for (int it = 0; it < SPIN_MAX; it++) if (__all_sync(0xffffffffu, t - now_ns() > 2 * TRIG_NS)) break;
        TSW(11);
        t = now_clk() + (is_f ? 0 : DOFF);
#pragma unroll 1
        for (int i = 0; i < 8; i++, t += is_f ? GCLK : DCLK) {
            wait_clk(t);
            if (is_f) {
                request_box(sb + SM_G + i * 5120, &p.wg, fidx * 32, i * 80, sb + BAR_G + i * 8, EVICT_NORMAL);
                request_box(sb + SM_G + 40960 + i * 5120, &p.wu, fidx * 32, i * 80, sb + BAR_G + i * 8, EVICT_NORMAL);
            } else {
                request_box(sb + SM_G + i * 6144, &p.wd, fidx * 16, i * 192, sb + BAR_G + i * 8, EVICT_NORMAL);
            }
        }
        return;
    }
    if (warp == NAUX + NWORK) {
        if (cta < NQ_CTAS) {
#pragma unroll
            for (int i = lane; i < STATE_V4; i += 32)
                if (cta * STATE_V4 + i < (int)(sizeof(State) / 16)) reinterpret_cast<uint4*>(&g_st)[cta * STATE_V4 + i] = make_uint4(0u, 0u, 0u, 0u);
            if (cta * 512 < X_END) {
                uint4* z = sided<uint4>(0, cta * 512 + lane * 16);
                *z = make_uint4(0u, 0u, 0u, 0u);
                *other_side(z) = make_uint4(0u, 0u, 0u, 0u);
            }
            __syncwarp();
            if (lane == 0) red_release(g_cnt_z);
        }
        if (lane == 0) { TS2(2); wait_count(g_cnt_z, NQ_CTAS); TS2(29); }
        __syncwarp();
        asm volatile("bar.arrive 2, %0;" :: "n"((NWORK + 1) * 32) : "memory");
        uint32_t rtt[2] = {0xffffffffu, 0xffffffffu};
        if (lane == 0) {
#pragma unroll 1
            for (int r = 0; r < 2 * NPROBE; r++) {
                int v = 0;
                uint32_t t1 = 0;
                unsigned* ctr = sided<unsigned>(r & 1, X_P + ((cta * 32 + (r >> 1) * 768) & 4095));
                pin(ctr);
                const uint32_t t0 = now_clk();
                draw(v, ctr, true);
                asm volatile("{\n.reg .pred q;\nsetp.ge.s32 q, %1, 0;\n@q mov.u32 %0, %%clock;\n}" : "+r"(t1) : "r"(v) : "memory");
                if (r & 1) rtt[1] = min(rtt[1], t1 - t0); else rtt[0] = min(rtt[0], t1 - t0);
            }
            sts32f(sb + SM_SIDE, __int_as_float(rtt[1] < rtt[0]));
        }
        const int side = __shfl_sync(0xffffffffu, rtt[1] < rtt[0], 0);
        fin_arrive<3>();
        int job = cta;
        auto sum_rows = [&](int row_end) {
#pragma unroll 1
            for (; job < 8 * min(row_end, RED0); job += NCTAS) {
                const int row = job >> 3, grp = (job & 7) * 8 + (lane & 7);
                if (lane == 0) wait_row(side, row, UPB);
                __syncwarp();
                const float4* src = &g_ring[row % RING][lane >> 3][grp];
                float sx = 0.f, sy = 0.f, sz = 0.f;
#pragma unroll 1
                for (int i = 0; i < 2; i++, src += 64 * 64) {
                    float4 v[16];
#pragma unroll 1
                    for (int it = 0; it < SPIN_MAX; it++) {
                        bool ok = true;
#pragma unroll
                        for (int k = 0; k < 16; k++) v[k] = ld_relaxed_b128(src + k * 4 * 64);
#pragma unroll
                        for (int k = 0; k < 16; k++) ok &= v[k].w == (float)(row + 1);
                        if (__all_sync(0xffffffffu, ok)) break;
                    }
#pragma unroll
                    for (int k = 0; k < 16; k++) { sx += v[k].x; sy += v[k].y; sz += v[k].z; }
                }
#pragma unroll
                for (int o = 8; o < 32; o <<= 1) {
                    sx += __shfl_xor_sync(0xffffffffu, sx, o); sy += __shfl_xor_sync(0xffffffffu, sy, o); sz += __shfl_xor_sync(0xffffffffu, sz, o);
                }
                if (lane < 8) st_relaxed_b128(&g_st.oacc[row][grp], sx, sy, sz, UPB);
            }
        };
        {
            uint32_t wr[10];
            float wsum = 0.f;
#pragma unroll
            for (int i = 0; i < 10; i++) {
                const int w = 4 * lane + 128 * (i >> 2) + (i & 3) - (i >= 8 ? 2 * lane : 0);
                wr[i] = *reinterpret_cast<const uint32_t*>(p.wr + (w >> 4) * 32 + (w & 3) * 8 + ((w >> 1) & 6));
                wsum += lo_f(wr[i]) + hi_f(wr[i]);
            }
            wsum = warp_sum(wsum);
            const int lb = lane >> 3, lc = lane & 7;
            uint32_t ypart = sb + SM_RED2 + (lb >> 1) * 160 + lc * 16 + (lb & 1) * 8;
            __nv_bfloat16* out = p.out + lb * DM + fidx * 16 + lc;
            float nmean_l = 0.f, rden_l = 0.f, sig_l = 0.f;
#pragma unroll 1
            for (int b = 0; b < NB; b++) {
                const uint32_t hx = X_H + b * (DM * 2), hrow = sb + SM_X + b * HPITCH;
                const uint4 *src0 = sided<uint4>(side, hx + 16 * lane), *src1 = sided<uint4>(side, hx + 512 + 16 * lane);
                const uint2* src2 = sided<uint2>(side, hx + 1024 + 8 * lane);
                sum_rows((b + 1) * NH);
                if (!is_l && !is_f && !is_g) continue;
                pin(src0); pin(src1); pin(src2); pin(ypart); pin(out);
                if (lane == 0) wait_row(side, b * NH + (is_l ? 28 : NH - 1), is_l ? 1 : FWAIT);
                __syncwarp();
                if (is_l) {
                    const int col = (cta - NE_CTAS) * 32 + 2 * (lane & 15);
                    uint32_t lpart = sb + SM_RED + (lane & 15) * 8;
                    const uint32_t xv = *reinterpret_cast<const uint32_t*>(p.x + b * DM + col);
                    uint32_t* hdst = sided<uint32_t>(lane >> 4, hx + 4 * ((col >> 5) * 16 + (col & 6) * 2 + ((col >> 3) & 3)));
                    float4 early;
#pragma unroll 1
                    for (int it = 0; it < SPIN_MAX; it++) {
                        early = ld_relaxed_f4(&g_st.attn[b][col]);
                        if (__all_sync(0xffffffffu, early.y == NE_CTAS / 4 && early.w == NE_CTAS / 4)) break;
                    }
                    if (lane == 0) TS2(23);
                    float x0 = lo_f(xv), x1 = hi_f(xv);
                    pin(hdst); pin(lpart); pin(x0); pin(x1);
                    fin_sync<4>();
                    CK(2, lds32(sb + SM_RED));
                    const float2 late = sum8(lpart);
                    st_relaxed(hdst, pack_neg(x0 + bf16r(early.x + late.x), x1 + bf16r(early.z + late.y)));
                    CK(3, 0);
                    if (lane == 0) TS2(15);
                    fin_sync<5>();
                    continue;
                }
                uint4 h0, h1;
                uint2 h2;
                float mm[5][4];
#pragma unroll 1
                for (int it = 0; it < SPIN_MAX; it++) {
                    h0 = ld_relaxed_v4(src0);
                    h1 = ld_relaxed_v4(src1);
                    h2 = ld_relaxed_v2(src2);
                    asm volatile("st.shared.v4.u32 [%0], {%1,%2,%3,%4};" :: "r"(hrow + lane * 16), "r"(h0.x), "r"(h0.y), "r"(h0.z), "r"(h0.w) : "memory");
                    asm volatile("st.shared.v4.u32 [%0], {%1,%2,%3,%4};" :: "r"(hrow + 512 + lane * 16), "r"(h1.x), "r"(h1.y), "r"(h1.z), "r"(h1.w) : "memory");
                    asm volatile("st.shared.v2.u32 [%0], {%1,%2};" :: "r"(hrow + 1024 + lane * 8), "r"(h2.x), "r"(h2.y) : "memory");
                    const uint32_t w[10] = {h0.x, h0.y, h0.z, h0.w, h1.x, h1.y, h1.z, h1.w, h2.x, h2.y};
#pragma unroll
                    for (int i = 0; i < 5; i++) {
                        const uint32_t a[4] = {w[2 * i], 0x3f803f80u, w[2 * i + 1], 0x3f803f80u};
                        mm[i][0] = mm[i][1] = mm[i][2] = mm[i][3] = 0.f;
                        mma16816(mm[i], a, w[2 * i], w[2 * i + 1]);
                    }
                    const uint32_t lo = min(min(min(h0.x, h0.y), min(h0.z, h0.w)), min(min(min(h1.x, h1.y), min(h1.z, h1.w)), min(h2.x, h2.y)));
                    if (GDLY && !is_f) sts32f(sb + SM_MOM, __uint_as_float(now_clk()));
                    const bool ok = __all_sync(0xffffffffu, lo != 0 || it == SPIN_MAX - 1);
                    asm volatile("{\n.reg .pred p;\nsetp.ne.u32 p, %0, 0;\n@p bar.arrive 7, 288;\n}" :: "r"((uint32_t)ok) : "memory");
                    if (ok) break;
                    if (!is_f) __nanosleep(HNAP);
                }
                CK(4, h0.x);
                if (lane == 0 && is_f) TS2(12);
                const uint32_t hw[10] = {h0.x, h0.y, h0.z, h0.w, h1.x, h1.y, h1.z, h1.w, h2.x, h2.y};
                float m1 = ((mm[0][2] + mm[1][2]) + (mm[2][2] + mm[3][2])) + ((mm[0][3] + mm[1][3]) + (mm[2][3] + mm[3][3])) + (mm[4][2] + mm[4][3]);
                float m2 = (g & 1) ? ((mm[0][1] + mm[1][1]) + (mm[2][1] + mm[3][1])) + mm[4][1] : ((mm[0][0] + mm[1][0]) + (mm[2][0] + mm[3][0])) + mm[4][0];
                m2 += __shfl_xor_sync(0xffffffffu, m2, 4);
                m1 = (m1 + __shfl_xor_sync(0xffffffffu, m1, 1)) + (__shfl_xor_sync(0xffffffffu, m1, 2) + __shfl_xor_sync(0xffffffffu, m1, 3));
                m2 = (__shfl_sync(0xffffffffu, m2, 0) + __shfl_sync(0xffffffffu, m2, 9)) + (__shfl_sync(0xffffffffu, m2, 18) + __shfl_sync(0xffffffffu, m2, 27));
                m1 *= 1.0f / DM;
                const float nmean = bf16r(m1);
                const float var = bf16r(fmaxf(fmaf(-m1, m1, m2 * (1.0f / DM)), 0.f));
                const float den = bf16r(sqrt_approx(bf16r(var + 1e-5f)));
                if (is_f) {
                    sts64f(sb + SM_MOM + b * 8, nmean, den, lane == 0);
                    CK(5, 0);
                    fin_arrive<4>();
                } else {
                    const float rden = rcp_approx(den);
                    if (lb == b) { nmean_l = nmean; rden_l = rden; }
                    __syncwarp();
                    const float2 hw2 = lds64f(sb + SM_X + lb * HPITCH + ((fidx >> 1) * 16 + (lc & 6) * 2 + (fidx & 1) * 2) * 4);
                    const float nh0 = (lc & 1) ? hi_f(__float_as_uint(hw2.x)) : lo_f(__float_as_uint(hw2.x));
                    const float nh1 = (lc & 1) ? hi_f(__float_as_uint(hw2.y)) : lo_f(__float_as_uint(hw2.y));
                    float rr = 0.f;
#pragma unroll
                    for (int i = 0; i < 10; i++) rr = fmaf(lo_f(hw[i]), lo_f(wr[i]), fmaf(hi_f(hw[i]), hi_f(wr[i]), rr));
                    const float sig = bf16r(sigmoid_approx(bf16r((nmean * wsum - warp_sum(rr)) * rden)));
                    if (lb == b) sig_l = sig;
                    const float ln0 = bf16r(bf16r(nmean_l - nh0) * rden_l), ln1 = bf16r(bf16r(nmean_l - nh1) * rden_l);
                    fin_sync<6>(after(after(after(288, sig_l), ln0), ln1));
                    CK(10, lds32(ypart));
                    float2 t[16];
#pragma unroll
                    for (int i = 0; i < 16; i++) t[i] = lds64f(ypart + i * YPITCH);
#pragma unroll
                    for (int o = 1; o < 16; o <<= 1) {
#pragma unroll
                        for (int i = 0; i < 16; i += 2 * o) { t[i].x += t[i + o].x; t[i].y += t[i + o].y; }
                    }
                    const uint32_t ov = pack_bf16(bf16r(ln0 + bf16r(bf16r(-t[0].x) * sig_l)) - nh0, bf16r(ln1 + bf16r(bf16r(-t[0].y) * sig_l)) - nh1);
                    asm volatile("{\n.reg .pred p;\n.reg .b16 lo, hi;\nsetp.eq.u32 p, %2, 3;\nmov.b32 {lo, hi}, %1;\n"
                                 "@p st.global.u16 [%0], lo;\n@p st.global.u16 [%0 + 16], hi;\n}" :: "l"(out), "r"(ov), "r"(b) : "memory");
                    CK(11, 0);
                    if (lane == 0) TS2(13);
                }
                if (b < NB - 1) fin_sync<5>();
            }
            if (cta == 0 && lane == 0) { g_work[0] = 0; g_cnt_z[0] = 0; }
        }
        return;
    }
    if (warp >= NAUX) {
        const int wk = warp - NAUX;
        const uint32_t bar = sb + BAR_KV + wk * 8;
        const uint32_t buf = sb + SM_KV + wk * TILE_BYTES;
        uint64_t pol;
        asm volatile("createpolicy.fractional.L2::evict_first.b64 %0, 1.0;" : "=l"(pol));
        const int nstatic = NWORK * grid;
        constexpr int POOL0 = NUNITS - NPOOL;
        int uk = wk * grid + cta;
        if (lane == 0) {
            spin_ns(K0_DELAY_NS + wk * K0_STEP_NS);
            mbar_expect_tx(bar, TILE_BYTES);
            tma_tile(buf, &p.k, uk * TILE_ROWS, bar, pol);
        }
        __syncwarp();
        uint32_t koff[3], voff[3];
        {
            const int r = lane & 7, hf = (lane >> 3) & 1;
            const int kkey = hf ? 8 + (r ^ 1) : r;
            const int vh = lane >> 4;
            const int vkey = ((r & 1) ? 8 : 0) + (vh ? (r ^ 1) : r);
#pragma unroll
            for (int b = 0; b < 3; b++) {
                const int rk = 3 * kkey + b, rv = 3 * vkey + b;
                koff[b] = buf + rk * 128 + (((lane >> 4) ^ (rk & 7)) << 4);
                voff[b] = buf + rv * 128 + ((hf ^ (rv & 7)) << 4);
            }
        }
        uint32_t phase = 0;
        uint4 qf[6];
        auto load_q = [&](int u) {
            const uint32_t* q = &g_early[u / UPB].q[j * 4];
#pragma unroll
            for (int i = 0; i < 6; i++) qf[i] = ld_relaxed_v4(q + i * 16);
        };
        load_q(uk);
        int uq[LAG];
        uint32_t sq[LAG];
#pragma unroll
        for (int i = 0; i < LAG; i++) { uq[i] = -1; sq[i] = 0; }
        uint4 mv = make_uint4(0u, 0u, 0u, 0u);
        float freed = UPB;
        while (true) {
            const int uv = uq[0];
            uint32_t sv = sq[0];
#pragma unroll
            for (int i = 0; i + 1 < LAG; i++) { uq[i] = uq[i + 1]; sq[i] = sq[i + 1]; }
            uq[LAG - 1] = uk;
            if (uk < NUNITS) {
                PH(7);
#pragma unroll 1
                for (int it = 0; it < SPIN_MAX; it++) {
                    uint32_t lo = 0xffffffffu;
#pragma unroll
                    for (int i = 0; i < 6; i++) lo = min(min(lo, min(qf[i].x, qf[i].y)), min(qf[i].z, qf[i].w));
                    if (__all_sync(0xffffffffu, lo != 0)) break;
                    __nanosleep(QNAP);
                    load_q(uk);
                }
                mbar_wait(bar, phase); phase ^= 1;
                PH(0); ARR();
                TSI(0, 16); TSI(1, 18);
                float acc[2][4][4] = {};
#pragma unroll
                for (int ks = 0; ks < 12; ks++) {
                    const uint4 qq = qf[ks >> 1];
                    const uint32_t b0 = (ks & 1) ? qq.z : qq.x, b1 = (ks & 1) ? qq.w : qq.y;
#pragma unroll
                    for (int mt = 0; mt < 4; mt++) {
                        uint32_t a[4];
                        ldsm4(a, (koff[ks >> 2] ^ ((ks & 3) << 5)) + mt * 6144);
                        mma16816(acc[ks & 1][mt], a, b0, b1);
                    }
                }
                PH(1);
                TSI(0, 17); TSI(1, 19);
                if (uv < NUNITS) request_tile(buf, uv >= 0 ? &p.v : &p.k, uv >= 0 ? uv : uk + nstatic, bar, pol);
                const float sa = sel4(j, acc[0][0][0], acc[0][1][0], acc[0][2][0], acc[0][3][0]) + sel4(j, acc[1][0][0], acc[1][1][0], acc[1][2][0], acc[1][3][0]);
                const float sc = sel4(j, acc[0][0][2], acc[0][1][2], acc[0][2][2], acc[0][3][2]) + sel4(j, acc[1][0][2], acc[1][1][2], acc[1][2][2], acc[1][3][2]);
                const uint32_t raw = pack_bf16(sa, sc);
                const float scale = -0.07216878364870322f;
                const uint32_t sk = pack_bf16(lo_f(raw) * scale, hi_f(raw) * scale);
                sq[LAG - 1] = sk;
                if (uk >= POOL0) {
                    uint32_t* sdst = score_at(0, uk, lane);
                    st_relaxed(sdst, sk ? sk : 0x80008000u);
                    if (uk >= NUNITS - NSS) st_relaxed(other_side(sdst), sk ? sk : 0x80008000u);
                }
                int a = (int)(sk << 16), b = (int)(sk & 0xffff0000u);
                a ^= (a >> 31) & 0x7fff0000; b ^= (b >> 31) & 0x7fff0000;
                const int mx = __reduce_max_sync(0xffffffffu, max(a, b));
                if (lane == 0) st_relaxed(&g_early[uk / UPB].umax[uk % UPB], (uint32_t)mx | 1u);
            }
            if (uv < 0) {
                uk += nstatic;
                load_q(uk);
                continue;
            }
            if (uv >= NUNITS) break;
            const int bh = uv / UPB;
#pragma unroll 1
            for (int it = 0; it < SPIN_MAX; it++) {
                if (__all_sync(0xffffffffu, (mv.x & mv.y & mv.z & mv.w & 1u) && (uv < POOL0 || sv != 0) && freed == UPB)) break;
                mv = ld_relaxed_v4(&g_early[bh].umax[lane * 4]);
                if (bh >= RING && bh < RED0) freed = __uint_as_float(ld_relaxed_u32(&g_st.oacc[bh - RING][(lane & 7) * 8].w));
                if (uv >= POOL0) sv = ld_relaxed_u32(score_at(lds32(sb + SM_SIDE), uv, lane));
            }
            PH(2);
            int un = NUNITS, vn = 0;
            draw(un, g_work, uk < NUNITS && lane == 0);
            int mx = __reduce_max_sync(0xffffffffu, max(max((int)mv.x, (int)mv.y), max((int)mv.z, (int)mv.w))) & 0xffff0000;
            mx ^= (mx >> 31) & 0x7fff0000;
            const float m = __int_as_float(mx);
            const float l2e = 1.4426950408889634f;
            const uint32_t pp = pack_bf16(exp2f((lo_f(sv) - m) * l2e), exp2f((hi_f(sv) - m) * l2e));
            uint32_t pb[8];
#pragma unroll
            for (int t = 0; t < 4; t++) {
                pb[2 * t] = __shfl_sync(0xffffffffu, pp, 8 * j + t);
                pb[2 * t + 1] = __shfl_sync(0xffffffffu, pp, 8 * j + 4 + t);
            }
            float lacc[4] = {};
            const uint32_t ones[4] = {0x3f803f80u, 0x3f803f80u, 0x3f803f80u, 0x3f803f80u};
#pragma unroll
            for (int t = 0; t < 4; t++) mma16816(lacc, ones, pb[2 * t], pb[2 * t + 1]);
            if (uv < nstatic) {
                asm volatile("bar.sync 2, %0;" :: "n"((NWORK + 1) * 32) : "memory");
                TSW(3);
            }
            const int grp = 16 * j + 4 * (g & 1) + (g >> 1);
            const int acc_row = bh >= NBH - 4 && uv % OREP ? bh + 4 * (uv % OREP) : bh;
            float4* dst = bh < RED0 ? &g_ring[bh % RING][uv % UPB][grp] : oacc_at(FARFIRST ? lds32(sb + SM_SIDE) ^ 1 : 0, acc_row, grp);
            float4* dst2 = other_side(dst);
            float2* ldst = lsum_at(lane & 1, acc_row);
            if (bh >= SROW0 && lane < 2) red_f2(&ldst->x, lacc[0], 1.f);
            float tag = bh < RED0 ? (float)(bh + 1) : 1.f;
            un = __shfl_sync(0xffffffffu, un, 0) + (LAG + 1) * nstatic;
            uint32_t pooled = uq[0] >= POOL0 && lane == 0;
            pin(dst); pin(dst2); pin(ldst); pin(tag); pin(voff[0]); pin(voff[1]); pin(voff[2]); pin(pooled);
            PH(3);
            mbar_wait(bar, phase); phase ^= 1;
            PH(4); ARR();
            draw(vn, g_st.pool, pooled);
            float acc[12][4] = {};
#pragma unroll
            for (int t = 0; t < 4; t++) {
#pragma unroll
                for (int mt = 0; mt < 12; mt++) {
                    uint32_t a[4];
                    ldsm4t(a, (voff[mt >> 2] ^ ((mt & 3) << 5)) + t * 6144);
                    mma16816(acc[mt], a, pb[2 * t], pb[2 * t + 1]);
                }
            }
            PH(5);
            if (lane == 0) PROG(un);
            if (un < NUNITS) request_tile(buf, &p.k, un, bar, pol);
            float o[6];
#pragma unroll
            for (int e = 0; e < 6; e++) {
                const int q = e % 3, c = (e / 3) * 2;
                o[e] = sel4(j, acc[q][c], acc[3 + q][c], acc[6 + q][c], acc[9 + q][c]);
            }
            if (bh >= SROW0) {
                red_f4(&dst->x, o[0], o[1], o[2], tag);
                red_f4(&dst[SPREAD ? 16 : 8].x, o[3], o[4], o[5], tag);
                red_f4(&dst2->x, o[0], o[1], o[2], tag);
                red_f4(&dst2[SPREAD ? 16 : 8].x, o[3], o[4], o[5], tag);
            } else {
                if (bh >= RED0) {
                    red_f4(&dst->x, o[0], o[1], o[2], tag);
                    red_f4(&dst[8].x, o[3], o[4], o[5], tag);
                } else {
                    st_relaxed_b128(dst, o[0], o[1], o[2], tag);
                    st_relaxed_b128(dst + 8, o[3], o[4], o[5], tag);
                }
                if (lane == 0) red_f2(&ldst->x, lacc[0], 1.f);
            }
            if (uq[0] >= POOL0) {
                vn = __shfl_sync(0xffffffffu, vn, 0);
                uq[0] = POOL0 + vn;
                if (vn == VTRIG && lane == 0) st_relaxed(g_st.tstart, (now_ns() + TRIG_NS) | 1u);
            }
            if (un < NUNITS) load_q(un);
            else if (uq[0] < NUNITS) request_tile(buf, &p.v, uq[0], bar, pol);
            PH(6);
            if (uq[0] >= NUNITS && un >= NUNITS) break;
            uk = un;
            if (uq[0] < NUNITS) {
                const int nb = uq[0] / UPB;
                mv = ld_relaxed_v4(&g_early[nb].umax[lane * 4]);
                freed = nb >= RING && nb < RED0 ? __uint_as_float(ld_relaxed_u32(&g_st.oacc[nb - RING][(lane & 7) * 8].w)) : UPB;
                if (uq[0] >= POOL0) sq[0] = ld_relaxed_u32(score_at(lds32(sb + SM_SIDE), uq[0], lane));
            }
        }
        return;
    }

    __nv_bfloat16* xs = reinterpret_cast<__nv_bfloat16*>(smem + SM_X);
    float* red = reinterpret_cast<float*>(smem + SM_RED);
    const int frow = (lane & 7) + ((lane >> 4) << 3), fcol = (lane >> 3) & 1;
    if (cta < NQ_CTAS) {
        uint2 xr[5];
        if (warp < NB) {
#pragma unroll
            for (int i = 0; i < 5; i++) xr[i] = *reinterpret_cast<const uint2*>(p.x + warp * DM + i * 128 + lane * 4);
        }
        TS(26);
        if (warp < NB) {
            float v[20];
#pragma unroll
            for (int i = 0; i < 5; i++) {
                v[4 * i] = lo_f(xr[i].x); v[4 * i + 1] = hi_f(xr[i].x); v[4 * i + 2] = lo_f(xr[i].y); v[4 * i + 3] = hi_f(xr[i].y);
            }
            layernorm20(v);
#pragma unroll
            for (int i = 0; i < 5; i++)
                *reinterpret_cast<uint2*>(xs + warp * XPITCH + i * 128 + lane * 4) =
                    make_uint2(pack_bf16(v[4 * i], v[4 * i + 1]), pack_bf16(v[4 * i + 2], v[4 * i + 3]));
        }
        TS(27);
        aux_sync();
        mbar_wait(sb + BAR_WQ, 0);
        TS(1);
        const uint32_t xfrag = sb + SM_X + ((g & 3) * XPITCH + 2 * j) * 2;
        float acc[3][4] = {};
#pragma unroll
        for (int s = 0; s < 5; s++) {
            const int ks = warp * 5 + s;
            const uint32_t b0 = lds32(xfrag + ks * 32), b1 = lds32(xfrag + ks * 32 + 16);
            const int row = ks * 16 + frow;
#pragma unroll
            for (int mt = 0; mt < 3; mt++) {
                uint32_t a[4];
                ldsm4t(a, sb + SM_WQ + (row * 6 + 2 * mt + fcol) * 16);
                mma16816(acc[mt], a, b0, b1);
            }
        }
        if (j < 2) {
#pragma unroll
            for (int mt = 0; mt < 3; mt++) {
                *reinterpret_cast<float2*>(red + (warp * 48 + mt * 16 + g) * 4 + 2 * j) = make_float2(acc[mt][0], acc[mt][1]);
                *reinterpret_cast<float2*>(red + (warp * 48 + mt * 16 + 8 + g) * 4 + 2 * j) = make_float2(acc[mt][2], acc[mt][3]);
            }
        }
        aux_sync();
        if (tid < 96) {
            const int b = tid & 3, cp = tid >> 2;
            float s0 = 0.f, s1 = 0.f;
#pragma unroll
            for (int w = 0; w < 8; w++) { s0 += red[(w * 48 + 2 * cp) * 4 + b]; s1 += red[(w * 48 + 2 * cp + 1) * 4 + b]; }
            const int h = cta >> 2, d = (cta & 3) * 48 + 2 * cp;
            const int ch = d >> 3, jj = (d & 7) >> 1;
            st_relaxed(&g_early[b * NH + h].q[(ch >> 2) * 16 + jj * 4 + (ch & 3)], pack_neg(s0, s1));
        }
        TS(28);
    }
    if (tid < 160) *reinterpret_cast<uint2*>(smem + SM_X + 4 * HPITCH + tid * 8) = make_uint2(0x3f803f80u, 0x3f803f80u);
    fin_sync<3>();
    const int side = lds32(sb + SM_SIDE);
    mbar_wait(sb + BAR_W, 0);
    TS(7);
    uint32_t part = sb + SM_RED + (warp * 32 + 8 * j + g) * 4;

#pragma unroll 1
    for (int b = 0; b < NB; b++) {
        if (b == NB - 1 && (is_f || is_g)) asm volatile("bar.arrive 9, 288;" ::: "memory");
        if (is_l) {
            uint32_t a[6][2][4];
#pragma unroll
            for (int s = 0; s < 6; s++) {
                const int row = (warp * 6 + s) * 16 + frow;
#pragma unroll
                for (int mt = 0; mt < 2; mt++) ldsm4t(a[s][mt], sb + SM_A + (row * 4 + ((2 * mt + fcol) ^ ((row >> 1) & 3))) * 16);
            }
            const int bh = b * NH + 28 + (warp >> 1);
            const float4* osrc[OREP];
            const float2* lsrc[OREP];
#pragma unroll
            for (int c = 0; c < OREP; c++) {
                const int row = b == NB - 1 ? bh + 4 * c : bh;
                osrc[c] = oacc_at(side, row, (warp & 1) * 32 + lane);
                lsrc[c] = lsum_at(side, row);
                pin(osrc[c]); pin(lsrc[c]);
            }
            if (lane == 0) wait_row_o(side, bh, 1);
            __syncwarp();
            float2 lv;
#pragma unroll 1
            for (int it = 0; it < SPIN_MAX; it++) {
                lv = ld_relaxed_f2(lsrc[0]);
#pragma unroll
                for (int c = 1; c < OREP; c++) {
                    const float2 lc = ld_relaxed_f2(lsrc[c]);
                    if (b == NB - 1) { lv.x += lc.x; lv.y += lc.y; }
                }
                if (__all_sync(0xffffffffu, lv.y == UPB)) break;
            }
            if (warp == 7) TSW(25);
            float rl = rcp_approx(lv.x);
            float4 ov;
            pin(part); pin(rl);
            if (OPRE && lane == 0) {
#pragma unroll 1
                for (int it = 0; it < SPIN_MAX; it++) {
                    if (__uint_as_float(ld_relaxed_u32(&osrc[0]->w)) >= UPB * OPRE / (16 * OREP)) break;
                    if (ONAP) __nanosleep(ONAP);
                }
            }
            __syncwarp();
#pragma unroll 1
            for (int it = 0;; it++) {
                float4 oc[OREP];
#pragma unroll
                for (int c = 0; c < OREP; c++) oc[c] = ld_relaxed_f4(osrc[c]);
                ov = oc[0];
                if (b == NB - 1) {
#pragma unroll
                    for (int c = 1; c < OREP; c++) { ov.x += oc[c].x; ov.y += oc[c].y; ov.z += oc[c].z; ov.w += oc[c].w; }
                }
                if (__all_sync(0xffffffffu, ov.w == UPB || it == SPIN_MAX)) break;
            }
            CK(0, __float_as_uint(ov.x));
            const float px = __shfl_xor_sync(0xffffffffu, ov.x, 4), py = __shfl_xor_sync(0xffffffffu, ov.y, 4),
                        pz = __shfl_xor_sync(0xffffffffu, ov.z, 4);
            const uint32_t w[3] = {pack_bf16(ov.x * rl, px * rl), pack_bf16(ov.y * rl, py * rl), pack_bf16(ov.z * rl, pz * rl)};
            float acc[2][2][4] = {};
#pragma unroll
            for (int s = 0; s < 6; s++) {
                const uint32_t b0 = __shfl_sync(0xffffffffu, w[s % 3], (s / 3) * 16 + j);
                const uint32_t b1 = __shfl_sync(0xffffffffu, w[s % 3], (s / 3) * 16 + 8 + j);
#pragma unroll
                for (int mt = 0; mt < 2; mt++) mma16816(acc[mt][s & 1], a[s][mt], b0, b1);
            }
            sts32f(part, sel4(j, acc[0][0][0] + acc[0][1][0], acc[0][0][2] + acc[0][1][2], acc[1][0][0] + acc[1][1][0], acc[1][0][2] + acc[1][1][2]));
            CK(1, 0);
            fin_arrive<4>();
            if (warp == 7) TSW(30);
            if (warp == 5) TSW(31);
            if (cta == NE_CTAS && lane < 28) reinterpret_cast<uint4*>(&g_early[bh])[(warp & 1) * 28 + lane] = make_uint4(0u, 0u, 0u, 0u);
            fin_sync<5>();
            continue;
        }
        {
            const int bh = b * NH + (cta >> 2);
            if (tid == 0) wait_row_o(side, bh, UPB);
            aux_sync();
            if (warp < 5) {
                uint32_t ob[12][2];
                load_o<4>(ob, bh, 0, j);
                float acc[2][2][4] = {};
#pragma unroll
                for (int ks = 0; ks < 12; ks++) {
                    const int row = ks * 16 + frow;
#pragma unroll
                    for (int mt = 0; mt < 2; mt++) {
                        uint32_t a[4];
                        ldsm4t(a, sb + SM_A + warp * 12288 + (row * 4 + ((2 * mt + fcol) ^ ((row >> 1) & 3))) * 16);
                        mma16816(acc[mt][ks & 1], a, ob[ks][0], ob[ks][1]);
                    }
                }
                red_f2(&g_st.attn[b][(cta & 3) * 160 + warp * 32 + 8 * j + g].x,
                       sel4(j, acc[0][0][0] + acc[0][1][0], acc[0][0][2] + acc[0][1][2], acc[1][0][0] + acc[1][1][0], acc[1][0][2] + acc[1][1][2]), 1.f);
                TS(8);
            } else if (warp > 5 && (cta & 3) == 0 && tid - 192 < 56) {
                reinterpret_cast<uint4*>(&g_early[bh])[tid - 192] = make_uint4(0u, 0u, 0u, 0u);
            }
        }
        if (is_f) {
            const int kq = warp >> 1, tp = warp & 1;
            uint32_t hfrag = sb + SM_X + min(g, 4) * HPITCH + (kq * 80 + 4 * j) * 4;
            uint4 hv[5] = {};
#pragma unroll
            for (int s = 0; s < 5; s++) lds128_if(hv[s], hfrag + s * 64, true);
            uint32_t ga[10][2][4];
#pragma unroll
            for (int s = 0; s < 10; s++) {
                if (s % 5 == 0 && b == NB - 1) mbar_wait(sb + BAR_G + (kq * 2 + s / 5) * 8, 0);
                const int row = (kq * 10 + s) * 16 + frow;
#pragma unroll
                for (int t = 0; t < 2; t++) ldsm4t(ga[s][t], sb + SM_G + fcol * 40960 + (row * 4 + ((2 * tp + t) ^ ((row >> 1) & 3))) * 16);
            }
            if (warp == NAUX - 1) TSW(9);
            uint32_t fpart = sb + SM_RED + 2 * j * FPITCH + warp * 128 + g * 16;
            uint32_t dsum = sb + SM_RED + (lane >> 3) * FPITCH + tp * 128 + (lane & 7) * 16, csum = sb + SM_RED + 4 * FPITCH + tp * 128 + (lane & 7) * 16;
            uint32_t mom = sb + SM_MOM + (lane >> 3) * 8;
            uint32_t* dst = sided<uint32_t>(side ^ 1, X_A + (2 * fidx + tp) * 128 + (lane ^ 2 * tp) * 4);
            pin(fpart); pin(hfrag); pin(dsum); pin(csum); pin(mom); pin(dst);
            fin_sync<7>();
#pragma unroll
            for (int s = 0; s < 5; s++) lds128_if(hv[s], hfrag + s * 64, g == b);
            float acc[2][2][4] = {};
#pragma unroll
            for (int s = 0; s < 5; s++) {
#pragma unroll
                for (int t = 0; t < 2; t++) mma16816(acc[t][0], ga[2 * s][t], hv[s].x, hv[s].y);
#pragma unroll
                for (int t = 0; t < 2; t++) mma16816(acc[t][1], ga[2 * s + 1][t], hv[s].z, hv[s].w);
            }
#pragma unroll
            for (int e = 0; e < 2; e++)
                sts128f(fpart + e * FPITCH, acc[0][0][e] + acc[0][1][e], acc[0][0][2 + e] + acc[0][1][2 + e],
                        acc[1][0][e] + acc[1][1][e], acc[1][0][2 + e] + acc[1][1][2 + e], 2 * j + e < 5);
            CK(5, 0);
            if (warp < 2) {
                fin_sync<4>();
                CK(6, lds32(dsum));
                float2 m = lds64f(mom);
                m.y = rcp_approx(m.y);
                const float4 d = sum4x4(dsum), cs = sum4x4(csum);
                const float g0 = bf16r(fmaf(m.x, cs.x, -d.x) * m.y), g1 = bf16r(fmaf(m.x, cs.z, -d.z) * m.y);
                const float u0 = bf16r(fmaf(m.x, cs.y, -d.y) * m.y), u1 = bf16r(fmaf(m.x, cs.w, -d.w) * m.y);
                const uint32_t av = pack_neg(bf16r(g0 * sigmoid_approx(g0)) * u0, bf16r(g1 * sigmoid_approx(g1)) * u1);
                asm volatile("{\n.reg .pred p;\nsetp.eq.u32 p, %3, 3;\n@p st.relaxed.gpu.global.u32 [%0], %2;\n@p st.relaxed.gpu.global.u32 [%1], %2;\n}"
                             :: "l"(dst), "l"(other_side(dst)), "r"(av), "r"(b) : "memory");
                CK(7, 0);
                TS(14);
            } else {
                fin_arrive<4>();
            }
        } else if (is_g) {
            if (b == NB - 1) {
                mbar_wait(sb + BAR_G + warp * 8, 0);
                if (warp == NAUX - 1) TSW(10);
            }
            uint32_t wb[3][2][2][4];
#pragma unroll
            for (int s = 0; s < 12; s++) {
                const int odd = (lane >> 2) & 1, c = ((lane & 2) * 2 + (s & 1) * 2 + (lane >> 4)) ^ (2 * odd);
                const int row = (warp * 12 + (s >> 1) * 2 + odd) * 16 + (lane & 1) * 8 + c;
                ldsm4t(wb[s >> 2][(s >> 1) & 1][s & 1], sb + SM_G + (row * 2 + (fcol ^ ((row >> 2) & 1))) * 16);
            }
            const uint4* asrc[3];
#pragma unroll
            for (int q = 0; q < 3; q++) {
                asrc[q] = sided<uint4>(side, X_A + (warp * 12 + 4 * q + 2 * (g >> 2) + (j >> 1)) * 128 + (g & 3) * 32 + (j & 1) * 16);
                pin(asrc[q]);
            }
            uint32_t ypart = sb + SM_RED2 + (warp * 2 + (j >> 1)) * YPITCH + (j & 1) * 160 + g * 16;
            pin(ypart);
            fin_sync<7>();
            if (GDLY) wait_clk(lds32(sb + SM_MOM) + GDLY);
            uint4 v[3] = {};
            uint32_t mq[3] = {};
#pragma unroll 1
            for (int it = b < NB - 1 ? SPIN_MAX : 0;; it++) {
                asm volatile("{\n.reg .pred p0, p1, p2;\nsetp.eq.u32 p0, %15, 0;\nsetp.eq.u32 p1, %16, 0;\nsetp.eq.u32 p2, %17, 0;\n"
                             "@p0 ld.relaxed.gpu.global.v4.u32 {%0,%1,%2,%3}, [%12];\n"
                             "@p1 ld.relaxed.gpu.global.v4.u32 {%4,%5,%6,%7}, [%13];\n"
                             "@p2 ld.relaxed.gpu.global.v4.u32 {%8,%9,%10,%11}, [%14];\n}"
                             : "+r"(v[0].x), "+r"(v[0].y), "+r"(v[0].z), "+r"(v[0].w), "+r"(v[1].x), "+r"(v[1].y), "+r"(v[1].z), "+r"(v[1].w),
                               "+r"(v[2].x), "+r"(v[2].y), "+r"(v[2].z), "+r"(v[2].w)
                             : "l"(asrc[0]), "l"(asrc[1]), "l"(asrc[2]), "r"(mq[0]), "r"(mq[1]), "r"(mq[2]) : "memory");
#pragma unroll
                for (int q = 0; q < 3; q++) mq[q] = min(min(v[q].x, v[q].y), min(v[q].z, v[q].w));
                const uint32_t lo = min(min(mq[0], mq[1]), mq[2]);
                if (__all_sync(0xffffffffu, lo != 0 || it == SPIN_MAX)) break;
            }
            CK(8, v[0].x);
            float acc[2][2][4] = {};
#pragma unroll
            for (int q = 0; q < 3; q++) {
#pragma unroll
                for (int pr = 0; pr < 2; pr++) {
                    mma16816(acc[pr][0], wb[q][pr][0], v[q].x, v[q].y);
                    mma16816(acc[pr][1], wb[q][pr][1], v[q].z, v[q].w);
                }
            }
            float y[4];
#pragma unroll
            for (int e = 0; e < 4; e++) y[e] = j < 2 ? acc[0][0][e] + acc[0][1][e] : acc[1][0][e] + acc[1][1][e];
            asm volatile("st.shared.v4.f32 [%0], {%1,%2,%3,%4};" :: "r"(ypart), "f"(y[0]), "f"(y[2]), "f"(y[1]), "f"(y[3]) : "memory");
            CK(9, 0);
            fin_arrive<6>();
        } else {
            continue;
        }
        if (b < NB - 1) fin_sync<5>();
    }
}

typedef CUresult (*EncodeFn)(CUtensorMap*, CUtensorMapDataType, cuuint32_t, void*, const cuuint64_t*, const cuuint64_t*,
                             const cuuint32_t*, const cuuint32_t*, CUtensorMapInterleave, CUtensorMapSwizzle,
                             CUtensorMapL2promotion, CUtensorMapFloatOOBfill);

CUtensorMap make_map(EncodeFn enc, void* ptr, uint64_t cols, uint64_t rows, uint32_t bcols, uint32_t brows,
                     CUtensorMapSwizzle sw, CUtensorMapL2promotion promo) {
    CUtensorMap m;
    const cuuint64_t dims[2] = {cols, rows};
    const cuuint64_t strides[1] = {cols * 2};
    const cuuint32_t box[2] = {bcols, brows};
    const cuuint32_t es[2] = {1, 1};
    enc(&m, CU_TENSOR_MAP_DATA_TYPE_BFLOAT16, 2, ptr, dims, strides, box, es, CU_TENSOR_MAP_INTERLEAVE_NONE, sw, promo,
        CU_TENSOR_MAP_FLOAT_OOB_FILL_NONE);
    return m;
}

}

extern "C" void kernel_launch(void* const* d_in, const int* in_sizes, int n_in, void* d_out, int out_size) {
    (void)in_sizes; (void)n_in; (void)out_size;
    static EncodeFn enc = nullptr;
    static int sms = 0;
    if (!enc) {
        cudaDriverEntryPointQueryResult qr;
        cudaGetDriverEntryPoint("cuTensorMapEncodeTiled", (void**)&enc, cudaEnableDefault, &qr);
        int dev = 0;
        cudaGetDevice(&dev);
        cudaDeviceGetAttribute(&sms, cudaDevAttrMultiProcessorCount, dev);
        cudaFuncSetAttribute(fused_decode_kernel, cudaFuncAttributeMaxDynamicSharedMemorySize, SM_TOTAL);
    }
    if (sms < NCTAS) return;
    const CUtensorMapL2promotion WPROMO = CU_TENSOR_MAP_L2_PROMOTION_L2_128B;
    Params p;
    p.k = make_map(enc, d_in[1], 64, (uint64_t)NBH * SK * 3, 64, TILE_ROWS, CU_TENSOR_MAP_SWIZZLE_128B, CU_TENSOR_MAP_L2_PROMOTION_NONE);
    p.v = make_map(enc, d_in[2], 64, (uint64_t)NBH * SK * 3, 64, TILE_ROWS, CU_TENSOR_MAP_SWIZZLE_128B, CU_TENSOR_MAP_L2_PROMOTION_NONE);
    p.wq = make_map(enc, d_in[3], NH * DH, DM, 48, 160, CU_TENSOR_MAP_SWIZZLE_NONE, WPROMO);
    p.wo = make_map(enc, d_in[4], DM, NH * DH, 32, WO_ROWS, CU_TENSOR_MAP_SWIZZLE_64B, WPROMO);
    p.wg = make_map(enc, d_in[7], FF, DM, 32, 80, CU_TENSOR_MAP_SWIZZLE_64B, (CUtensorMapL2promotion)GPROMO);
    p.wu = make_map(enc, d_in[8], FF, DM, 32, 80, CU_TENSOR_MAP_SWIZZLE_64B, (CUtensorMapL2promotion)GPROMO);
    p.wd = make_map(enc, d_in[9], DM, FF, 16, 192, CU_TENSOR_MAP_SWIZZLE_32B, WPROMO);
    p.x = (const __nv_bfloat16*)d_in[0];
    p.wr = (const __nv_bfloat16*)d_in[6];
    p.out = (__nv_bfloat16*)d_out;
    fused_decode_kernel<<<NCTAS, NTHREADS, SM_TOTAL, cudaStreamPerThread>>>(p);
}
```

```cpp
#include <cuda_runtime.h>
#include <cuda_bf16.h>
#include <cuda.h>
#include <stdint.h>

namespace {

constexpr int NB = 4, NH = 32, SK = 8192, DH = 192, DM = 640, FF = 1536;
constexpr int NBH = NB * NH;
constexpr int TILE = 64;
constexpr int UPB = SK / TILE;
constexpr int NUNITS = NBH * UPB;
constexpr int TILE_BYTES = TILE * DH * 2;
constexpr int TILE_ROWS = TILE * 3;
constexpr int NCTAS = 132;
constexpr int NQ_CTAS = 128;
constexpr int NE_CTAS = 112;

#define NWORK 2
#define LAG 3
#define NPOOL 896
#define RED0 120
#define RING 12
#define OREP 1
#define SROW0 124
#define NPROBE 6
#define VTRIG (NPOOL - 240)
#define TRIG_NS 2250
#define GPROMO 2
#define DCLK 150
#define DOFF 2300
#define HNAP 100
#define PAD0 1024
#define PAD1 1024
#define PAD2 1792
#define JIT 1
#define FARFIRST 1
#define OPRE 0
#define ONAP 0
#define NSS 0
#define FWAIT 100
#define SPREAD 1
#define GDLY 0
#define GPRED 1
#define NWL 2
#define GCLK 250
#define K0_DELAY_NS 1700
#define K0_STEP_NS 900
#define WO_GAP_NS 550
#define WO_ROWS 48
#define QNAP 250
#define WO_AT_NS 3600
constexpr int NAUX = 8;
constexpr int NTHREADS = (NAUX + NWORK + 2) * 32;
constexpr int SPIN_MAX = 1 << 22;

constexpr int SM_KV = 0;
constexpr int SM_A = SM_KV + NWORK * TILE_BYTES;
constexpr int SM_WQ = SM_A + 61440;
constexpr int SM_G = SM_WQ;
constexpr int SM_X = SM_G + 81920;
constexpr int XPITCH = 648;
constexpr int HPITCH = 1344;
constexpr int SM_RED = SM_X + 5 * HPITCH;
constexpr int FPITCH = 1040;
constexpr int SM_RED2 = SM_RED;
constexpr int YPITCH = 320;
constexpr int SM_MISC = SM_RED + 6144;
constexpr int BAR_KV = SM_MISC, BAR_WQ = SM_MISC + 32, BAR_W = SM_MISC + 40, SM_SIDE = SM_MISC + 48, BAR_G = SM_MISC + 64, SM_MOM = SM_MISC + 128;
constexpr int SM_TOTAL = SM_MISC + 160;

struct Params {
    CUtensorMap k, v;
    CUtensorMap wq;
    CUtensorMap wo;
    CUtensorMap wg, wu;
    CUtensorMap wd;
    const __nv_bfloat16 *x, *wr;
    __nv_bfloat16* out;
};

struct Early {
    uint32_t q[96];
    uint32_t umax[UPB];
};
#define LSTRIDE 16
struct State {
    float4 oacc[SROW0][64];
    float2 attn[NB][DM];
    float2 lsum[SROW0][LSTRIDE];
    unsigned pool[64];
    uint32_t tstart[32];
    uint32_t score[NPOOL - NSS][32];
};
constexpr int STATE_V4 = ((sizeof(State) / 32 + NQ_CTAS - 1) / NQ_CTAS) * 2;
static_assert(sizeof(State) % 32 == 0, "State is cleared in whole sectors");
static_assert(sizeof(Early) == 56 * 16, "an Early entry is cleared by 56 threads");
constexpr uint32_t X_O = 0;
constexpr uint32_t X_L = X_O + 4 * OREP * 1024;
constexpr uint32_t X_H = X_L + 4 * OREP * 128;
constexpr uint32_t X_A = X_H + NB * DM * 2;
constexpr uint32_t X_P = X_A + NB * FF * 2;
constexpr uint32_t X_S = X_P + 4096;
constexpr uint32_t X_END = X_S + NSS * 128;
static_assert(X_END <= 8 * 4096 && SROW0 == NBH - 4, "");
struct Scratch {
    unsigned char sided[8][2][4096];
    unsigned work[64];
    unsigned cnt_z[32];
    unsigned char pad0[PAD0];
    Early early[NBH];
    unsigned char pad1[PAD1];
    State st;
    unsigned char pad2[PAD2];
    float4 ring[RING][UPB][64];
};
constexpr size_t PAGE = 2u << 20;
static_assert(sizeof(Scratch) <= PAGE, "scratch must fit one page");
__device__ __align__(128) unsigned char g_raw[2 * PAGE];
__device__ __forceinline__ Scratch* scratch() {
    return reinterpret_cast<Scratch*>((reinterpret_cast<uintptr_t>(g_raw) + PAGE - 1) & ~(uintptr_t)(PAGE - 1));
}
template <typename T> __device__ __forceinline__ T* sided(int side, uint32_t x) {
    const uint32_t pair = (x >> 10) & 7;
    return reinterpret_cast<T*>(&scratch()->sided[pair][(side ^ pair) & 1]
                                    [(x & 127) + ((x & 128) << 1) + ((x & 768) << 2) + ((x >> 6) & 128) + ((x >> 5) & 512)]);
}
template <typename T> __device__ __forceinline__ T* other_side(T* p) { return reinterpret_cast<T*>(reinterpret_cast<uintptr_t>(p) ^ 4096); }
#define g_early scratch()->early
#define g_st scratch()->st
#define g_ring scratch()->ring
#define g_cnt_z scratch()->cnt_z
#define g_work scratch()->work
#define TS(i)
#define TSW(i)
#define TS2(i)
#define TSI(n, i)
#define PH(i)
#define CK(i, dep)
#define ARR()
#define PROG(u)

__device__ __forceinline__ int row_of(int u) { return (((unsigned)u >> (7 + NWL)) << NWL) | (u & ((1 << NWL) - 1)); }
__device__ __forceinline__ int pos_of(int u) { return ((unsigned)u >> NWL) & (UPB - 1); }
__device__ __forceinline__ int tile_of(int u) { return (row_of(u) * UPB + pos_of(u)) * TILE_ROWS; }

__device__ __forceinline__ uint32_t s2u(const void* p) { return (uint32_t)__cvta_generic_to_shared(p); }
__device__ __forceinline__ void mbar_init(uint32_t bar, int cnt) {
    asm volatile("mbarrier.init.shared::cta.b64 [%0], %1;" :: "r"(bar), "r"(cnt) : "memory");
}
__device__ __forceinline__ void mbar_expect_tx(uint32_t bar, uint32_t bytes) {
    asm volatile("mbarrier.arrive.expect_tx.shared::cta.b64 _, [%0], %1;" :: "r"(bar), "r"(bytes) : "memory");
}
__device__ __forceinline__ void mbar_wait(uint32_t bar, uint32_t parity) {
    asm volatile("{\n.reg .pred p;\n.reg .u32 n;\nmov.u32 n, 0;\nWAIT_LOOP:\n"
                 "mbarrier.try_wait.parity.shared::cta.b64 p, [%0], %1;\n"
                 "@p bra WAIT_DONE;\nadd.u32 n, n, 1;\nsetp.lt.u32 p, n, %2;\n@p bra WAIT_LOOP;\nWAIT_DONE:\n}"
                 :: "r"(bar), "r"(parity), "n"(SPIN_MAX) : "memory");
}
__device__ __forceinline__ void tma_tile(uint32_t dst, const CUtensorMap* tm, int row, uint32_t bar, uint64_t pol) {
    asm volatile("cp.async.bulk.tensor.2d.shared::cluster.global.mbarrier::complete_tx::bytes.L2::cache_hint "
                 "[%0], [%1, {%3, %4}], [%2], %5;"
                 :: "r"(dst), "l"(tm), "r"(bar), "r"(0), "r"(row), "l"(pol) : "memory");
}
__device__ __forceinline__ void request_tile(uint32_t dst, const CUtensorMap* tm, int unit, uint32_t bar, uint64_t pol) {
    asm volatile("{\n.reg .pred p;\nelect.sync _|p, 0xffffffff;\n"
                 "@p mbarrier.arrive.expect_tx.shared::cta.b64 _, [%2], %6;\n"
                 "@p cp.async.bulk.tensor.2d.shared::cluster.global.mbarrier::complete_tx::bytes.L2::cache_hint "
                 "[%0], [%1, {%3, %4}], [%2], %5;\n}"
                 :: "r"(dst), "l"(tm), "r"(bar), "r"(0), "r"(tile_of(unit)), "l"(pol), "n"(TILE_BYTES) : "memory");
}
__device__ __forceinline__ uint32_t now_ns() { uint32_t t; asm volatile("mov.u32 %0, %%globaltimer_lo;" : "=r"(t)); return t; }
__device__ __forceinline__ uint32_t now_clk() { uint32_t t; asm volatile("mov.u32 %0, %%clock;" : "=r"(t)); return t; }
__device__ __forceinline__ void wait_clk(uint32_t t) { while (__any_sync(0xffffffffu, (int)(now_clk() - t) < 0)) {} }
constexpr uint64_t EVICT_FIRST = 0x12F0000000000000ull, EVICT_NORMAL = 0x1000000000000000ull;
__device__ __forceinline__ void request_box(uint32_t dst, const CUtensorMap* tm, int col, int row, uint32_t bar, uint64_t pol) {
    asm volatile("{\n.reg .pred p;\nelect.sync _|p, 0xffffffff;\n"
                 "@p cp.async.bulk.tensor.2d.shared::cluster.global.mbarrier::complete_tx::bytes.L2::cache_hint [%0], [%1, {%3, %4}], [%2], %5;\n}"
                 :: "r"(dst), "l"(tm), "r"(bar), "r"(col), "r"(row), "l"(pol) : "memory");
}
__device__ __forceinline__ uint32_t lds32(uint32_t addr) {
    uint32_t v;
    asm volatile("ld.shared.u32 %0, [%1];" : "=r"(v) : "r"(addr) : "memory");
    return v;
}
__device__ __forceinline__ void ldsm4(uint32_t (&r)[4], uint32_t addr) {
    asm volatile("ldmatrix.sync.aligned.m8n8.x4.shared.b16 {%0,%1,%2,%3}, [%4];"
                 : "=r"(r[0]), "=r"(r[1]), "=r"(r[2]), "=r"(r[3]) : "r"(addr) : "memory");
}
__device__ __forceinline__ void ldsm4t(uint32_t (&r)[4], uint32_t addr) {
    asm volatile("ldmatrix.sync.aligned.m8n8.x4.trans.shared.b16 {%0,%1,%2,%3}, [%4];"
                 : "=r"(r[0]), "=r"(r[1]), "=r"(r[2]), "=r"(r[3]) : "r"(addr) : "memory");
}
__device__ __forceinline__ void mma16816(float (&c)[4], const uint32_t (&a)[4], uint32_t b0, uint32_t b1) {
    asm volatile("mma.sync.aligned.m16n8k16.row.col.f32.bf16.bf16.f32 {%0,%1,%2,%3}, {%4,%5,%6,%7}, {%8,%9}, {%0,%1,%2,%3};"
                 : "+f"(c[0]), "+f"(c[1]), "+f"(c[2]), "+f"(c[3])
                 : "r"(a[0]), "r"(a[1]), "r"(a[2]), "r"(a[3]), "r"(b0), "r"(b1));
}
__device__ __forceinline__ uint4 ld_relaxed_v4(const void* p) {
    uint4 v;
    asm volatile("ld.relaxed.gpu.global.v4.u32 {%0,%1,%2,%3}, [%4];" : "=r"(v.x), "=r"(v.y), "=r"(v.z), "=r"(v.w) : "l"(p) : "memory");
    return v;
}
__device__ __forceinline__ float4 ld_relaxed_f4(const void* p) {
    float4 v;
    asm volatile("ld.relaxed.gpu.global.v4.f32 {%0,%1,%2,%3}, [%4];" : "=f"(v.x), "=f"(v.y), "=f"(v.z), "=f"(v.w) : "l"(p) : "memory");
    return v;
}
__device__ __forceinline__ float2 ld_relaxed_f2(const void* p) {
    float2 v;
    asm volatile("ld.relaxed.gpu.global.v2.f32 {%0,%1}, [%2];" : "=f"(v.x), "=f"(v.y) : "l"(p) : "memory");
    return v;
}
__device__ __forceinline__ float4 ld_relaxed_b128(const void* p) {
    float4 v;
    asm volatile("{\n.reg .b128 t;\n.reg .b64 a, b;\nld.relaxed.gpu.global.b128 t, [%4];\nmov.b128 {a, b}, t;\n"
                 "mov.b64 {%0, %1}, a;\nmov.b64 {%2, %3}, b;\n}" : "=f"(v.x), "=f"(v.y), "=f"(v.z), "=f"(v.w) : "l"(p) : "memory");
    return v;
}
__device__ __forceinline__ void st_relaxed_b128(void* p, float x, float y, float z, float w) {
    asm volatile("{\n.reg .b128 t;\n.reg .b64 a, b;\nmov.b64 a, {%1, %2};\nmov.b64 b, {%3, %4};\nmov.b128 t, {a, b};\n"
                 "st.relaxed.gpu.global.b128 [%0], t;\n}" :: "l"(p), "f"(x), "f"(y), "f"(z), "f"(w) : "memory");
}
__device__ __forceinline__ unsigned ld_acquire(const unsigned* p) {
    unsigned v;
    asm volatile("ld.acquire.gpu.global.u32 %0, [%1];" : "=r"(v) : "l"(p) : "memory");
    return v;
}
__device__ __forceinline__ void st_relaxed(void* p, uint32_t v) {
    asm volatile("st.relaxed.gpu.global.u32 [%0], %1;" :: "l"(p), "r"(v) : "memory");
}
__device__ __forceinline__ void red_f2(float* p, float a, float b) {
    asm volatile("red.relaxed.gpu.global.add.v2.f32 [%0], {%1,%2};" :: "l"(p), "f"(a), "f"(b) : "memory");
}
__device__ __forceinline__ void red_f4(float* p, float a, float b, float c, float d) {
    asm volatile("red.relaxed.gpu.global.add.v4.f32 [%0], {%1,%2,%3,%4};" :: "l"(p), "f"(a), "f"(b), "f"(c), "f"(d) : "memory");
}
__device__ __forceinline__ void draw(int& ticket, unsigned* ctr, bool pred) {
    asm volatile("{\n.reg .pred p;\nsetp.ne.u32 p, %2, 0;\n@p atom.relaxed.gpu.global.inc.u32 %0, [%1], 0x7fffffff;\n}"
                 : "+r"(ticket) : "l"(ctr), "r"((uint32_t)pred) : "memory");
}
__device__ __forceinline__ void red_release(unsigned* p) {
    asm volatile("red.release.gpu.global.add.u32 [%0], 1;" :: "l"(p) : "memory");
}
__device__ __forceinline__ uint32_t ld_relaxed_u32(const void* p) {
    uint32_t v;
    asm volatile("ld.relaxed.gpu.global.u32 %0, [%1];" : "=r"(v) : "l"(p) : "memory");
    return v;
}
__device__ __forceinline__ float rcp_approx(float v) {
    float r;
    asm("rcp.approx.ftz.f32 %0, %1;" : "=f"(r) : "f"(v));
    return r;
}
__device__ __forceinline__ float sigmoid_approx(float v) {
    float e;
    asm("ex2.approx.ftz.f32 %0, %1;" : "=f"(e) : "f"(v * -1.4426950408889634f));
    return rcp_approx(1.0f + e);
}
__device__ __forceinline__ float sqrt_approx(float v) {
    float r;
    asm("sqrt.approx.ftz.f32 %0, %1;" : "=f"(r) : "f"(v));
    return r;
}
__device__ __forceinline__ uint2 ld_relaxed_v2(const void* p) {
    uint2 v;
    asm volatile("ld.relaxed.gpu.global.v2.u32 {%0,%1}, [%2];" : "=r"(v.x), "=r"(v.y) : "l"(p) : "memory");
    return v;
}
__device__ __forceinline__ void wait_count(const unsigned* p, unsigned target) {
#pragma unroll 1
    for (int it = 0; it < SPIN_MAX; it++) {
        if (ld_acquire(p) >= target) break;
        __nanosleep(400);
    }
}
__device__ __forceinline__ float4* oacc_at(int side, int row, int grp) {
    return row >= SROW0 ? sided<float4>(side, X_O + (row - SROW0) * 1024 + grp * 16) : &g_st.oacc[row][grp];
}
__device__ __forceinline__ float2* lsum_at(int side, int row) {
    return row >= SROW0 ? sided<float2>(side, X_L + (row - SROW0) * 128) : g_st.lsum[row];
}
__device__ __forceinline__ uint32_t* score_at(int side, int u, int lane) {
    return u >= NUNITS - NSS ? sided<uint32_t>(side, X_S + (u - (NUNITS - NSS)) * 128 + lane * 4) : &g_st.score[u - (NUNITS - NPOOL)][lane];
}
__device__ __forceinline__ void wait_row(int side, int bh, float n) {
    const float2* l = lsum_at(side, bh);
#pragma unroll 1
    for (int it = 0; it < SPIN_MAX; it++) {
        const float c = ld_relaxed_f2(l).y;
        if (c >= n) break;
        if (c == 0.f) __nanosleep(600);
    }
}
__device__ __forceinline__ void wait_row_o(int side, int bh, float n) {
    wait_row(side, bh, n);
    if (bh >= RED0) return;
#pragma unroll 1
    for (int it = 0; it < SPIN_MAX; it++) {
        if (__uint_as_float(ld_relaxed_u32(&g_st.oacc[bh][0].w)) == UPB) break;
        __nanosleep(300);
    }
}
__device__ __forceinline__ void spin_ns(int ns) {
    const long long t0 = clock64();
    while (clock64() - t0 < (long long)ns * 2) {}
}
__device__ __forceinline__ uint32_t pack_bf16(float lo, float hi) {
    uint32_t r;
    asm("cvt.rn.bf16x2.f32 %0, %1, %2;" : "=r"(r) : "f"(hi), "f"(lo));
    return r;
}
__device__ __forceinline__ float bf16r(float v) { return __uint_as_float(pack_bf16(0.f, v)); }
__device__ __forceinline__ uint32_t pack_neg(float lo, float hi) {
    const uint32_t w = pack_bf16(-lo, -hi);
    return w ? w : 0x80008000u;
}
__device__ __forceinline__ float lo_f(uint32_t v) { return __uint_as_float(v << 16); }
__device__ __forceinline__ float hi_f(uint32_t v) { return __uint_as_float(v & 0xffff0000u); }
__device__ __forceinline__ float warp_sum(float v) {
#pragma unroll
    for (int o = 16; o; o >>= 1) v += __shfl_xor_sync(0xffffffffu, v, o);
    return v;
}
__device__ __forceinline__ void layernorm20(float (&v)[20]) {
    float s = 0.f;
#pragma unroll
    for (int i = 0; i < 20; i++) s += v[i];
    const float mean = warp_sum(s) * (1.0f / DM);
    float q = 0.f;
#pragma unroll
    for (int i = 0; i < 20; i++) { const float d = v[i] - mean; q += d * d; }
    const float var = bf16r(warp_sum(q) * (1.0f / DM));
    const float m = bf16r(mean);
    const float rden = 1.0f / bf16r(sqrtf(bf16r(var + 1e-5f)));
#pragma unroll
    for (int i = 0; i < 20; i++) v[i] = bf16r(bf16r(v[i] - m) * rden);
}

__device__ __forceinline__ float sel4(int j, float a, float b, float c, float d) {
    float lo, hi, r;
    asm("{\n.reg .pred p;\nsetp.ne.s32 p, %3, 0;\nselp.f32 %0, %2, %1, p;\n}" : "=f"(lo) : "f"(a), "f"(b), "r"(j & 1));
    asm("{\n.reg .pred p;\nsetp.ne.s32 p, %3, 0;\nselp.f32 %0, %2, %1, p;\n}" : "=f"(hi) : "f"(c), "f"(d), "r"(j & 1));
    asm("{\n.reg .pred p;\nsetp.ne.s32 p, %3, 0;\nselp.f32 %0, %2, %1, p;\n}" : "=f"(r) : "f"(lo), "f"(hi), "r"(j & 2));
    return r;
}
template <typename T> __device__ __forceinline__ void pin(T*& p) { asm volatile("" : "+l"(p)); }
__device__ __forceinline__ void pin(uint32_t& v) { asm volatile("" : "+r"(v)); }
__device__ __forceinline__ void pin(float& v) { asm volatile("" : "+f"(v)); }
__device__ __forceinline__ uint32_t after(uint32_t n, float v) {
    asm volatile("{\n.reg .pred p;\nsetp.eq.u32 p, %1, 0x7fc1a5a5;\n@p add.u32 %0, %0, 32;\n}" : "+r"(n) : "r"(__float_as_uint(v)));
    return n;
}
__device__ __forceinline__ float2 lds64f(uint32_t addr) {
    float2 v;
    asm volatile("ld.shared.v2.f32 {%0,%1}, [%2];" : "=f"(v.x), "=f"(v.y) : "r"(addr) : "memory");
    return v;
}
__device__ __forceinline__ float4 lds128f(uint32_t addr) {
    float4 v;
    asm volatile("ld.shared.v4.f32 {%0,%1,%2,%3}, [%4];" : "=f"(v.x), "=f"(v.y), "=f"(v.z), "=f"(v.w) : "r"(addr) : "memory");
    return v;
}
__device__ __forceinline__ void sts64f(uint32_t addr, float a, float b, bool pred) {
    asm volatile("{\n.reg .pred p;\nsetp.ne.u32 p, %3, 0;\n@p st.shared.v2.f32 [%0], {%1,%2};\n}" :: "r"(addr), "f"(a), "f"(b), "r"((uint32_t)pred) : "memory");
}
__device__ __forceinline__ void sts128f(uint32_t addr, float a, float b, float c, float d, bool pred) {
    asm volatile("{\n.reg .pred p;\nsetp.ne.u32 p, %5, 0;\n@p st.shared.v4.f32 [%0], {%1,%2,%3,%4};\n}"
                 :: "r"(addr), "f"(a), "f"(b), "f"(c), "f"(d), "r"((uint32_t)pred) : "memory");
}
__device__ __forceinline__ void lds128_if(uint4& v, uint32_t addr, bool pred) {
    asm volatile("{\n.reg .pred p;\nsetp.ne.u32 p, %5, 0;\n@p ld.shared.v4.u32 {%0,%1,%2,%3}, [%4];\n}"
                 : "+r"(v.x), "+r"(v.y), "+r"(v.z), "+r"(v.w) : "r"(addr), "r"((uint32_t)pred) : "memory");
}
__device__ __forceinline__ void sts32f(uint32_t addr, float v) { asm volatile("st.shared.f32 [%0], %1;" :: "r"(addr), "f"(v) : "memory"); }
template <int ID> __device__ __forceinline__ void fin_arrive() { asm volatile("bar.arrive %0, 288;" :: "n"(ID) : "memory"); }
template <int ID> __device__ __forceinline__ void fin_sync() { asm volatile("bar.sync %0, 288;" :: "n"(ID) : "memory"); }
template <int ID> __device__ __forceinline__ void fin_sync(uint32_t n) { asm volatile("bar.sync %0, %1;" :: "n"(ID), "r"(n) : "memory"); }
__device__ __forceinline__ float2 sum8(uint32_t addr) {
    float2 t[8];
#pragma unroll
    for (int w = 0; w < 8; w++) t[w] = lds64f(addr + w * 128);
    return make_float2(((t[0].x + t[1].x) + (t[2].x + t[3].x)) + ((t[4].x + t[5].x) + (t[6].x + t[7].x)),
                       ((t[0].y + t[1].y) + (t[2].y + t[3].y)) + ((t[4].y + t[5].y) + (t[6].y + t[7].y)));
}
__device__ __forceinline__ float4 sum4x4(uint32_t addr) {
    float4 t[4];
#pragma unroll
    for (int w = 0; w < 4; w++) t[w] = lds128f(addr + w * 256);
    return make_float4((t[0].x + t[1].x) + (t[2].x + t[3].x), (t[0].y + t[1].y) + (t[2].y + t[3].y),
                       (t[0].z + t[1].z) + (t[2].z + t[3].z), (t[0].w + t[1].w) + (t[2].w + t[3].w));
}
template <int NJ>
__device__ __forceinline__ void load_o(uint32_t (&ob)[3 * NJ][2], int bh, int J0, int j) {
    float4 v[NJ][4];
    float2 l;
#pragma unroll 1
    for (int it = 0; it < SPIN_MAX; it++) {
#pragma unroll
        for (int J = 0; J < NJ; J++) {
#pragma unroll
            for (int e = 0; e < 4; e++) v[J][e] = ld_relaxed_f4(&g_st.oacc[bh][(J0 + J) * 16 + e * 4 + j]);
        }
        l = ld_relaxed_f2(g_st.lsum[bh]);
        bool ok = l.y == UPB;
#pragma unroll
        for (int J = 0; J < NJ; J++) {
#pragma unroll
            for (int e = 0; e < 4; e++) ok &= v[J][e].w == UPB;
        }
        if (__all_sync(0xffffffffu, ok)) break;
    }
    const float rl = __fdividef(1.0f, l.x);
#pragma unroll
    for (int J = 0; J < NJ; J++) {
        ob[3 * J][0] = pack_bf16(v[J][0].x * rl, v[J][1].x * rl);     ob[3 * J][1] = pack_bf16(v[J][2].x * rl, v[J][3].x * rl);
        ob[3 * J + 1][0] = pack_bf16(v[J][0].y * rl, v[J][1].y * rl); ob[3 * J + 1][1] = pack_bf16(v[J][2].y * rl, v[J][3].y * rl);
        ob[3 * J + 2][0] = pack_bf16(v[J][0].z * rl, v[J][1].z * rl); ob[3 * J + 2][1] = pack_bf16(v[J][2].z * rl, v[J][3].z * rl);
    }
}
__device__ __forceinline__ void aux_sync() { asm volatile("bar.sync 1, 256;" ::: "memory"); }

__global__ void __launch_bounds__(NTHREADS, 1)
fused_decode_kernel(const __grid_constant__ Params p) {
    extern __shared__ __align__(1024) unsigned char smem[];
    const uint32_t sb = s2u(smem);
    const int tid = threadIdx.x, warp = __shfl_sync(0xffffffffu, tid >> 5, 0), lane = tid & 31;
    const int cta = blockIdx.x;
    constexpr int grid = NCTAS;
    const int g = lane >> 2, j = lane & 3;
    const bool is_l = cta >= NE_CTAS, is_f = cta < 96 && !(cta & 1), is_g = cta < 80 && (cta & 1);
    const int fidx = cta >> 1;

    TS(0);
    if (warp == 4 && cta < NQ_CTAS) {
        asm volatile("{\n.reg .pred p;\nelect.sync _|p, 0xffffffff;\n"
                     "@p mbarrier.init.shared::cta.b64 [%0], 1;\n"
                     "@p fence.mbarrier_init.release.cluster;\n"
                     "@p mbarrier.arrive.expect_tx.shared::cta.b64 _, [%0], 61440;\n}" :: "r"(sb + BAR_WQ) : "memory");
#pragma unroll
        for (int i = 0; i < 4; i++) request_box(sb + SM_WQ + i * 15360, &p.wq, cta * 48, i * 160, sb + BAR_WQ, EVICT_NORMAL);
    }
    if (tid == 160) {
#pragma unroll
        for (int w = 0; w < NWORK; w++) mbar_init(sb + BAR_KV + w * 8, 1);
        mbar_init(sb + BAR_W, 1);
#pragma unroll
        for (int w = 0; w < 8; w++) mbar_init(sb + BAR_G + w * 8, 1);
        asm volatile("fence.mbarrier_init.release.cluster;" ::: "memory");
    }
    __syncthreads();
    if (warp == NAUX + NWORK + 1) {
        uint32_t t = now_clk() + 2 * WO_AT_NS;
        if (lane == 0) mbar_expect_tx(sb + BAR_W, cta < NE_CTAS ? 61440 : 49152);
        const int col = cta < NE_CTAS ? (cta & 3) * 160 : (cta - NE_CTAS) * 32, row = cta < NE_CTAS ? (cta >> 2) * DH : 28 * DH;
#pragma unroll 1
        for (int r = 0; r < DH; r += WO_ROWS) {
            wait_clk(t);
#pragma unroll 1
            for (int i = 0; i < (cta < NE_CTAS ? 5 : 4); i++)
                request_box(sb + SM_A + i * 12288 + r * 64, &p.wo, cta < NE_CTAS ? col + i * 32 : col, (cta < NE_CTAS ? row : row + i * DH) + r, sb + BAR_W, EVICT_FIRST);
            t += 2 * WO_GAP_NS;
        }
        if (!is_f && !is_g) return;
        if (lane < 8) mbar_expect_tx(sb + BAR_G + lane * 8, is_f ? 10240 : 6144);
        asm volatile("bar.sync 9, 288;" ::: "memory");
        asm volatile("fence.proxy.async.shared::cta;" ::: "memory");
#pragma unroll 1
        for (int it = 0; it < SPIN_MAX; it++) {
            t = ld_relaxed_u32(g_st.tstart);
            if (__all_sync(0xffffffffu, t != 0)) break;
            __nanosleep(400);
        }
#pragma unroll 1
        for (int it = 0; it < SPIN_MAX; it++) if (__all_sync(0xffffffffu, t - now_ns() > 2 * TRIG_NS)) break;
        TSW(11);
        t = now_clk() + (is_f ? 0 : DOFF);
#pragma unroll 1
        for (int i = 0; i < 8; i++, t += is_f ? GCLK : DCLK) {
            wait_clk(t);
            if (is_f) {
                request_box(sb + SM_G + i * 5120, &p.wg, fidx * 32, i * 80, sb + BAR_G + i * 8, EVICT_NORMAL);
                request_box(sb + SM_G + 40960 + i * 5120, &p.wu, fidx * 32, i * 80, sb + BAR_G + i * 8, EVICT_NORMAL);
            } else {
                request_box(sb + SM_G + i * 6144, &p.wd, fidx * 16, i * 192, sb + BAR_G + i * 8, EVICT_NORMAL);
            }
        }
        return;
    }
    if (warp == NAUX + NWORK) {
        if (cta < NQ_CTAS) {
#pragma unroll
            for (int i = lane; i < STATE_V4; i += 32)
                if (cta * STATE_V4 + i < (int)(sizeof(State) / 16)) reinterpret_cast<uint4*>(&g_st)[cta * STATE_V4 + i] = make_uint4(0u, 0u, 0u, 0u);
            if (cta * 512 < X_END) {
                uint4* z = sided<uint4>(0, cta * 512 + lane * 16);
                *z = make_uint4(0u, 0u, 0u, 0u);
                *other_side(z) = make_uint4(0u, 0u, 0u, 0u);
            }
            __syncwarp();
            if (lane == 0) red_release(g_cnt_z);
        }
        if (lane == 0) { TS2(2); wait_count(g_cnt_z, NQ_CTAS); TS2(29); }
        __syncwarp();
        asm volatile("bar.arrive 2, %0;" :: "n"((NWORK + 1) * 32) : "memory");
        uint32_t rtt[2] = {0xffffffffu, 0xffffffffu};
        if (lane == 0) {
#pragma unroll 1
            for (int r = 0; r < 2 * NPROBE; r++) {
                int v = 0;
                uint32_t t1 = 0;
                unsigned* ctr = sided<unsigned>(r & 1, X_P + ((cta * 32 + (r >> 1) * 768) & 4095));
                pin(ctr);
                const uint32_t t0 = now_clk();
                draw(v, ctr, true);
                asm volatile("{\n.reg .pred q;\nsetp.ge.s32 q, %1, 0;\n@q mov.u32 %0, %%clock;\n}" : "+r"(t1) : "r"(v) : "memory");
                if (r & 1) rtt[1] = min(rtt[1], t1 - t0); else rtt[0] = min(rtt[0], t1 - t0);
            }
            sts32f(sb + SM_SIDE, __int_as_float(rtt[1] < rtt[0]));
        }
        const int side = __shfl_sync(0xffffffffu, rtt[1] < rtt[0], 0);
        fin_arrive<3>();
        int job = cta;
        auto sum_rows = [&](int row_end) {
#pragma unroll 1
            for (; job < 8 * min(row_end, RED0); job += NCTAS) {
                const int row = job >> 3, grp = (job & 7) * 8 + (lane & 7);
                if (lane == 0) wait_row(side, row, UPB);
                __syncwarp();
                const float4* src = &g_ring[row % RING][lane >> 3][grp];
                float sx = 0.f, sy = 0.f, sz = 0.f;
#pragma unroll 1
                for (int i = 0; i < 2; i++, src += 64 * 64) {
                    float4 v[16];
#pragma unroll 1
                    for (int it = 0; it < SPIN_MAX; it++) {
                        bool ok = true;
#pragma unroll
                        for (int k = 0; k < 16; k++) v[k] = ld_relaxed_b128(src + k * 4 * 64);
#pragma unroll
                        for (int k = 0; k < 16; k++) ok &= v[k].w == (float)(row + 1);
                        if (__all_sync(0xffffffffu, ok)) break;
                    }
#pragma unroll
                    for (int k = 0; k < 16; k++) { sx += v[k].x; sy += v[k].y; sz += v[k].z; }
                }
#pragma unroll
                for (int o = 8; o < 32; o <<= 1) {
                    sx += __shfl_xor_sync(0xffffffffu, sx, o); sy += __shfl_xor_sync(0xffffffffu, sy, o); sz += __shfl_xor_sync(0xffffffffu, sz, o);
                }
                if (lane < 8) st_relaxed_b128(&g_st.oacc[row][grp], sx, sy, sz, UPB);
            }
        };
        {
            uint32_t wr[10];
            float wsum = 0.f;
#pragma unroll
            for (int i = 0; i < 10; i++) {
                const int w = 4 * lane + 128 * (i >> 2) + (i & 3) - (i >= 8 ? 2 * lane : 0);
                wr[i] = *reinterpret_cast<const uint32_t*>(p.wr + (w >> 4) * 32 + (w & 3) * 8 + ((w >> 1) & 6));
                wsum += lo_f(wr[i]) + hi_f(wr[i]);
            }
            wsum = warp_sum(wsum);
            const int lb = lane >> 3, lc = lane & 7;
            uint32_t ypart = sb + SM_RED2 + (lb >> 1) * 160 + lc * 16 + (lb & 1) * 8;
            __nv_bfloat16* out = p.out + lb * DM + fidx * 16 + lc;
            float nmean_l = 0.f, rden_l = 0.f, sig_l = 0.f;
#pragma unroll 1
            for (int b = 0; b < NB; b++) {
                const uint32_t hx = X_H + b * (DM * 2), hrow = sb + SM_X + b * HPITCH;
                const uint4 *src0 = sided<uint4>(side, hx + 16 * lane), *src1 = sided<uint4>(side, hx + 512 + 16 * lane);
                const uint2* src2 = sided<uint2>(side, hx + 1024 + 8 * lane);
                sum_rows((b + 1) * NH);
                if (!is_l && !is_f && !is_g) continue;
                pin(src0); pin(src1); pin(src2); pin(ypart); pin(out);
                if (lane == 0) wait_row(side, b * NH + (is_l ? 28 : NH - 1), is_l ? 1 : FWAIT);
                __syncwarp();
                if (is_l) {
                    const int col = (cta - NE_CTAS) * 32 + 2 * (lane & 15);
                    uint32_t lpart = sb + SM_RED + (lane & 15) * 8;
                    const uint32_t xv = *reinterpret_cast<const uint32_t*>(p.x + b * DM + col);
                    uint32_t* hdst = sided<uint32_t>(lane >> 4, hx + 4 * ((col >> 5) * 16 + (col & 6) * 2 + ((col >> 3) & 3)));
                    float4 early;
#pragma unroll 1
                    for (int it = 0; it < SPIN_MAX; it++) {
                        early = ld_relaxed_f4(&g_st.attn[b][col]);
                        if (__all_sync(0xffffffffu, early.y == NE_CTAS / 4 && early.w == NE_CTAS / 4)) break;
                    }
                    if (lane == 0) TS2(23);
                    float x0 = lo_f(xv), x1 = hi_f(xv);
                    pin(hdst); pin(lpart); pin(x0); pin(x1);
                    fin_sync<4>();
                    CK(2, lds32(sb + SM_RED));
                    const float2 late = sum8(lpart);
                    st_relaxed(hdst, pack_neg(x0 + bf16r(early.x + late.x), x1 + bf16r(early.z + late.y)));
                    CK(3, 0);
                    if (lane == 0) TS2(15);
                    fin_sync<5>();
                    continue;
                }
                uint4 h0, h1;
                uint2 h2;
                float mm[5][4];
#pragma unroll 1
                for (int it = 0; it < SPIN_MAX; it++) {
                    h0 = ld_relaxed_v4(src0);
                    h1 = ld_relaxed_v4(src1);
                    h2 = ld_relaxed_v2(src2);
                    asm volatile("st.shared.v4.u32 [%0], {%1,%2,%3,%4};" :: "r"(hrow + lane * 16), "r"(h0.x), "r"(h0.y), "r"(h0.z), "r"(h0.w) : "memory");
                    asm volatile("st.shared.v4.u32 [%0], {%1,%2,%3,%4};" :: "r"(hrow + 512 + lane * 16), "r"(h1.x), "r"(h1.y), "r"(h1.z), "r"(h1.w) : "memory");
                    asm volatile("st.shared.v2.u32 [%0], {%1,%2};" :: "r"(hrow + 1024 + lane * 8), "r"(h2.x), "r"(h2.y) : "memory");
                    const uint32_t w[10] = {h0.x, h0.y, h0.z, h0.w, h1.x, h1.y, h1.z, h1.w, h2.x, h2.y};
#pragma unroll
                    for (int i = 0; i < 5; i++) {
                        const uint32_t a[4] = {w[2 * i], 0x3f803f80u, w[2 * i + 1], 0x3f803f80u};
                        mm[i][0] = mm[i][1] = mm[i][2] = mm[i][3] = 0.f;
                        mma16816(mm[i], a, w[2 * i], w[2 * i + 1]);
                    }
                    const uint32_t lo = min(min(min(h0.x, h0.y), min(h0.z, h0.w)), min(min(min(h1.x, h1.y), min(h1.z, h1.w)), min(h2.x, h2.y)));
                    if (GDLY && !is_f) sts32f(sb + SM_MOM, __uint_as_float(now_clk()));
                    const bool ok = __all_sync(0xffffffffu, lo != 0 || it == SPIN_MAX - 1);
                    asm volatile("{\n.reg .pred p;\nsetp.ne.u32 p, %0, 0;\n@p bar.arrive 7, 288;\n}" :: "r"((uint32_t)ok) : "memory");
                    if (ok) break;
                    if (!is_f) __nanosleep(HNAP);
                }
                CK(4, h0.x);
                if (lane == 0 && is_f) TS2(12);
                const uint32_t hw[10] = {h0.x, h0.y, h0.z, h0.w, h1.x, h1.y, h1.z, h1.w, h2.x, h2.y};
                float m1 = ((mm[0][2] + mm[1][2]) + (mm[2][2] + mm[3][2])) + ((mm[0][3] + mm[1][3]) + (mm[2][3] + mm[3][3])) + (mm[4][2] + mm[4][3]);
                float m2 = (g & 1) ? ((mm[0][1] + mm[1][1]) + (mm[2][1] + mm[3][1])) + mm[4][1] : ((mm[0][0] + mm[1][0]) + (mm[2][0] + mm[3][0])) + mm[4][0];
                m2 += __shfl_xor_sync(0xffffffffu, m2, 4);
                m1 = (m1 + __shfl_xor_sync(0xffffffffu, m1, 1)) + (__shfl_xor_sync(0xffffffffu, m1, 2) + __shfl_xor_sync(0xffffffffu, m1, 3));
                m2 = (__shfl_sync(0xffffffffu, m2, 0) + __shfl_sync(0xffffffffu, m2, 9)) + (__shfl_sync(0xffffffffu, m2, 18) + __shfl_sync(0xffffffffu, m2, 27));
                m1 *= 1.0f / DM;
                const float nmean = bf16r(m1);
                const float var = bf16r(fmaxf(fmaf(-m1, m1, m2 * (1.0f / DM)), 0.f));
                const float den = bf16r(sqrt_approx(bf16r(var + 1e-5f)));
                if (is_f) {
                    sts64f(sb + SM_MOM + b * 8, nmean, den, lane == 0);
                    CK(5, 0);
                    fin_arrive<4>();
                } else {
                    const float rden = rcp_approx(den);
                    if (lb == b) { nmean_l = nmean; rden_l = rden; }
                    __syncwarp();
                    const float2 hw2 = lds64f(sb + SM_X + lb * HPITCH + ((fidx >> 1) * 16 + (lc & 6) * 2 + (fidx & 1) * 2) * 4);
                    const float nh0 = (lc & 1) ? hi_f(__float_as_uint(hw2.x)) : lo_f(__float_as_uint(hw2.x));
                    const float nh1 = (lc & 1) ? hi_f(__float_as_uint(hw2.y)) : lo_f(__float_as_uint(hw2.y));
                    float rr = 0.f;
#pragma unroll
                    for (int i = 0; i < 10; i++) rr = fmaf(lo_f(hw[i]), lo_f(wr[i]), fmaf(hi_f(hw[i]), hi_f(wr[i]), rr));
                    const float sig = bf16r(sigmoid_approx(bf16r((nmean * wsum - warp_sum(rr)) * rden)));
                    if (lb == b) sig_l = sig;
                    const float ln0 = bf16r(bf16r(nmean_l - nh0) * rden_l), ln1 = bf16r(bf16r(nmean_l - nh1) * rden_l);
                    fin_sync<6>(after(after(after(288, sig_l), ln0), ln1));
                    CK(10, lds32(ypart));
                    float2 t[16];
#pragma unroll
                    for (int i = 0; i < 16; i++) t[i] = lds64f(ypart + i * YPITCH);
#pragma unroll
                    for (int o = 1; o < 16; o <<= 1) {
#pragma unroll
                        for (int i = 0; i < 16; i += 2 * o) { t[i].x += t[i + o].x; t[i].y += t[i + o].y; }
                    }
                    const uint32_t ov = pack_bf16(bf16r(ln0 + bf16r(bf16r(-t[0].x) * sig_l)) - nh0, bf16r(ln1 + bf16r(bf16r(-t[0].y) * sig_l)) - nh1);
                    asm volatile("{\n.reg .pred p;\n.reg .b16 lo, hi;\nsetp.eq.u32 p, %2, 3;\nmov.b32 {lo, hi}, %1;\n"
                                 "@p st.global.u16 [%0], lo;\n@p st.global.u16 [%0 + 16], hi;\n}" :: "l"(out), "r"(ov), "r"(b) : "memory");
                    CK(11, 0);
                    if (lane == 0) TS2(13);
                }
                if (b < NB - 1) fin_sync<5>();
            }
            if (cta == 0 && lane == 0) { g_work[0] = 0; g_cnt_z[0] = 0; }
        }
        return;
    }
    if (warp >= NAUX) {
        const int wk = warp - NAUX;
        const uint32_t bar = sb + BAR_KV + wk * 8;
        const uint32_t buf = sb + SM_KV + wk * TILE_BYTES;
        uint64_t pol;
        asm volatile("createpolicy.fractional.L2::evict_first.b64 %0, 1.0;" : "=l"(pol));
        const int nstatic = NWORK * grid;
        constexpr int POOL0 = NUNITS - NPOOL;
        int uk = wk * grid + cta;
        if (lane == 0) {
            spin_ns(K0_DELAY_NS + wk * K0_STEP_NS);
            mbar_expect_tx(bar, TILE_BYTES);
            tma_tile(buf, &p.k, tile_of(uk), bar, pol);
        }
        __syncwarp();
        uint32_t koff[3], voff[3];
        {
            const int r = lane & 7, hf = (lane >> 3) & 1;
            const int kkey = hf ? 8 + (r ^ 1) : r;
            const int vh = lane >> 4;
            const int vkey = ((r & 1) ? 8 : 0) + (vh ? (r ^ 1) : r);
#pragma unroll
            for (int b = 0; b < 3; b++) {
                const int rk = 3 * kkey + b, rv = 3 * vkey + b;
                koff[b] = buf + rk * 128 + (((lane >> 4) ^ (rk & 7)) << 4);
                voff[b] = buf + rv * 128 + ((hf ^ (rv & 7)) << 4);
            }
        }
        uint32_t phase = 0;
        uint4 qf[6];
        auto load_q = [&](int u) {
            const uint32_t* q = &g_early[row_of(u)].q[j * 4];
#pragma unroll
            for (int i = 0; i < 6; i++) qf[i] = ld_relaxed_v4(q + i * 16);
        };
        load_q(uk);
        int uq[LAG];
        uint32_t sq[LAG];
#pragma unroll
        for (int i = 0; i < LAG; i++) { uq[i] = -1; sq[i] = 0; }
        uint4 mv = make_uint4(0u, 0u, 0u, 0u);
        float freed = UPB;
        while (true) {
            const int uv = uq[0];
            uint32_t sv = sq[0];
#pragma unroll
            for (int i = 0; i + 1 < LAG; i++) { uq[i] = uq[i + 1]; sq[i] = sq[i + 1]; }
            uq[LAG - 1] = uk;
            if (uk < NUNITS) {
                PH(7);
#pragma unroll 1
                for (int it = 0; it < SPIN_MAX; it++) {
                    uint32_t lo = 0xffffffffu;
#pragma unroll
                    for (int i = 0; i < 6; i++) lo = min(min(lo, min(qf[i].x, qf[i].y)), min(qf[i].z, qf[i].w));
                    if (__all_sync(0xffffffffu, lo != 0)) break;
                    __nanosleep(QNAP);
                    load_q(uk);
                }
                mbar_wait(bar, phase); phase ^= 1;
                PH(0); ARR();
                TSI(0, 16); TSI(1, 18);
                float acc[2][4][4] = {};
#pragma unroll
                for (int ks = 0; ks < 12; ks++) {
                    const uint4 qq = qf[ks >> 1];
                    const uint32_t b0 = (ks & 1) ? qq.z : qq.x, b1 = (ks & 1) ? qq.w : qq.y;
#pragma unroll
                    for (int mt = 0; mt < 4; mt++) {
                        uint32_t a[4];
                        ldsm4(a, (koff[ks >> 2] ^ ((ks & 3) << 5)) + mt * 6144);
                        mma16816(acc[ks & 1][mt], a, b0, b1);
                    }
                }
                PH(1);
                TSI(0, 17); TSI(1, 19);
                if (uv < NUNITS) request_tile(buf, uv >= 0 ? &p.v : &p.k, uv >= 0 ? uv : uk + nstatic, bar, pol);
                const float sa = sel4(j, acc[0][0][0], acc[0][1][0], acc[0][2][0], acc[0][3][0]) + sel4(j, acc[1][0][0], acc[1][1][0], acc[1][2][0], acc[1][3][0]);
                const float sc = sel4(j, acc[0][0][2], acc[0][1][2], acc[0][2][2], acc[0][3][2]) + sel4(j, acc[1][0][2], acc[1][1][2], acc[1][2][2], acc[1][3][2]);
                const uint32_t raw = pack_bf16(sa, sc);
                const float scale = -0.07216878364870322f;
                const uint32_t sk = pack_bf16(lo_f(raw) * scale, hi_f(raw) * scale);
                sq[LAG - 1] = sk;
                if (uk >= POOL0) {
                    uint32_t* sdst = score_at(0, uk, lane);
                    st_relaxed(sdst, sk ? sk : 0x80008000u);
                    if (uk >= NUNITS - NSS) st_relaxed(other_side(sdst), sk ? sk : 0x80008000u);
                }
                int a = (int)(sk << 16), b = (int)(sk & 0xffff0000u);
                a ^= (a >> 31) & 0x7fff0000; b ^= (b >> 31) & 0x7fff0000;
                const int mx = __reduce_max_sync(0xffffffffu, max(a, b));
                if (lane == 0) st_relaxed(&g_early[row_of(uk)].umax[pos_of(uk)], (uint32_t)mx | 1u);
            }
            if (uv < 0) {
                uk += nstatic;
                load_q(uk);
                continue;
            }
            if (uv >= NUNITS) break;
            const int bh = row_of(uv);
#pragma unroll 1
            for (int it = 0; it < SPIN_MAX; it++) {
                if (__all_sync(0xffffffffu, (mv.x & mv.y & mv.z & mv.w & 1u) && (uv < POOL0 || sv != 0) && freed == UPB)) break;
                mv = ld_relaxed_v4(&g_early[bh].umax[lane * 4]);
                if (bh >= RING && bh < RED0) freed = __uint_as_float(ld_relaxed_u32(&g_st.oacc[bh - RING][(lane & 7) * 8].w));
                if (uv >= POOL0) sv = ld_relaxed_u32(score_at(lds32(sb + SM_SIDE), uv, lane));
            }
            PH(2);
            int un = NUNITS, vn = 0;
            draw(un, g_work, uk < NUNITS && lane == 0);
            int mx = __reduce_max_sync(0xffffffffu, max(max((int)mv.x, (int)mv.y), max((int)mv.z, (int)mv.w))) & 0xffff0000;
            mx ^= (mx >> 31) & 0x7fff0000;
            const float m = __int_as_float(mx);
            const float l2e = 1.4426950408889634f;
            const uint32_t pp = pack_bf16(exp2f((lo_f(sv) - m) * l2e), exp2f((hi_f(sv) - m) * l2e));
            uint32_t pb[8];
#pragma unroll
            for (int t = 0; t < 4; t++) {
                pb[2 * t] = __shfl_sync(0xffffffffu, pp, 8 * j + t);
                pb[2 * t + 1] = __shfl_sync(0xffffffffu, pp, 8 * j + 4 + t);
            }
            float lacc[4] = {};
            const uint32_t ones[4] = {0x3f803f80u, 0x3f803f80u, 0x3f803f80u, 0x3f803f80u};
#pragma unroll
            for (int t = 0; t < 4; t++) mma16816(lacc, ones, pb[2 * t], pb[2 * t + 1]);
            if (uv < nstatic) {
                asm volatile("bar.sync 2, %0;" :: "n"((NWORK + 1) * 32) : "memory");
                TSW(3);
            }
            const int grp = 16 * j + 4 * (g & 1) + (g >> 1);
            const int acc_row = bh >= NBH - 4 ? bh + 4 * (pos_of(uv) % OREP) : bh;
            float4* dst = bh < RED0 ? &g_ring[bh % RING][pos_of(uv)][grp] : oacc_at(FARFIRST ? lds32(sb + SM_SIDE) ^ 1 : 0, acc_row, grp);
            float4* dst2 = other_side(dst);
            float2* ldst = lsum_at(lane & 1, acc_row);
            if (bh >= SROW0 && lane < 2) red_f2(&ldst->x, lacc[0], 1.f);
            float tag = bh < RED0 ? (float)(bh + 1) : 1.f;
            un = __shfl_sync(0xffffffffu, un, 0) + (LAG + 1) * nstatic;
            uint32_t pooled = uq[0] >= POOL0 && lane == 0;
            pin(dst); pin(dst2); pin(ldst); pin(tag); pin(voff[0]); pin(voff[1]); pin(voff[2]); pin(pooled);
            PH(3);
            mbar_wait(bar, phase); phase ^= 1;
            PH(4); ARR();
            draw(vn, g_st.pool, pooled);
            float acc[12][4] = {};
#pragma unroll
            for (int t = 0; t < 4; t++) {
#pragma unroll
                for (int mt = 0; mt < 12; mt++) {
                    uint32_t a[4];
                    ldsm4t(a, (voff[mt >> 2] ^ ((mt & 3) << 5)) + t * 6144);
                    mma16816(acc[mt], a, pb[2 * t], pb[2 * t + 1]);
                }
            }
            PH(5);
            if (lane == 0) PROG(un);
            if (un < NUNITS) request_tile(buf, &p.k, un, bar, pol);
            float o[6];
#pragma unroll
            for (int e = 0; e < 6; e++) {
                const int q = e % 3, c = (e / 3) * 2;
                o[e] = sel4(j, acc[q][c], acc[3 + q][c], acc[6 + q][c], acc[9 + q][c]);
            }
            if (bh >= SROW0) {
                red_f4(&dst->x, o[0], o[1], o[2], tag);
                red_f4(&dst[16].x, o[3], o[4], o[5], tag);
                red_f4(&dst2->x, o[0], o[1], o[2], tag);
                red_f4(&dst2[16].x, o[3], o[4], o[5], tag);
            } else {
                if (bh >= RED0) {
                    red_f4(&dst->x, o[0], o[1], o[2], tag);
                    red_f4(&dst[8].x, o[3], o[4], o[5], tag);
                } else {
                    st_relaxed_b128(dst, o[0], o[1], o[2], tag);
                    st_relaxed_b128(dst + 8, o[3], o[4], o[5], tag);
                }
                if (lane == 0) red_f2(&ldst->x, lacc[0], 1.f);
            }
            if (uq[0] >= POOL0) {
                vn = __shfl_sync(0xffffffffu, vn, 0);
                uq[0] = POOL0 + vn;
                if (vn == VTRIG && lane == 0) st_relaxed(g_st.tstart, (now_ns() + TRIG_NS) | 1u);
            }
            if (un < NUNITS) load_q(un);
            else if (uq[0] < NUNITS) request_tile(buf, &p.v, uq[0], bar, pol);
            PH(6);
            if (uq[0] >= NUNITS && un >= NUNITS) break;
            uk = un;
            if (uq[0] < NUNITS) {
                const int nb = row_of(uq[0]);
                mv = ld_relaxed_v4(&g_early[nb].umax[lane * 4]);
                freed = nb >= RING && nb < RED0 ? __uint_as_float(ld_relaxed_u32(&g_st.oacc[nb - RING][(lane & 7) * 8].w)) : UPB;
                if (uq[0] >= POOL0) sq[0] = ld_relaxed_u32(score_at(lds32(sb + SM_SIDE), uq[0], lane));
            }
        }
        return;
    }

    __nv_bfloat16* xs = reinterpret_cast<__nv_bfloat16*>(smem + SM_X);
    float* red = reinterpret_cast<float*>(smem + SM_RED);
    const int frow = (lane & 7) + ((lane >> 4) << 3), fcol = (lane >> 3) & 1;
    if (cta < NQ_CTAS) {
        uint2 xr[5];
        if (warp < NB) {
#pragma unroll
            for (int i = 0; i < 5; i++) xr[i] = *reinterpret_cast<const uint2*>(p.x + warp * DM + i * 128 + lane * 4);
        }
        TS(26);
        if (warp < NB) {
            float v[20];
#pragma unroll
            for (int i = 0; i < 5; i++) {
                v[4 * i] = lo_f(xr[i].x); v[4 * i + 1] = hi_f(xr[i].x); v[4 * i + 2] = lo_f(xr[i].y); v[4 * i + 3] = hi_f(xr[i].y);
            }
            layernorm20(v);
#pragma unroll
            for (int i = 0; i < 5; i++)
                *reinterpret_cast<uint2*>(xs + warp * XPITCH + i * 128 + lane * 4) =
                    make_uint2(pack_bf16(v[4 * i], v[4 * i + 1]), pack_bf16(v[4 * i + 2], v[4 * i + 3]));
        }
        TS(27);
        aux_sync();
        mbar_wait(sb + BAR_WQ, 0);
        TS(1);
        const uint32_t xfrag = sb + SM_X + ((g & 3) * XPITCH + 2 * j) * 2;
        float acc[3][4] = {};
#pragma unroll
        for (int s = 0; s < 5; s++) {
            const int ks = warp * 5 + s;
            const uint32_t b0 = lds32(xfrag + ks * 32), b1 = lds32(xfrag + ks * 32 + 16);
            const int row = ks * 16 + frow;
#pragma unroll
            for (int mt = 0; mt < 3; mt++) {
                uint32_t a[4];
                ldsm4t(a, sb + SM_WQ + (row * 6 + 2 * mt + fcol) * 16);
                mma16816(acc[mt], a, b0, b1);
            }
        }
        if (j < 2) {
#pragma unroll
            for (int mt = 0; mt < 3; mt++) {
                *reinterpret_cast<float2*>(red + (warp * 48 + mt * 16 + g) * 4 + 2 * j) = make_float2(acc[mt][0], acc[mt][1]);
                *reinterpret_cast<float2*>(red + (warp * 48 + mt * 16 + 8 + g) * 4 + 2 * j) = make_float2(acc[mt][2], acc[mt][3]);
            }
        }
        aux_sync();
        if (tid < 96) {
            const int b = tid & 3, cp = tid >> 2;
            float s0 = 0.f, s1 = 0.f;
#pragma unroll
            for (int w = 0; w < 8; w++) { s0 += red[(w * 48 + 2 * cp) * 4 + b]; s1 += red[(w * 48 + 2 * cp + 1) * 4 + b]; }
            const int h = cta >> 2, d = (cta & 3) * 48 + 2 * cp;
            const int ch = d >> 3, jj = (d & 7) >> 1;
            st_relaxed(&g_early[b * NH + h].q[(ch >> 2) * 16 + jj * 4 + (ch & 3)], pack_neg(s0, s1));
        }
        TS(28);
    }
    if (tid < 160) *reinterpret_cast<uint2*>(smem + SM_X + 4 * HPITCH + tid * 8) = make_uint2(0x3f803f80u, 0x3f803f80u);
    fin_sync<3>();
    const int side = lds32(sb + SM_SIDE);
    mbar_wait(sb + BAR_W, 0);
    TS(7);
    uint32_t part = sb + SM_RED + (warp * 32 + 8 * j + g) * 4;

#pragma unroll 1
    for (int b = 0; b < NB; b++) {
        if (b == NB - 1 && (is_f || is_g)) asm volatile("bar.arrive 9, 288;" ::: "memory");
        if (is_l) {
            uint32_t a[6][2][4];
#pragma unroll
            for (int s = 0; s < 6; s++) {
                const int row = (warp * 6 + s) * 16 + frow;
#pragma unroll
                for (int mt = 0; mt < 2; mt++) ldsm4t(a[s][mt], sb + SM_A + (row * 4 + ((2 * mt + fcol) ^ ((row >> 1) & 3))) * 16);
            }
            const int bh = b * NH + 28 + (warp >> 1);
            const float4* osrc[OREP];
            const float2* lsrc[OREP];
#pragma unroll
            for (int c = 0; c < OREP; c++) {
                const int row = b == NB - 1 ? bh + 4 * c : bh;
                osrc[c] = oacc_at(side, row, (warp & 1) * 32 + lane);
                lsrc[c] = lsum_at(side, row);
                pin(osrc[c]); pin(lsrc[c]);
            }
            if (lane == 0) wait_row_o(side, bh, 1);
            __syncwarp();
            float2 lv;
#pragma unroll 1
            for (int it = 0; it < SPIN_MAX; it++) {
                lv = ld_relaxed_f2(lsrc[0]);
#pragma unroll
                for (int c = 1; c < OREP; c++) {
                    const float2 lc = ld_relaxed_f2(lsrc[c]);
                    if (b == NB - 1) { lv.x += lc.x; lv.y += lc.y; }
                }
                if (__all_sync(0xffffffffu, lv.y == UPB)) break;
            }
            if (warp == 7) TSW(25);
            float rl = rcp_approx(lv.x);
            float4 ov;
            pin(part); pin(rl);
            if (OPRE && lane == 0) {
#pragma unroll 1
                for (int it = 0; it < SPIN_MAX; it++) {
                    if (__uint_as_float(ld_relaxed_u32(&osrc[0]->w)) >= UPB * OPRE / (16 * OREP)) break;
                    if (ONAP) __nanosleep(ONAP);
                }
            }
            __syncwarp();
#pragma unroll 1
            for (int it = 0;; it++) {
                float4 oc[OREP];
#pragma unroll
                for (int c = 0; c < OREP; c++) oc[c] = ld_relaxed_f4(osrc[c]);
                ov = oc[0];
                if (b == NB - 1) {
#pragma unroll
                    for (int c = 1; c < OREP; c++) { ov.x += oc[c].x; ov.y += oc[c].y; ov.z += oc[c].z; ov.w += oc[c].w; }
                }
                if (__all_sync(0xffffffffu, ov.w == UPB || it == SPIN_MAX)) break;
            }
            CK(0, __float_as_uint(ov.x));
            const float px = __shfl_xor_sync(0xffffffffu, ov.x, 4), py = __shfl_xor_sync(0xffffffffu, ov.y, 4),
                        pz = __shfl_xor_sync(0xffffffffu, ov.z, 4);
            const uint32_t w[3] = {pack_bf16(ov.x * rl, px * rl), pack_bf16(ov.y * rl, py * rl), pack_bf16(ov.z * rl, pz * rl)};
            float acc[2][2][4] = {};
#pragma unroll
            for (int s = 0; s < 6; s++) {
                const uint32_t b0 = __shfl_sync(0xffffffffu, w[s % 3], (s / 3) * 16 + j);
                const uint32_t b1 = __shfl_sync(0xffffffffu, w[s % 3], (s / 3) * 16 + 8 + j);
#pragma unroll
                for (int mt = 0; mt < 2; mt++) mma16816(acc[mt][s & 1], a[s][mt], b0, b1);
            }
            sts32f(part, sel4(j, acc[0][0][0] + acc[0][1][0], acc[0][0][2] + acc[0][1][2], acc[1][0][0] + acc[1][1][0], acc[1][0][2] + acc[1][1][2]));
            CK(1, 0);
            fin_arrive<4>();
            if (warp == 7) TSW(30);
            if (warp == 5) TSW(31);
            if (cta == NE_CTAS && lane < 28) reinterpret_cast<uint4*>(&g_early[bh])[(warp & 1) * 28 + lane] = make_uint4(0u, 0u, 0u, 0u);
            fin_sync<5>();
            continue;
        }
        {
            const int bh = b * NH + (cta >> 2);
            if (tid == 0) wait_row_o(side, bh, UPB);
            aux_sync();
            if (warp < 5) {
                uint32_t ob[12][2];
                load_o<4>(ob, bh, 0, j);
                float acc[2][2][4] = {};
#pragma unroll
                for (int ks = 0; ks < 12; ks++) {
                    const int row = ks * 16 + frow;
#pragma unroll
                    for (int mt = 0; mt < 2; mt++) {
                        uint32_t a[4];
                        ldsm4t(a, sb + SM_A + warp * 12288 + (row * 4 + ((2 * mt + fcol) ^ ((row >> 1) & 3))) * 16);
                        mma16816(acc[mt][ks & 1], a, ob[ks][0], ob[ks][1]);
                    }
                }
                red_f2(&g_st.attn[b][(cta & 3) * 160 + warp * 32 + 8 * j + g].x,
                       sel4(j, acc[0][0][0] + acc[0][1][0], acc[0][0][2] + acc[0][1][2], acc[1][0][0] + acc[1][1][0], acc[1][0][2] + acc[1][1][2]), 1.f);
                TS(8);
            } else if (warp > 5 && (cta & 3) == 0 && tid - 192 < 56) {
                reinterpret_cast<uint4*>(&g_early[bh])[tid - 192] = make_uint4(0u, 0u, 0u, 0u);
            }
        }
        if (is_f) {
            const int kq = warp >> 1, tp = warp & 1;
            uint32_t hfrag = sb + SM_X + min(g, 4) * HPITCH + (kq * 80 + 4 * j) * 4;
            uint4 hv[5] = {};
#pragma unroll
            for (int s = 0; s < 5; s++) lds128_if(hv[s], hfrag + s * 64, true);
            uint32_t ga[10][2][4];
#pragma unroll
            for (int s = 0; s < 10; s++) {
                if (s % 5 == 0 && b == NB - 1) mbar_wait(sb + BAR_G + (kq * 2 + s / 5) * 8, 0);
                const int row = (kq * 10 + s) * 16 + frow;
#pragma unroll
                for (int t = 0; t < 2; t++) ldsm4t(ga[s][t], sb + SM_G + fcol * 40960 + (row * 4 + ((2 * tp + t) ^ ((row >> 1) & 3))) * 16);
            }
            if (warp == NAUX - 1) TSW(9);
            uint32_t fpart = sb + SM_RED + 2 * j * FPITCH + warp * 128 + g * 16;
            uint32_t dsum = sb + SM_RED + (lane >> 3) * FPITCH + tp * 128 + (lane & 7) * 16, csum = sb + SM_RED + 4 * FPITCH + tp * 128 + (lane & 7) * 16;
            uint32_t mom = sb + SM_MOM + (lane >> 3) * 8;
            uint32_t* dst = sided<uint32_t>(side ^ 1, X_A + (2 * fidx + tp) * 128 + (lane ^ 2 * tp) * 4);
            pin(fpart); pin(hfrag); pin(dsum); pin(csum); pin(mom); pin(dst);
            fin_sync<7>();
#pragma unroll
            for (int s = 0; s < 5; s++) lds128_if(hv[s], hfrag + s * 64, g == b);
            float acc[2][2][4] = {};
#pragma unroll
            for (int s = 0; s < 5; s++) {
#pragma unroll
                for (int t = 0; t < 2; t++) mma16816(acc[t][0], ga[2 * s][t], hv[s].x, hv[s].y);
#pragma unroll
                for (int t = 0; t < 2; t++) mma16816(acc[t][1], ga[2 * s + 1][t], hv[s].z, hv[s].w);
            }
#pragma unroll
            for (int e = 0; e < 2; e++)
                sts128f(fpart + e * FPITCH, acc[0][0][e] + acc[0][1][e], acc[0][0][2 + e] + acc[0][1][2 + e],
                        acc[1][0][e] + acc[1][1][e], acc[1][0][2 + e] + acc[1][1][2 + e], 2 * j + e < 5);
            CK(5, 0);
            if (warp < 2) {
                fin_sync<4>();
                CK(6, lds32(dsum));
                float2 m = lds64f(mom);
                m.y = rcp_approx(m.y);
                const float4 d = sum4x4(dsum), cs = sum4x4(csum);
                const float g0 = bf16r(fmaf(m.x, cs.x, -d.x) * m.y), g1 = bf16r(fmaf(m.x, cs.z, -d.z) * m.y);
                const float u0 = bf16r(fmaf(m.x, cs.y, -d.y) * m.y), u1 = bf16r(fmaf(m.x, cs.w, -d.w) * m.y);
                const uint32_t av = pack_neg(bf16r(g0 * sigmoid_approx(g0)) * u0, bf16r(g1 * sigmoid_approx(g1)) * u1);
                asm volatile("{\n.reg .pred p;\nsetp.eq.u32 p, %3, 3;\n@p st.relaxed.gpu.global.u32 [%0], %2;\n@p st.relaxed.gpu.global.u32 [%1], %2;\n}"
                             :: "l"(dst), "l"(other_side(dst)), "r"(av), "r"(b) : "memory");
                CK(7, 0);
                TS(14);
            } else {
                fin_arrive<4>();
            }
        } else if (is_g) {
            if (b == NB - 1) {
                mbar_wait(sb + BAR_G + warp * 8, 0);
                if (warp == NAUX - 1) TSW(10);
            }
            uint32_t wb[3][2][2][4];
#pragma unroll
            for (int s = 0; s < 12; s++) {
                const int odd = (lane >> 2) & 1, c = ((lane & 2) * 2 + (s & 1) * 2 + (lane >> 4)) ^ (2 * odd);
                const int row = (warp * 12 + (s >> 1) * 2 + odd) * 16 + (lane & 1) * 8 + c;
                ldsm4t(wb[s >> 2][(s >> 1) & 1][s & 1], sb + SM_G + (row * 2 + (fcol ^ ((row >> 2) & 1))) * 16);
            }
            const uint4* asrc[3];
#pragma unroll
            for (int q = 0; q < 3; q++) {
                asrc[q] = sided<uint4>(side, X_A + (warp * 12 + 4 * q + 2 * (g >> 2) + (j >> 1)) * 128 + (g & 3) * 32 + (j & 1) * 16);
                pin(asrc[q]);
            }
            uint32_t ypart = sb + SM_RED2 + (warp * 2 + (j >> 1)) * YPITCH + (j & 1) * 160 + g * 16;
            pin(ypart);
            fin_sync<7>();
            if (GDLY) wait_clk(lds32(sb + SM_MOM) + GDLY);
            uint4 v[3] = {};
            uint32_t mq[3] = {};
#pragma unroll 1
            for (int it = b < NB - 1 ? SPIN_MAX : 0;; it++) {
                asm volatile("{\n.reg .pred p0, p1, p2;\nsetp.eq.u32 p0, %15, 0;\nsetp.eq.u32 p1, %16, 0;\nsetp.eq.u32 p2, %17, 0;\n"
                             "@p0 ld.relaxed.gpu.global.v4.u32 {%0,%1,%2,%3}, [%12];\n"
                             "@p1 ld.relaxed.gpu.global.v4.u32 {%4,%5,%6,%7}, [%13];\n"
                             "@p2 ld.relaxed.gpu.global.v4.u32 {%8,%9,%10,%11}, [%14];\n}"
                             : "+r"(v[0].x), "+r"(v[0].y), "+r"(v[0].z), "+r"(v[0].w), "+r"(v[1].x), "+r"(v[1].y), "+r"(v[1].z), "+r"(v[1].w),
                               "+r"(v[2].x), "+r"(v[2].y), "+r"(v[2].z), "+r"(v[2].w)
                             : "l"(asrc[0]), "l"(asrc[1]), "l"(asrc[2]), "r"(mq[0]), "r"(mq[1]), "r"(mq[2]) : "memory");
#pragma unroll
                for (int q = 0; q < 3; q++) mq[q] = min(min(v[q].x, v[q].y), min(v[q].z, v[q].w));
                const uint32_t lo = min(min(mq[0], mq[1]), mq[2]);
                if (__all_sync(0xffffffffu, lo != 0 || it == SPIN_MAX)) break;
            }
            CK(8, v[0].x);
            float acc[2][2][4] = {};
#pragma unroll
            for (int q = 0; q < 3; q++) {
#pragma unroll
                for (int pr = 0; pr < 2; pr++) {
                    mma16816(acc[pr][0], wb[q][pr][0], v[q].x, v[q].y);
                    mma16816(acc[pr][1], wb[q][pr][1], v[q].z, v[q].w);
                }
            }
            float y[4];
#pragma unroll
            for (int e = 0; e < 4; e++) y[e] = j < 2 ? acc[0][0][e] + acc[0][1][e] : acc[1][0][e] + acc[1][1][e];
            asm volatile("st.shared.v4.f32 [%0], {%1,%2,%3,%4};" :: "r"(ypart), "f"(y[0]), "f"(y[2]), "f"(y[1]), "f"(y[3]) : "memory");
            CK(9, 0);
            fin_arrive<6>();
        } else {
            continue;
        }
        if (b < NB - 1) fin_sync<5>();
    }
}

typedef CUresult (*EncodeFn)(CUtensorMap*, CUtensorMapDataType, cuuint32_t, void*, const cuuint64_t*, const cuuint64_t*,
                             const cuuint32_t*, const cuuint32_t*, CUtensorMapInterleave, CUtensorMapSwizzle,
                             CUtensorMapL2promotion, CUtensorMapFloatOOBfill);

CUtensorMap make_map(EncodeFn enc, void* ptr, uint64_t cols, uint64_t rows, uint32_t bcols, uint32_t brows,
                     CUtensorMapSwizzle sw, CUtensorMapL2promotion promo) {
    CUtensorMap m;
    const cuuint64_t dims[2] = {cols, rows};
    const cuuint64_t strides[1] = {cols * 2};
    const cuuint32_t box[2] = {bcols, brows};
    const cuuint32_t es[2] = {1, 1};
    enc(&m, CU_TENSOR_MAP_DATA_TYPE_BFLOAT16, 2, ptr, dims, strides, box, es, CU_TENSOR_MAP_INTERLEAVE_NONE, sw, promo,
        CU_TENSOR_MAP_FLOAT_OOB_FILL_NONE);
    return m;
}

}

extern "C" void kernel_launch(void* const* d_in, const int* in_sizes, int n_in, void* d_out, int out_size) {
    (void)in_sizes; (void)n_in; (void)out_size;
    static EncodeFn enc = nullptr;
    static int sms = 0;
    if (!enc) {
        cudaDriverEntryPointQueryResult qr;
        cudaGetDriverEntryPoint("cuTensorMapEncodeTiled", (void**)&enc, cudaEnableDefault, &qr);
        int dev = 0;
        cudaGetDevice(&dev);
        cudaDeviceGetAttribute(&sms, cudaDevAttrMultiProcessorCount, dev);
        cudaFuncSetAttribute(fused_decode_kernel, cudaFuncAttributeMaxDynamicSharedMemorySize, SM_TOTAL);
    }
    if (sms < NCTAS) return;
    const CUtensorMapL2promotion WPROMO = CU_TENSOR_MAP_L2_PROMOTION_L2_128B;
    Params p;
    p.k = make_map(enc, d_in[1], 64, (uint64_t)NBH * SK * 3, 64, TILE_ROWS, CU_TENSOR_MAP_SWIZZLE_128B, CU_TENSOR_MAP_L2_PROMOTION_NONE);
    p.v = make_map(enc, d_in[2], 64, (uint64_t)NBH * SK * 3, 64, TILE_ROWS, CU_TENSOR_MAP_SWIZZLE_128B, CU_TENSOR_MAP_L2_PROMOTION_NONE);
    p.wq = make_map(enc, d_in[3], NH * DH, DM, 48, 160, CU_TENSOR_MAP_SWIZZLE_NONE, WPROMO);
    p.wo = make_map(enc, d_in[4], DM, NH * DH, 32, WO_ROWS, CU_TENSOR_MAP_SWIZZLE_64B, WPROMO);
    p.wg = make_map(enc, d_in[7], FF, DM, 32, 80, CU_TENSOR_MAP_SWIZZLE_64B, (CUtensorMapL2promotion)GPROMO);
    p.wu = make_map(enc, d_in[8], FF, DM, 32, 80, CU_TENSOR_MAP_SWIZZLE_64B, (CUtensorMapL2promotion)GPROMO);
    p.wd = make_map(enc, d_in[9], DM, FF, 16, 192, CU_TENSOR_MAP_SWIZZLE_32B, WPROMO);
    p.x = (const __nv_bfloat16*)d_in[0];
    p.wr = (const __nv_bfloat16*)d_in[6];
    p.out = (__nv_bfloat16*)d_out;
    fused_decode_kernel<<<NCTAS, NTHREADS, SM_TOTAL, cudaStreamPerThread>>>(p);
}
```

```cpp
#include <cuda_runtime.h>
#include <cuda_bf16.h>
#include <cuda.h>
#include <stdint.h>

namespace {

constexpr int NB = 4, NH = 32, SK = 8192, DH = 192, DM = 640, FF = 1536;
constexpr int NBH = NB * NH;
constexpr int TILE = 64;
constexpr int UPB = SK / TILE;
constexpr int NUNITS = NBH * UPB;
constexpr int TILE_BYTES = TILE * DH * 2;
constexpr int TILE_ROWS = TILE * 3;
constexpr int NCTAS = 132;
constexpr int NQ_CTAS = 128;
constexpr int NE_CTAS = 112;

#define NWORK 2
#define LAG 3
#define NPOOL 896
#define RED0 120
#define RING 12
#define OREP 1
#define SROW0 124
#define NPROBE 6
#define VTRIG (NPOOL - 240)
#define TRIG_NS 2250
#define GPROMO 2
#define DCLK 150
#define DOFF 2300
#define HNAP 100
#define PAD0 1024
#define PAD1 1024
#define PAD2 1792
#define JIT 1
#define FARFIRST 1
#define OPRE 0
#define ONAP 0
#define NSS 0
#define FWAIT 100
#define SPREAD 1
#define GDLY 0
#define GPRED 1
#define NWL 2
#define WBAR 1
#define GEARLY 0
#define SKEW 16
#define GCLK 250
#define K0_DELAY_NS 1700
#define K0_STEP_NS 900
#define WO_GAP_NS 550
#define WO_ROWS 48
#define QNAP 250
#define WO_AT_NS 3600
constexpr int NAUX = 8;
constexpr int NTHREADS = (NAUX + NWORK + 2) * 32;
constexpr int SPIN_MAX = 1 << 22;

constexpr int SM_KV = 0;
constexpr int SM_A = SM_KV + NWORK * TILE_BYTES;
constexpr int SM_WQ = SM_A + 61440;
constexpr int SM_G = SM_WQ;
constexpr int SM_X = SM_G + 81920;
constexpr int XPITCH = 648;
constexpr int HPITCH = 1344;
constexpr int SM_RED = SM_X + 5 * HPITCH;
constexpr int FPITCH = 1040;
constexpr int SM_RED2 = SM_RED;
constexpr int YPITCH = 320;
constexpr int SM_MISC = SM_RED + 6144;
constexpr int BAR_KV = SM_MISC, BAR_WQ = SM_MISC + 32, BAR_W = SM_MISC + 40, SM_SIDE = SM_MISC + 48, BAR_G = SM_MISC + 64, SM_MOM = SM_MISC + 128;
constexpr int SM_TOTAL = SM_MISC + 160;

struct Params {
    CUtensorMap k, v;
    CUtensorMap wq;
    CUtensorMap wo;
    CUtensorMap wg, wu;
    CUtensorMap wd;
    const __nv_bfloat16 *x, *wr;
    __nv_bfloat16* out;
};

struct Early {
    uint32_t q[96];
    uint32_t umax[UPB];
};
#define LSTRIDE 16
struct State {
    float4 oacc[SROW0][64];
    float2 attn[NB][DM];
    float2 lsum[SROW0][LSTRIDE];
    unsigned pool[64];
    uint32_t tstart[32];
    uint32_t score[NPOOL][32];
};
constexpr int STATE_V4 = ((sizeof(State) / 32 + NQ_CTAS - 1) / NQ_CTAS) * 2;
static_assert(sizeof(State) % 32 == 0, "State is cleared in whole sectors");
static_assert(sizeof(Early) == 56 * 16, "an Early entry is cleared by 56 threads");
constexpr uint32_t X_O = 0;
constexpr uint32_t X_L = X_O + 4 * OREP * 1024;
constexpr uint32_t X_H = X_L + 4 * OREP * 128;
constexpr uint32_t X_A = X_H + NB * DM * 2;
constexpr uint32_t X_P = X_A + NB * FF * 2;
constexpr uint32_t X_END = X_P + 4096;
static_assert(X_END <= 8 * 4096 && SROW0 == NBH - 4, "");
struct Scratch {
    unsigned char sided[8][2][4096];
    unsigned work[64];
    unsigned cnt_z[32];
    unsigned char pad0[PAD0];
    Early early[NBH];
    unsigned char pad1[PAD1];
    State st;
    unsigned char pad2[PAD2];
    float4 ring[RING][UPB][64];
};
constexpr size_t PAGE = 2u << 20;
static_assert(sizeof(Scratch) <= PAGE, "scratch must fit one page");
__device__ __align__(128) unsigned char g_raw[2 * PAGE];
__device__ __forceinline__ Scratch* scratch() {
    return reinterpret_cast<Scratch*>((reinterpret_cast<uintptr_t>(g_raw) + PAGE - 1) & ~(uintptr_t)(PAGE - 1));
}
template <typename T> __device__ __forceinline__ T* sided(int side, uint32_t x) {
    const uint32_t pair = (x >> 10) & 7;
    return reinterpret_cast<T*>(&scratch()->sided[pair][(side ^ pair) & 1]
                                    [(x & 127) + ((x & 128) << 1) + ((x & 768) << 2) + ((x >> 6) & 128) + ((x >> 5) & 512)]);
}
template <typename T> __device__ __forceinline__ T* other_side(T* p) { return reinterpret_cast<T*>(reinterpret_cast<uintptr_t>(p) ^ 4096); }
#define g_early scratch()->early
#define g_st scratch()->st
#define g_ring scratch()->ring
#define g_cnt_z scratch()->cnt_z
#define g_work scratch()->work
#define TS(i)
#define TSW(i)
#define TS2(i)
#define TSI(n, i)
#define PH(i)
#define CK(i, dep)
#define ARR()
#define PROG(u)
#define LT(i)

__device__ __forceinline__ int row_of(int u) { return (((unsigned)u >> (7 + NWL)) << NWL) | (u & ((1 << NWL) - 1)); }
__device__ __forceinline__ int pos_of(int u) { return ((unsigned)u >> NWL) & (UPB - 1); }
__device__ __forceinline__ int tile_of(int u) { return (row_of(u) * UPB + ((pos_of(u) + (u & ((1 << NWL) - 1)) * SKEW) & (UPB - 1))) * TILE_ROWS; }

__device__ __forceinline__ uint32_t s2u(const void* p) { return (uint32_t)__cvta_generic_to_shared(p); }
__device__ __forceinline__ void mbar_init(uint32_t bar, int cnt) {
    asm volatile("mbarrier.init.shared::cta.b64 [%0], %1;" :: "r"(bar), "r"(cnt) : "memory");
}
__device__ __forceinline__ void mbar_expect_tx(uint32_t bar, uint32_t bytes) {
    asm volatile("mbarrier.arrive.expect_tx.shared::cta.b64 _, [%0], %1;" :: "r"(bar), "r"(bytes) : "memory");
}
__device__ __forceinline__ void mbar_wait(uint32_t bar, uint32_t parity) {
    asm volatile("{\n.reg .pred p;\n.reg .u32 n;\nmov.u32 n, 0;\nWAIT_LOOP:\n"
                 "mbarrier.try_wait.parity.shared::cta.b64 p, [%0], %1;\n"
                 "@p bra WAIT_DONE;\nadd.u32 n, n, 1;\nsetp.lt.u32 p, n, %2;\n@p bra WAIT_LOOP;\nWAIT_DONE:\n}"
                 :: "r"(bar), "r"(parity), "n"(SPIN_MAX) : "memory");
}
__device__ __forceinline__ void tma_tile(uint32_t dst, const CUtensorMap* tm, int row, uint32_t bar, uint64_t pol) {
    asm volatile("cp.async.bulk.tensor.2d.shared::cluster.global.mbarrier::complete_tx::bytes.L2::cache_hint "
                 "[%0], [%1, {%3, %4}], [%2], %5;"
                 :: "r"(dst), "l"(tm), "r"(bar), "r"(0), "r"(row), "l"(pol) : "memory");
}
__device__ __forceinline__ void request_tile(uint32_t dst, const CUtensorMap* tm, int unit, uint32_t bar, uint64_t pol) {
    asm volatile("{\n.reg .pred p;\nelect.sync _|p, 0xffffffff;\n"
                 "@p mbarrier.arrive.expect_tx.shared::cta.b64 _, [%2], %6;\n"
                 "@p cp.async.bulk.tensor.2d.shared::cluster.global.mbarrier::complete_tx::bytes.L2::cache_hint "
                 "[%0], [%1, {%3, %4}], [%2], %5;\n}"
                 :: "r"(dst), "l"(tm), "r"(bar), "r"(0), "r"(tile_of(unit)), "l"(pol), "n"(TILE_BYTES) : "memory");
}
__device__ __forceinline__ uint32_t now_ns() { uint32_t t; asm volatile("mov.u32 %0, %%globaltimer_lo;" : "=r"(t)); return t; }
__device__ __forceinline__ uint32_t now_clk() { uint32_t t; asm volatile("mov.u32 %0, %%clock;" : "=r"(t)); return t; }
__device__ __forceinline__ void wait_clk(uint32_t t) { while (__any_sync(0xffffffffu, (int)(now_clk() - t) < 0)) {} }
constexpr uint64_t EVICT_FIRST = 0x12F0000000000000ull, EVICT_NORMAL = 0x1000000000000000ull;
__device__ __forceinline__ void request_box(uint32_t dst, const CUtensorMap* tm, int col, int row, uint32_t bar, uint64_t pol) {
    asm volatile("{\n.reg .pred p;\nelect.sync _|p, 0xffffffff;\n"
                 "@p cp.async.bulk.tensor.2d.shared::cluster.global.mbarrier::complete_tx::bytes.L2::cache_hint [%0], [%1, {%3, %4}], [%2], %5;\n}"
                 :: "r"(dst), "l"(tm), "r"(bar), "r"(col), "r"(row), "l"(pol) : "memory");
}
__device__ __forceinline__ uint32_t lds32(uint32_t addr) {
    uint32_t v;
    asm volatile("ld.shared.u32 %0, [%1];" : "=r"(v) : "r"(addr) : "memory");
    return v;
}
__device__ __forceinline__ void ldsm4(uint32_t (&r)[4], uint32_t addr) {
    asm volatile("ldmatrix.sync.aligned.m8n8.x4.shared.b16 {%0,%1,%2,%3}, [%4];"
                 : "=r"(r[0]), "=r"(r[1]), "=r"(r[2]), "=r"(r[3]) : "r"(addr) : "memory");
}
__device__ __forceinline__ void ldsm4t(uint32_t (&r)[4], uint32_t addr) {
    asm volatile("ldmatrix.sync.aligned.m8n8.x4.trans.shared.b16 {%0,%1,%2,%3}, [%4];"
                 : "=r"(r[0]), "=r"(r[1]), "=r"(r[2]), "=r"(r[3]) : "r"(addr) : "memory");
}
__device__ __forceinline__ void mma16816(float (&c)[4], const uint32_t (&a)[4], uint32_t b0, uint32_t b1) {
    asm volatile("mma.sync.aligned.m16n8k16.row.col.f32.bf16.bf16.f32 {%0,%1,%2,%3}, {%4,%5,%6,%7}, {%8,%9}, {%0,%1,%2,%3};"
                 : "+f"(c[0]), "+f"(c[1]), "+f"(c[2]), "+f"(c[3])
                 : "r"(a[0]), "r"(a[1]), "r"(a[2]), "r"(a[3]), "r"(b0), "r"(b1));
}
__device__ __forceinline__ uint4 ld_relaxed_v4(const void* p) {
    uint4 v;
    asm volatile("ld.relaxed.gpu.global.v4.u32 {%0,%1,%2,%3}, [%4];" : "=r"(v.x), "=r"(v.y), "=r"(v.z), "=r"(v.w) : "l"(p) : "memory");
    return v;
}
__device__ __forceinline__ float4 ld_relaxed_f4(const void* p) {
    float4 v;
    asm volatile("ld.relaxed.gpu.global.v4.f32 {%0,%1,%2,%3}, [%4];" : "=f"(v.x), "=f"(v.y), "=f"(v.z), "=f"(v.w) : "l"(p) : "memory");
    return v;
}
__device__ __forceinline__ float2 ld_relaxed_f2(const void* p) {
    float2 v;
    asm volatile("ld.relaxed.gpu.global.v2.f32 {%0,%1}, [%2];" : "=f"(v.x), "=f"(v.y) : "l"(p) : "memory");
    return v;
}
__device__ __forceinline__ float4 ld_relaxed_b128(const void* p) {
    float4 v;
    asm volatile("{\n.reg .b128 t;\n.reg .b64 a, b;\nld.relaxed.gpu.global.b128 t, [%4];\nmov.b128 {a, b}, t;\n"
                 "mov.b64 {%0, %1}, a;\nmov.b64 {%2, %3}, b;\n}" : "=f"(v.x), "=f"(v.y), "=f"(v.z), "=f"(v.w) : "l"(p) : "memory");
    return v;
}
__device__ __forceinline__ void st_relaxed_b128(void* p, float x, float y, float z, float w) {
    asm volatile("{\n.reg .b128 t;\n.reg .b64 a, b;\nmov.b64 a, {%1, %2};\nmov.b64 b, {%3, %4};\nmov.b128 t, {a, b};\n"
                 "st.relaxed.gpu.global.b128 [%0], t;\n}" :: "l"(p), "f"(x), "f"(y), "f"(z), "f"(w) : "memory");
}
__device__ __forceinline__ unsigned ld_acquire(const unsigned* p) {
    unsigned v;
    asm volatile("ld.acquire.gpu.global.u32 %0, [%1];" : "=r"(v) : "l"(p) : "memory");
    return v;
}
__device__ __forceinline__ void st_relaxed(void* p, uint32_t v) {
    asm volatile("st.relaxed.gpu.global.u32 [%0], %1;" :: "l"(p), "r"(v) : "memory");
}
__device__ __forceinline__ void red_f2(float* p, float a, float b) {
    asm volatile("red.relaxed.gpu.global.add.v2.f32 [%0], {%1,%2};" :: "l"(p), "f"(a), "f"(b) : "memory");
}
__device__ __forceinline__ void red_f4(float* p, float a, float b, float c, float d) {
    asm volatile("red.relaxed.gpu.global.add.v4.f32 [%0], {%1,%2,%3,%4};" :: "l"(p), "f"(a), "f"(b), "f"(c), "f"(d) : "memory");
}
__device__ __forceinline__ void draw(int& ticket, unsigned* ctr, bool pred) {
    asm volatile("{\n.reg .pred p;\nsetp.ne.u32 p, %2, 0;\n@p atom.relaxed.gpu.global.inc.u32 %0, [%1], 0x7fffffff;\n}"
                 : "+r"(ticket) : "l"(ctr), "r"((uint32_t)pred) : "memory");
}
__device__ __forceinline__ void red_release(unsigned* p) {
    asm volatile("red.release.gpu.global.add.u32 [%0], 1;" :: "l"(p) : "memory");
}
__device__ __forceinline__ uint32_t ld_relaxed_u32(const void* p) {
    uint32_t v;
    asm volatile("ld.relaxed.gpu.global.u32 %0, [%1];" : "=r"(v) : "l"(p) : "memory");
    return v;
}
__device__ __forceinline__ float rcp_approx(float v) {
    float r;
    asm("rcp.approx.ftz.f32 %0, %1;" : "=f"(r) : "f"(v));
    return r;
}
__device__ __forceinline__ float sigmoid_approx(float v) {
    float e;
    asm("ex2.approx.ftz.f32 %0, %1;" : "=f"(e) : "f"(v * -1.4426950408889634f));
    return rcp_approx(1.0f + e);
}
__device__ __forceinline__ float sqrt_approx(float v) {
    float r;
    asm("sqrt.approx.ftz.f32 %0, %1;" : "=f"(r) : "f"(v));
    return r;
}
__device__ __forceinline__ uint2 ld_relaxed_v2(const void* p) {
    uint2 v;
    asm volatile("ld.relaxed.gpu.global.v2.u32 {%0,%1}, [%2];" : "=r"(v.x), "=r"(v.y) : "l"(p) : "memory");
    return v;
}
__device__ __forceinline__ void wait_count(const unsigned* p, unsigned target) {
#pragma unroll 1
    for (int it = 0; it < SPIN_MAX; it++) {
        if (ld_acquire(p) >= target) break;
        __nanosleep(400);
    }
}
__device__ __forceinline__ float4* oacc_at(int side, int row, int grp) {
    return row >= SROW0 ? sided<float4>(side, X_O + (row - SROW0) * 1024 + grp * 16) : &g_st.oacc[row][grp];
}
__device__ __forceinline__ float2* lsum_at(int side, int row) {
    return row >= SROW0 ? sided<float2>(side, X_L + (row - SROW0) * 128) : g_st.lsum[row];
}
__device__ __forceinline__ void wait_row(int side, int bh, float n) {
    const float2* l = lsum_at(side, bh);
#pragma unroll 1
    for (int it = 0; it < SPIN_MAX; it++) {
        const float c = ld_relaxed_f2(l).y;
        if (c >= n) break;
        if (c == 0.f) __nanosleep(600);
    }
}
__device__ __forceinline__ void wait_row_o(int side, int bh, float n) {
    wait_row(side, bh, n);
    if (bh >= RED0) return;
#pragma unroll 1
    for (int it = 0; it < SPIN_MAX; it++) {
        if (__uint_as_float(ld_relaxed_u32(&g_st.oacc[bh][0].w)) == UPB) break;
        __nanosleep(300);
    }
}
__device__ __forceinline__ void spin_ns(int ns) {
    const long long t0 = clock64();
    while (clock64() - t0 < (long long)ns * 2) {}
}
__device__ __forceinline__ uint32_t pack_bf16(float lo, float hi) {
    uint32_t r;
    asm("cvt.rn.bf16x2.f32 %0, %1, %2;" : "=r"(r) : "f"(hi), "f"(lo));
    return r;
}
__device__ __forceinline__ float bf16r(float v) { return __uint_as_float(pack_bf16(0.f, v)); }
__device__ __forceinline__ uint32_t pack_neg(float lo, float hi) {
    const uint32_t w = pack_bf16(-lo, -hi);
    return w ? w : 0x80008000u;
}
__device__ __forceinline__ float lo_f(uint32_t v) { return __uint_as_float(v << 16); }
__device__ __forceinline__ float hi_f(uint32_t v) { return __uint_as_float(v & 0xffff0000u); }
__device__ __forceinline__ float warp_sum(float v) {
#pragma unroll
    for (int o = 16; o; o >>= 1) v += __shfl_xor_sync(0xffffffffu, v, o);
    return v;
}
__device__ __forceinline__ void layernorm20(float (&v)[20]) {
    float s = 0.f;
#pragma unroll
    for (int i = 0; i < 20; i++) s += v[i];
    const float mean = warp_sum(s) * (1.0f / DM);
    float q = 0.f;
#pragma unroll
    for (int i = 0; i < 20; i++) { const float d = v[i] - mean; q += d * d; }
    const float var = bf16r(warp_sum(q) * (1.0f / DM));
    const float m = bf16r(mean);
    const float rden = 1.0f / bf16r(sqrtf(bf16r(var + 1e-5f)));
#pragma unroll
    for (int i = 0; i < 20; i++) v[i] = bf16r(bf16r(v[i] - m) * rden);
}

__device__ __forceinline__ float sel4(int j, float a, float b, float c, float d) {
    float lo, hi, r;
    asm("{\n.reg .pred p;\nsetp.ne.s32 p, %3, 0;\nselp.f32 %0, %2, %1, p;\n}" : "=f"(lo) : "f"(a), "f"(b), "r"(j & 1));
    asm("{\n.reg .pred p;\nsetp.ne.s32 p, %3, 0;\nselp.f32 %0, %2, %1, p;\n}" : "=f"(hi) : "f"(c), "f"(d), "r"(j & 1));
    asm("{\n.reg .pred p;\nsetp.ne.s32 p, %3, 0;\nselp.f32 %0, %2, %1, p;\n}" : "=f"(r) : "f"(lo), "f"(hi), "r"(j & 2));
    return r;
}
template <typename T> __device__ __forceinline__ void pin(T*& p) { asm volatile("" : "+l"(p)); }
__device__ __forceinline__ void pin(uint32_t& v) { asm volatile("" : "+r"(v)); }
__device__ __forceinline__ void pin(float& v) { asm volatile("" : "+f"(v)); }
__device__ __forceinline__ uint32_t after(uint32_t n, float v) {
    asm volatile("{\n.reg .pred p;\nsetp.eq.u32 p, %1, 0x7fc1a5a5;\n@p add.u32 %0, %0, 32;\n}" : "+r"(n) : "r"(__float_as_uint(v)));
    return n;
}
__device__ __forceinline__ float2 lds64f(uint32_t addr) {
    float2 v;
    asm volatile("ld.shared.v2.f32 {%0,%1}, [%2];" : "=f"(v.x), "=f"(v.y) : "r"(addr) : "memory");
    return v;
}
__device__ __forceinline__ float4 lds128f(uint32_t addr) {
    float4 v;
    asm volatile("ld.shared.v4.f32 {%0,%1,%2,%3}, [%4];" : "=f"(v.x), "=f"(v.y), "=f"(v.z), "=f"(v.w) : "r"(addr) : "memory");
    return v;
}
__device__ __forceinline__ void sts64f(uint32_t addr, float a, float b, bool pred) {
    asm volatile("{\n.reg .pred p;\nsetp.ne.u32 p, %3, 0;\n@p st.shared.v2.f32 [%0], {%1,%2};\n}" :: "r"(addr), "f"(a), "f"(b), "r"((uint32_t)pred) : "memory");
}
__device__ __forceinline__ void sts128f(uint32_t addr, float a, float b, float c, float d, bool pred) {
    asm volatile("{\n.reg .pred p;\nsetp.ne.u32 p, %5, 0;\n@p st.shared.v4.f32 [%0], {%1,%2,%3,%4};\n}"
                 :: "r"(addr), "f"(a), "f"(b), "f"(c), "f"(d), "r"((uint32_t)pred) : "memory");
}
__device__ __forceinline__ void lds128_if(uint4& v, uint32_t addr, bool pred) {
    asm volatile("{\n.reg .pred p;\nsetp.ne.u32 p, %5, 0;\n@p ld.shared.v4.u32 {%0,%1,%2,%3}, [%4];\n}"
                 : "+r"(v.x), "+r"(v.y), "+r"(v.z), "+r"(v.w) : "r"(addr), "r"((uint32_t)pred) : "memory");
}
__device__ __forceinline__ void sts32f(uint32_t addr, float v) { asm volatile("st.shared.f32 [%0], %1;" :: "r"(addr), "f"(v) : "memory"); }
template <int ID> __device__ __forceinline__ void fin_arrive() { asm volatile("bar.arrive %0, 288;" :: "n"(ID) : "memory"); }
template <int ID> __device__ __forceinline__ void fin_sync() { asm volatile("bar.sync %0, 288;" :: "n"(ID) : "memory"); }
template <int ID> __device__ __forceinline__ void fin_sync(uint32_t n) { asm volatile("bar.sync %0, %1;" :: "n"(ID), "r"(n) : "memory"); }
__device__ __forceinline__ float2 sum8(uint32_t addr) {
    float2 t[8];
#pragma unroll
    for (int w = 0; w < 8; w++) t[w] = lds64f(addr + w * 128);
    return make_float2(((t[0].x + t[1].x) + (t[2].x + t[3].x)) + ((t[4].x + t[5].x) + (t[6].x + t[7].x)),
                       ((t[0].y + t[1].y) + (t[2].y + t[3].y)) + ((t[4].y + t[5].y) + (t[6].y + t[7].y)));
}
__device__ __forceinline__ float4 sum4x4(uint32_t addr) {
    float4 t[4];
#pragma unroll
    for (int w = 0; w < 4; w++) t[w] = lds128f(addr + w * 256);
    return make_float4((t[0].x + t[1].x) + (t[2].x + t[3].x), (t[0].y + t[1].y) + (t[2].y + t[3].y),
                       (t[0].z + t[1].z) + (t[2].z + t[3].z), (t[0].w + t[1].w) + (t[2].w + t[3].w));
}
template <int NJ>
__device__ __forceinline__ void load_o(uint32_t (&ob)[3 * NJ][2], int bh, int J0, int j) {
    float4 v[NJ][4];
    float2 l;
#pragma unroll 1
    for (int it = 0; it < SPIN_MAX; it++) {
#pragma unroll
        for (int J = 0; J < NJ; J++) {
#pragma unroll
            for (int e = 0; e < 4; e++) v[J][e] = ld_relaxed_f4(&g_st.oacc[bh][(J0 + J) * 16 + e * 4 + j]);
        }
        l = ld_relaxed_f2(g_st.lsum[bh]);
        bool ok = l.y == UPB;
#pragma unroll
        for (int J = 0; J < NJ; J++) {
#pragma unroll
            for (int e = 0; e < 4; e++) ok &= v[J][e].w == UPB;
        }
        if (__all_sync(0xffffffffu, ok)) break;
    }
    const float rl = __fdividef(1.0f, l.x);
#pragma unroll
    for (int J = 0; J < NJ; J++) {
        ob[3 * J][0] = pack_bf16(v[J][0].x * rl, v[J][1].x * rl);     ob[3 * J][1] = pack_bf16(v[J][2].x * rl, v[J][3].x * rl);
        ob[3 * J + 1][0] = pack_bf16(v[J][0].y * rl, v[J][1].y * rl); ob[3 * J + 1][1] = pack_bf16(v[J][2].y * rl, v[J][3].y * rl);
        ob[3 * J + 2][0] = pack_bf16(v[J][0].z * rl, v[J][1].z * rl); ob[3 * J + 2][1] = pack_bf16(v[J][2].z * rl, v[J][3].z * rl);
    }
}
__device__ __forceinline__ void aux_sync() { asm volatile("bar.sync 1, 256;" ::: "memory"); }

__global__ void __launch_bounds__(NTHREADS, 1)
fused_decode_kernel(const __grid_constant__ Params p) {
    extern __shared__ __align__(1024) unsigned char smem[];
    const uint32_t sb = s2u(smem);
    const int tid = threadIdx.x, warp = __shfl_sync(0xffffffffu, tid >> 5, 0), lane = tid & 31;
    const int cta = blockIdx.x;
    constexpr int grid = NCTAS;
    const int g = lane >> 2, j = lane & 3;
    const bool is_l = cta >= NE_CTAS, is_f = cta < 96 && !(cta & 1), is_g = cta < 80 && (cta & 1);
    const int fidx = cta >> 1;

    TS(0);
    if (warp == 4 && cta < NQ_CTAS) {
        asm volatile("{\n.reg .pred p;\nelect.sync _|p, 0xffffffff;\n"
                     "@p mbarrier.init.shared::cta.b64 [%0], 1;\n"
                     "@p fence.mbarrier_init.release.cluster;\n"
                     "@p mbarrier.arrive.expect_tx.shared::cta.b64 _, [%0], 61440;\n}" :: "r"(sb + BAR_WQ) : "memory");
#pragma unroll
        for (int i = 0; i < 4; i++) request_box(sb + SM_WQ + i * 15360, &p.wq, cta * 48, i * 160, sb + BAR_WQ, EVICT_NORMAL);
    }
    if (tid == 160) {
#pragma unroll
        for (int w = 0; w < NWORK; w++) mbar_init(sb + BAR_KV + w * 8, 1);
        mbar_init(sb + BAR_W, 1);
#pragma unroll
        for (int w = 0; w < 8; w++) mbar_init(sb + BAR_G + w * 8, 1);
        asm volatile("fence.mbarrier_init.release.cluster;" ::: "memory");
    }
    __syncthreads();
    if (warp == NAUX + NWORK + 1) {
        uint32_t t = now_clk() + 2 * WO_AT_NS;
        if (lane == 0) mbar_expect_tx(sb + BAR_W, cta < NE_CTAS ? 61440 : 49152);
        const int col = cta < NE_CTAS ? (cta & 3) * 160 : (cta - NE_CTAS) * 32, row = cta < NE_CTAS ? (cta >> 2) * DH : 28 * DH;
#pragma unroll 1
        for (int r = 0; r < DH; r += WO_ROWS) {
            wait_clk(t);
#pragma unroll 1
            for (int i = 0; i < (cta < NE_CTAS ? 5 : 4); i++)
                request_box(sb + SM_A + i * 12288 + r * 64, &p.wo, cta < NE_CTAS ? col + i * 32 : col, (cta < NE_CTAS ? row : row + i * DH) + r, sb + BAR_W, EVICT_FIRST);
            t += 2 * WO_GAP_NS;
        }
        if (!is_f && !is_g) return;
        if (lane < 8) mbar_expect_tx(sb + BAR_G + lane * 8, is_f ? 10240 : 6144);
        asm volatile("bar.sync 9, 288;" ::: "memory");
        asm volatile("fence.proxy.async.shared::cta;" ::: "memory");
#pragma unroll 1
        for (int it = 0; it < SPIN_MAX; it++) {
            t = ld_relaxed_u32(g_st.tstart);
            if (__all_sync(0xffffffffu, t != 0)) break;
            __nanosleep(400);
        }
#pragma unroll 1
        for (int it = 0; it < SPIN_MAX; it++) if (__all_sync(0xffffffffu, t - now_ns() > 2 * TRIG_NS)) break;
        TSW(11);
        t = now_clk() + (is_f ? 0 : DOFF);
#pragma unroll 1
        for (int i = 0; i < 8; i++, t += is_f ? GCLK : DCLK) {
            wait_clk(t);
            if (is_f) {
                request_box(sb + SM_G + i * 5120, &p.wg, fidx * 32, i * 80, sb + BAR_G + i * 8, EVICT_NORMAL);
                request_box(sb + SM_G + 40960 + i * 5120, &p.wu, fidx * 32, i * 80, sb + BAR_G + i * 8, EVICT_NORMAL);
            } else {
                request_box(sb + SM_G + i * 6144, &p.wd, fidx * 16, i * 192, sb + BAR_G + i * 8, EVICT_NORMAL);
            }
        }
        return;
    }
    if (warp == NAUX + NWORK) {
        if (cta < NQ_CTAS) {
#pragma unroll
            for (int i = lane; i < STATE_V4; i += 32)
                if (cta * STATE_V4 + i < (int)(sizeof(State) / 16)) reinterpret_cast<uint4*>(&g_st)[cta * STATE_V4 + i] = make_uint4(0u, 0u, 0u, 0u);
            if (cta * 512 < X_END) {
                uint4* z = sided<uint4>(0, cta * 512 + lane * 16);
                *z = make_uint4(0u, 0u, 0u, 0u);
                *other_side(z) = make_uint4(0u, 0u, 0u, 0u);
            }
            __syncwarp();
            if (lane == 0) red_release(g_cnt_z);
        }
        if (lane == 0) { TS2(2); wait_count(g_cnt_z, NQ_CTAS); TS2(29); }
        __syncwarp();
        asm volatile("bar.arrive 2, %0;" :: "n"((NWORK + 1) * 32) : "memory");
        uint32_t rtt[2] = {0xffffffffu, 0xffffffffu};
        if (lane == 0) {
#pragma unroll 1
            for (int r = 0; r < 2 * NPROBE; r++) {
                int v = 0;
                uint32_t t1 = 0;
                unsigned* ctr = sided<unsigned>(r & 1, X_P + ((cta * 32 + (r >> 1) * 768) & 4095));
                pin(ctr);
                const uint32_t t0 = now_clk();
                draw(v, ctr, true);
                asm volatile("{\n.reg .pred q;\nsetp.ge.s32 q, %1, 0;\n@q mov.u32 %0, %%clock;\n}" : "+r"(t1) : "r"(v) : "memory");
                if (r & 1) rtt[1] = min(rtt[1], t1 - t0); else rtt[0] = min(rtt[0], t1 - t0);
            }
            sts32f(sb + SM_SIDE, __int_as_float(rtt[1] < rtt[0]));
        }
        const int side = __shfl_sync(0xffffffffu, rtt[1] < rtt[0], 0);
        fin_arrive<3>();
        int job = cta;
        auto sum_rows = [&](int row_end) {
#pragma unroll 1
            for (; job < 8 * min(row_end, RED0); job += NCTAS) {
                const int row = job >> 3, grp = (job & 7) * 8 + (lane & 7);
                if (lane == 0) wait_row(side, row, UPB);
                __syncwarp();
                const float4* src = &g_ring[row % RING][lane >> 3][grp];
                float sx = 0.f, sy = 0.f, sz = 0.f;
#pragma unroll 1
                for (int i = 0; i < 2; i++, src += 64 * 64) {
                    float4 v[16];
#pragma unroll 1
                    for (int it = 0; it < SPIN_MAX; it++) {
                        bool ok = true;
#pragma unroll
                        for (int k = 0; k < 16; k++) v[k] = ld_relaxed_b128(src + k * 4 * 64);
#pragma unroll
                        for (int k = 0; k < 16; k++) ok &= v[k].w == (float)(row + 1);
                        if (__all_sync(0xffffffffu, ok)) break;
                    }
#pragma unroll
                    for (int k = 0; k < 16; k++) { sx += v[k].x; sy += v[k].y; sz += v[k].z; }
                }
#pragma unroll
                for (int o = 8; o < 32; o <<= 1) {
                    sx += __shfl_xor_sync(0xffffffffu, sx, o); sy += __shfl_xor_sync(0xffffffffu, sy, o); sz += __shfl_xor_sync(0xffffffffu, sz, o);
                }
                if (lane < 8) st_relaxed_b128(&g_st.oacc[row][grp], sx, sy, sz, UPB);
            }
        };
        {
            uint32_t wr[10];
            float wsum = 0.f;
#pragma unroll
            for (int i = 0; i < 10; i++) {
                const int w = 4 * lane + 128 * (i >> 2) + (i & 3) - (i >= 8 ? 2 * lane : 0);
                wr[i] = *reinterpret_cast<const uint32_t*>(p.wr + (w >> 4) * 32 + (w & 3) * 8 + ((w >> 1) & 6));
                wsum += lo_f(wr[i]) + hi_f(wr[i]);
            }
            wsum = warp_sum(wsum);
            const int lb = lane >> 3, lc = lane & 7;
            uint32_t ypart = sb + SM_RED2 + (lb >> 1) * 160 + lc * 16 + (lb & 1) * 8;
            __nv_bfloat16* out = p.out + lb * DM + fidx * 16 + lc;
            float nmean_l = 0.f, rden_l = 0.f, sig_l = 0.f;
#pragma unroll 1
            for (int b = 0; b < NB; b++) {
                const uint32_t hx = X_H + b * (DM * 2), hrow = sb + SM_X + b * HPITCH;
                const uint4 *src0 = sided<uint4>(side, hx + 16 * lane), *src1 = sided<uint4>(side, hx + 512 + 16 * lane);
                const uint2* src2 = sided<uint2>(side, hx + 1024 + 8 * lane);
                sum_rows((b + 1) * NH);
                if (!is_l && !is_f && !is_g) continue;
                pin(src0); pin(src1); pin(src2); pin(ypart); pin(out);
                if (lane == 0) wait_row(side, b * NH + (is_l ? 28 : NH - 1), is_l ? 1 : FWAIT);
                __syncwarp();
                if (is_l) {
                    const int col = (cta - NE_CTAS) * 32 + 2 * (lane & 15);
                    uint32_t lpart = sb + SM_RED + (lane & 15) * 8;
                    const uint32_t xv = *reinterpret_cast<const uint32_t*>(p.x + b * DM + col);
                    uint32_t* hdst = sided<uint32_t>(lane >> 4, hx + 4 * ((col >> 5) * 16 + (col & 6) * 2 + ((col >> 3) & 3)));
                    float4 early;
#pragma unroll 1
                    for (int it = 0; it < SPIN_MAX; it++) {
                        early = ld_relaxed_f4(&g_st.attn[b][col]);
                        if (__all_sync(0xffffffffu, early.y == NE_CTAS / 4 && early.w == NE_CTAS / 4)) break;
                    }
                    if (lane == 0) TS2(23);
                    float x0 = lo_f(xv), x1 = hi_f(xv);
                    pin(hdst); pin(lpart); pin(x0); pin(x1);
                    fin_sync<4>();
                    CK(2, lds32(sb + SM_RED));
                    const float2 late = sum8(lpart);
                    st_relaxed(hdst, pack_neg(x0 + bf16r(early.x + late.x), x1 + bf16r(early.z + late.y)));
                    CK(3, 0);
                    if (lane == 0) TS2(15);
                    fin_sync<5>();
                    continue;
                }
                uint4 h0, h1;
                uint2 h2;
                float mm[5][4];
#pragma unroll 1
                for (int it = 0; it < SPIN_MAX; it++) {
                    h0 = ld_relaxed_v4(src0);
                    h1 = ld_relaxed_v4(src1);
                    h2 = ld_relaxed_v2(src2);
                    asm volatile("st.shared.v4.u32 [%0], {%1,%2,%3,%4};" :: "r"(hrow + lane * 16), "r"(h0.x), "r"(h0.y), "r"(h0.z), "r"(h0.w) : "memory");
                    asm volatile("st.shared.v4.u32 [%0], {%1,%2,%3,%4};" :: "r"(hrow + 512 + lane * 16), "r"(h1.x), "r"(h1.y), "r"(h1.z), "r"(h1.w) : "memory");
                    asm volatile("st.shared.v2.u32 [%0], {%1,%2};" :: "r"(hrow + 1024 + lane * 8), "r"(h2.x), "r"(h2.y) : "memory");
                    const uint32_t w[10] = {h0.x, h0.y, h0.z, h0.w, h1.x, h1.y, h1.z, h1.w, h2.x, h2.y};
#pragma unroll
                    for (int i = 0; i < 5; i++) {
                        const uint32_t a[4] = {w[2 * i], 0x3f803f80u, w[2 * i + 1], 0x3f803f80u};
                        mm[i][0] = mm[i][1] = mm[i][2] = mm[i][3] = 0.f;
                        mma16816(mm[i], a, w[2 * i], w[2 * i + 1]);
                    }
                    const uint32_t lo = min(min(min(h0.x, h0.y), min(h0.z, h0.w)), min(min(min(h1.x, h1.y), min(h1.z, h1.w)), min(h2.x, h2.y)));
                    if (GDLY && !is_f) sts32f(sb + SM_MOM, __uint_as_float(now_clk()));
                    const bool ok = __all_sync(0xffffffffu, lo != 0 || it == SPIN_MAX - 1);
                    asm volatile("{\n.reg .pred p;\nsetp.ne.u32 p, %0, 0;\n@p bar.arrive 7, 288;\n}" :: "r"((uint32_t)ok) : "memory");
                    if (ok) break;
                    if (!is_f) __nanosleep(HNAP);
                }
                CK(4, h0.x);
                if (lane == 0 && is_f) TS2(12);
                const uint32_t hw[10] = {h0.x, h0.y, h0.z, h0.w, h1.x, h1.y, h1.z, h1.w, h2.x, h2.y};
                float m1 = ((mm[0][2] + mm[1][2]) + (mm[2][2] + mm[3][2])) + ((mm[0][3] + mm[1][3]) + (mm[2][3] + mm[3][3])) + (mm[4][2] + mm[4][3]);
                float m2 = (g & 1) ? ((mm[0][1] + mm[1][1]) + (mm[2][1] + mm[3][1])) + mm[4][1] : ((mm[0][0] + mm[1][0]) + (mm[2][0] + mm[3][0])) + mm[4][0];
                m2 += __shfl_xor_sync(0xffffffffu, m2, 4);
                m1 = (m1 + __shfl_xor_sync(0xffffffffu, m1, 1)) + (__shfl_xor_sync(0xffffffffu, m1, 2) + __shfl_xor_sync(0xffffffffu, m1, 3));
                m2 = (__shfl_sync(0xffffffffu, m2, 0) + __shfl_sync(0xffffffffu, m2, 9)) + (__shfl_sync(0xffffffffu, m2, 18) + __shfl_sync(0xffffffffu, m2, 27));
                m1 *= 1.0f / DM;
                const float nmean = bf16r(m1);
                const float var = bf16r(fmaxf(fmaf(-m1, m1, m2 * (1.0f / DM)), 0.f));
                const float den = bf16r(sqrt_approx(bf16r(var + 1e-5f)));
                if (is_f) {
                    sts64f(sb + SM_MOM + b * 8, nmean, den, lane == 0);
                    CK(5, 0);
                    fin_arrive<4>();
                } else {
                    const float rden = rcp_approx(den);
                    if (lb == b) { nmean_l = nmean; rden_l = rden; }
                    __syncwarp();
                    const float2 hw2 = lds64f(sb + SM_X + lb * HPITCH + ((fidx >> 1) * 16 + (lc & 6) * 2 + (fidx & 1) * 2) * 4);
                    const float nh0 = (lc & 1) ? hi_f(__float_as_uint(hw2.x)) : lo_f(__float_as_uint(hw2.x));
                    const float nh1 = (lc & 1) ? hi_f(__float_as_uint(hw2.y)) : lo_f(__float_as_uint(hw2.y));
                    float rr = 0.f;
#pragma unroll
                    for (int i = 0; i < 10; i++) rr = fmaf(lo_f(hw[i]), lo_f(wr[i]), fmaf(hi_f(hw[i]), hi_f(wr[i]), rr));
                    const float sig = bf16r(sigmoid_approx(bf16r((nmean * wsum - warp_sum(rr)) * rden)));
                    if (lb == b) sig_l = sig;
                    const float ln0 = bf16r(bf16r(nmean_l - nh0) * rden_l), ln1 = bf16r(bf16r(nmean_l - nh1) * rden_l);
                    fin_sync<6>(after(after(after(288, sig_l), ln0), ln1));
                    CK(10, lds32(ypart));
                    float2 t[16];
#pragma unroll
                    for (int i = 0; i < 16; i++) t[i] = lds64f(ypart + i * YPITCH);
#pragma unroll
                    for (int o = 1; o < 16; o <<= 1) {
#pragma unroll
                        for (int i = 0; i < 16; i += 2 * o) { t[i].x += t[i + o].x; t[i].y += t[i + o].y; }
                    }
                    const uint32_t ov = pack_bf16(bf16r(ln0 + bf16r(bf16r(-t[0].x) * sig_l)) - nh0, bf16r(ln1 + bf16r(bf16r(-t[0].y) * sig_l)) - nh1);
                    asm volatile("{\n.reg .pred p;\n.reg .b16 lo, hi;\nsetp.eq.u32 p, %2, 3;\nmov.b32 {lo, hi}, %1;\n"
                                 "@p st.global.u16 [%0], lo;\n@p st.global.u16 [%0 + 16], hi;\n}" :: "l"(out), "r"(ov), "r"(b) : "memory");
                    CK(11, 0);
                    if (lane == 0) TS2(13);
                }
                if (b < NB - 1) fin_sync<5>();
            }
            if (cta == 0 && lane == 0) { g_work[0] = 0; g_cnt_z[0] = 0; }
        }
        return;
    }
    if (warp >= NAUX) {
        const int wk = warp - NAUX;
        const uint32_t bar = sb + BAR_KV + wk * 8;
        const uint32_t buf = sb + SM_KV + wk * TILE_BYTES;
        uint64_t pol;
        asm volatile("createpolicy.fractional.L2::evict_first.b64 %0, 1.0;" : "=l"(pol));
        const int nstatic = NWORK * grid;
        constexpr int POOL0 = NUNITS - NPOOL;
        int uk = wk * grid + cta;
        if (lane == 0) {
            spin_ns(K0_DELAY_NS + wk * K0_STEP_NS);
            mbar_expect_tx(bar, TILE_BYTES);
            tma_tile(buf, &p.k, tile_of(uk), bar, pol);
        }
        __syncwarp();
        uint32_t koff[3], voff[3];
        {
            const int r = lane & 7, hf = (lane >> 3) & 1;
            const int kkey = hf ? 8 + (r ^ 1) : r;
            const int vh = lane >> 4;
            const int vkey = ((r & 1) ? 8 : 0) + (vh ? (r ^ 1) : r);
#pragma unroll
            for (int b = 0; b < 3; b++) {
                const int rk = 3 * kkey + b, rv = 3 * vkey + b;
                koff[b] = buf + rk * 128 + (((lane >> 4) ^ (rk & 7)) << 4);
                voff[b] = buf + rv * 128 + ((hf ^ (rv & 7)) << 4);
            }
        }
        uint32_t phase = 0;
        uint4 qf[6];
        auto load_q = [&](int u) {
            const uint32_t* q = &g_early[row_of(u)].q[j * 4];
#pragma unroll
            for (int i = 0; i < 6; i++) qf[i] = ld_relaxed_v4(q + i * 16);
        };
        load_q(uk);
        int uq[LAG];
        uint32_t sq[LAG];
#pragma unroll
        for (int i = 0; i < LAG; i++) { uq[i] = -1; sq[i] = 0; }
        uint4 mv = make_uint4(0u, 0u, 0u, 0u);
        uint32_t svp = 0;
        float freed = UPB;
        while (true) {
            const int uv = uq[0];
            uint32_t sv = sq[0];
#pragma unroll
            for (int i = 0; i + 1 < LAG; i++) { uq[i] = uq[i + 1]; sq[i] = sq[i + 1]; }
            uq[LAG - 1] = uk;
            if (uk < NUNITS) {
                PH(7);
#pragma unroll 1
                for (int it = 0; it < SPIN_MAX; it++) {
                    uint32_t lo = 0xffffffffu;
#pragma unroll
                    for (int i = 0; i < 6; i++) lo = min(min(lo, min(qf[i].x, qf[i].y)), min(qf[i].z, qf[i].w));
                    if (__all_sync(0xffffffffu, lo != 0)) break;
                    __nanosleep(QNAP);
                    load_q(uk);
                }
                mbar_wait(bar, phase); phase ^= 1;
                PH(0); ARR();
                TSI(0, 16); TSI(1, 18);
                float acc[2][4][4] = {};
#pragma unroll
                for (int ks = 0; ks < 12; ks++) {
                    const uint4 qq = qf[ks >> 1];
                    const uint32_t b0 = (ks & 1) ? qq.z : qq.x, b1 = (ks & 1) ? qq.w : qq.y;
#pragma unroll
                    for (int mt = 0; mt < 4; mt++) {
                        uint32_t a[4];
                        ldsm4(a, (koff[ks >> 2] ^ ((ks & 3) << 5)) + mt * 6144);
                        mma16816(acc[ks & 1][mt], a, b0, b1);
                    }
                }
                PH(1);
                TSI(0, 17); TSI(1, 19);
                if (uv < NUNITS) request_tile(buf, uv >= 0 ? &p.v : &p.k, uv >= 0 ? uv : uk + nstatic, bar, pol);
                const float sa = sel4(j, acc[0][0][0], acc[0][1][0], acc[0][2][0], acc[0][3][0]) + sel4(j, acc[1][0][0], acc[1][1][0], acc[1][2][0], acc[1][3][0]);
                const float sc = sel4(j, acc[0][0][2], acc[0][1][2], acc[0][2][2], acc[0][3][2]) + sel4(j, acc[1][0][2], acc[1][1][2], acc[1][2][2], acc[1][3][2]);
                const uint32_t raw = pack_bf16(sa, sc);
                const float scale = -0.07216878364870322f;
                const uint32_t sk = pack_bf16(lo_f(raw) * scale, hi_f(raw) * scale);
                sq[LAG - 1] = sk;
                if (uk >= POOL0) st_relaxed(&g_st.score[uk - POOL0][lane], sk ? sk : 0x80008000u);
                int a = (int)(sk << 16), b = (int)(sk & 0xffff0000u);
                a ^= (a >> 31) & 0x7fff0000; b ^= (b >> 31) & 0x7fff0000;
                const int mx = __reduce_max_sync(0xffffffffu, max(a, b));
                if (lane == 0) st_relaxed(&g_early[row_of(uk)].umax[pos_of(uk)], (uint32_t)mx | 1u);
            }
            if (uv < 0) {
                uk += nstatic;
                load_q(uk);
                continue;
            }
            if (uv >= NUNITS) break;
            const int bh = row_of(uv);
#pragma unroll 1
            for (int it = 0; it < SPIN_MAX; it++) {
                if (__all_sync(0xffffffffu, (mv.x & mv.y & mv.z & mv.w & 1u) && (uv < POOL0 || svp != 0) && freed == UPB)) break;
                mv = ld_relaxed_v4(&g_early[bh].umax[lane * 4]);
                if (bh >= RING && bh < RED0) freed = __uint_as_float(ld_relaxed_u32(&g_st.oacc[bh - RING][(lane & 7) * 8].w));
                if (uv >= POOL0) svp = ld_relaxed_u32(&g_st.score[uv - POOL0][lane]);
            }
            if (uv >= POOL0) sv = svp;
            PH(2);
            int un = NUNITS, vn = 0;
            draw(un, g_work, uk < NUNITS && lane == 0);
            int mx = __reduce_max_sync(0xffffffffu, max(max((int)mv.x, (int)mv.y), max((int)mv.z, (int)mv.w))) & 0xffff0000;
            mx ^= (mx >> 31) & 0x7fff0000;
            const float m = __int_as_float(mx);
            const float l2e = 1.4426950408889634f;
            const uint32_t pp = pack_bf16(exp2f((lo_f(sv) - m) * l2e), exp2f((hi_f(sv) - m) * l2e));
            uint32_t pb[8];
#pragma unroll
            for (int t = 0; t < 4; t++) {
                pb[2 * t] = __shfl_sync(0xffffffffu, pp, 8 * j + t);
                pb[2 * t + 1] = __shfl_sync(0xffffffffu, pp, 8 * j + 4 + t);
            }
            float lacc[4] = {};
            const uint32_t ones[4] = {0x3f803f80u, 0x3f803f80u, 0x3f803f80u, 0x3f803f80u};
#pragma unroll
            for (int t = 0; t < 4; t++) mma16816(lacc, ones, pb[2 * t], pb[2 * t + 1]);
            if (uv < nstatic) {
                asm volatile("bar.sync 2, %0;" :: "n"((NWORK + 1) * 32) : "memory");
                TSW(3);
            }
            const int grp = 16 * j + 4 * (g & 1) + (g >> 1);
            const int acc_row = bh >= NBH - 4 ? bh + 4 * (pos_of(uv) % OREP) : bh;
            float4* dst = bh < RED0 ? &g_ring[bh % RING][pos_of(uv)][grp] : oacc_at(FARFIRST ? lds32(sb + SM_SIDE) ^ 1 : 0, acc_row, grp);
            float4* dst2 = other_side(dst);
            float2* ldst = lsum_at(lane & 1, acc_row);
            if (bh >= SROW0 && lane < 2) red_f2(&ldst->x, lacc[0], 1.f);
            float tag = bh < RED0 ? (float)(bh + 1) : 1.f;
            un = __shfl_sync(0xffffffffu, un, 0) + (LAG + 1) * nstatic;
            uint32_t pooled = uq[0] >= POOL0 && lane == 0;
            pin(dst); pin(dst2); pin(ldst); pin(tag); pin(voff[0]); pin(voff[1]); pin(voff[2]); pin(pooled);
            PH(3);
            LT(1);
            mbar_wait(bar, phase); phase ^= 1;
            PH(4); ARR();
            LT(2);
            draw(vn, g_st.pool, pooled);
            float acc[12][4] = {};
#pragma unroll
            for (int t = 0; t < 4; t++) {
#pragma unroll
                for (int mt = 0; mt < 12; mt++) {
                    uint32_t a[4];
                    ldsm4t(a, (voff[mt >> 2] ^ ((mt & 3) << 5)) + t * 6144);
                    mma16816(acc[mt], a, pb[2 * t], pb[2 * t + 1]);
                }
            }
            PH(5);
            if (lane == 0) PROG(un);
            if (un < NUNITS) request_tile(buf, &p.k, un, bar, pol);
            float o[6];
#pragma unroll
            for (int e = 0; e < 6; e++) {
                const int q = e % 3, c = (e / 3) * 2;
                o[e] = sel4(j, acc[q][c], acc[3 + q][c], acc[6 + q][c], acc[9 + q][c]);
            }
            if (bh >= SROW0) {
                red_f4(&dst->x, o[0], o[1], o[2], tag);
                red_f4(&dst[16].x, o[3], o[4], o[5], tag);
                red_f4(&dst2->x, o[0], o[1], o[2], tag);
                red_f4(&dst2[16].x, o[3], o[4], o[5], tag);
            } else {
                if (bh >= RED0) {
                    red_f4(&dst->x, o[0], o[1], o[2], tag);
                    red_f4(&dst[8].x, o[3], o[4], o[5], tag);
                } else {
                    st_relaxed_b128(dst, o[0], o[1], o[2], tag);
                    st_relaxed_b128(dst + 8, o[3], o[4], o[5], tag);
                }
                if (lane == 0) red_f2(&ldst->x, lacc[0], 1.f);
            }
            if (uq[0] >= POOL0) {
                vn = __shfl_sync(0xffffffffu, vn, 0);
                uq[0] = POOL0 + vn;
                if (vn == VTRIG && lane == 0) st_relaxed(g_st.tstart, (now_ns() + TRIG_NS) | 1u);
            }
            if (un < NUNITS) load_q(un);
            PH(6);
            if (uq[0] >= NUNITS && un >= NUNITS) break;
            uk = un;
            if (uq[0] < NUNITS) {
                const int nb = row_of(uq[0]);
                mv = ld_relaxed_v4(&g_early[nb].umax[lane * 4]);
                freed = nb >= RING && nb < RED0 ? __uint_as_float(ld_relaxed_u32(&g_st.oacc[nb - RING][(lane & 7) * 8].w)) : UPB;
                if (uq[0] >= POOL0) svp = ld_relaxed_u32(&g_st.score[uq[0] - POOL0][lane]);
                if (un >= NUNITS) {
                    request_tile(buf, &p.v, uq[0], bar, pol);
                    LT(0);
                }
            }
        }
        if (WBAR && is_f) asm volatile("bar.arrive 10, %0;" :: "n"((NAUX + NWORK) * 32) : "memory");
        return;
    }

    __nv_bfloat16* xs = reinterpret_cast<__nv_bfloat16*>(smem + SM_X);
    float* red = reinterpret_cast<float*>(smem + SM_RED);
    const int frow = (lane & 7) + ((lane >> 4) << 3), fcol = (lane >> 3) & 1;
    if (cta < NQ_CTAS) {
        uint2 xr[5];
        if (warp < NB) {
#pragma unroll
            for (int i = 0; i < 5; i++) xr[i] = *reinterpret_cast<const uint2*>(p.x + warp * DM + i * 128 + lane * 4);
        }
        TS(26);
        if (warp < NB) {
            float v[20];
#pragma unroll
            for (int i = 0; i < 5; i++) {
                v[4 * i] = lo_f(xr[i].x); v[4 * i + 1] = hi_f(xr[i].x); v[4 * i + 2] = lo_f(xr[i].y); v[4 * i + 3] = hi_f(xr[i].y);
            }
            layernorm20(v);
#pragma unroll
            for (int i = 0; i < 5; i++)
                *reinterpret_cast<uint2*>(xs + warp * XPITCH + i * 128 + lane * 4) =
                    make_uint2(pack_bf16(v[4 * i], v[4 * i + 1]), pack_bf16(v[4 * i + 2], v[4 * i + 3]));
        }
        TS(27);
        aux_sync();
        mbar_wait(sb + BAR_WQ, 0);
        TS(1);
        const uint32_t xfrag = sb + SM_X + ((g & 3) * XPITCH + 2 * j) * 2;
        float acc[3][4] = {};
#pragma unroll
        for (int s = 0; s < 5; s++) {
            const int ks = warp * 5 + s;
            const uint32_t b0 = lds32(xfrag + ks * 32), b1 = lds32(xfrag + ks * 32 + 16);
            const int row = ks * 16 + frow;
#pragma unroll
            for (int mt = 0; mt < 3; mt++) {
                uint32_t a[4];
                ldsm4t(a, sb + SM_WQ + (row * 6 + 2 * mt + fcol) * 16);
                mma16816(acc[mt], a, b0, b1);
            }
        }
        if (j < 2) {
#pragma unroll
            for (int mt = 0; mt < 3; mt++) {
                *reinterpret_cast<float2*>(red + (warp * 48 + mt * 16 + g) * 4 + 2 * j) = make_float2(acc[mt][0], acc[mt][1]);
                *reinterpret_cast<float2*>(red + (warp * 48 + mt * 16 + 8 + g) * 4 + 2 * j) = make_float2(acc[mt][2], acc[mt][3]);
            }
        }
        aux_sync();
        if (tid < 96) {
            const int b = tid & 3, cp = tid >> 2;
            float s0 = 0.f, s1 = 0.f;
#pragma unroll
            for (int w = 0; w < 8; w++) { s0 += red[(w * 48 + 2 * cp) * 4 + b]; s1 += red[(w * 48 + 2 * cp + 1) * 4 + b]; }
            const int h = cta >> 2, d = (cta & 3) * 48 + 2 * cp;
            const int ch = d >> 3, jj = (d & 7) >> 1;
            st_relaxed(&g_early[b * NH + h].q[(ch >> 2) * 16 + jj * 4 + (ch & 3)], pack_neg(s0, s1));
        }
        TS(28);
    }
    if (tid < 160) *reinterpret_cast<uint2*>(smem + SM_X + 4 * HPITCH + tid * 8) = make_uint2(0x3f803f80u, 0x3f803f80u);
    fin_sync<3>();
    const int side = lds32(sb + SM_SIDE);
    mbar_wait(sb + BAR_W, 0);
    TS(7);
    uint32_t part = sb + SM_RED + (warp * 32 + 8 * j + g) * 4;

#pragma unroll 1
    for (int b = 0; b < NB; b++) {
        if (b == NB - 1 && (is_f || is_g)) asm volatile("bar.arrive 9, 288;" ::: "memory");
        if (is_l) {
            uint32_t a[6][2][4];
#pragma unroll
            for (int s = 0; s < 6; s++) {
                const int row = (warp * 6 + s) * 16 + frow;
#pragma unroll
                for (int mt = 0; mt < 2; mt++) ldsm4t(a[s][mt], sb + SM_A + (row * 4 + ((2 * mt + fcol) ^ ((row >> 1) & 3))) * 16);
            }
            const int bh = b * NH + 28 + (warp >> 1);
            const float4* osrc[OREP];
            const float2* lsrc[OREP];
#pragma unroll
            for (int c = 0; c < OREP; c++) {
                const int row = b == NB - 1 ? bh + 4 * c : bh;
                osrc[c] = oacc_at(side, row, (warp & 1) * 32 + lane);
                lsrc[c] = lsum_at(side, row);
                pin(osrc[c]); pin(lsrc[c]);
            }
            if (lane == 0) wait_row_o(side, bh, 1);
            __syncwarp();
            float2 lv;
#pragma unroll 1
            for (int it = 0; it < SPIN_MAX; it++) {
                lv = ld_relaxed_f2(lsrc[0]);
#pragma unroll
                for (int c = 1; c < OREP; c++) {
                    const float2 lc = ld_relaxed_f2(lsrc[c]);
                    if (b == NB - 1) { lv.x += lc.x; lv.y += lc.y; }
                }
                if (__all_sync(0xffffffffu, lv.y == UPB)) break;
            }
            if (warp == 7) TSW(25);
            float rl = rcp_approx(lv.x);
            float4 ov;
            pin(part); pin(rl);
            if (OPRE && lane == 0) {
#pragma unroll 1
                for (int it = 0; it < SPIN_MAX; it++) {
                    if (__uint_as_float(ld_relaxed_u32(&osrc[0]->w)) >= UPB * OPRE / (16 * OREP)) break;
                    if (ONAP) __nanosleep(ONAP);
                }
            }
            __syncwarp();
#pragma unroll 1
            for (int it = 0;; it++) {
                float4 oc[OREP];
#pragma unroll
                for (int c = 0; c < OREP; c++) oc[c] = ld_relaxed_f4(osrc[c]);
                ov = oc[0];
                if (b == NB - 1) {
#pragma unroll
                    for (int c = 1; c < OREP; c++) { ov.x += oc[c].x; ov.y += oc[c].y; ov.z += oc[c].z; ov.w += oc[c].w; }
                }
                if (__all_sync(0xffffffffu, ov.w == UPB || it == SPIN_MAX)) break;
            }
            CK(0, __float_as_uint(ov.x));
            const float px = __shfl_xor_sync(0xffffffffu, ov.x, 4), py = __shfl_xor_sync(0xffffffffu, ov.y, 4),
                        pz = __shfl_xor_sync(0xffffffffu, ov.z, 4);
            const uint32_t w[3] = {pack_bf16(ov.x * rl, px * rl), pack_bf16(ov.y * rl, py * rl), pack_bf16(ov.z * rl, pz * rl)};
            float acc[2][2][4] = {};
#pragma unroll
            for (int s = 0; s < 6; s++) {
                const uint32_t b0 = __shfl_sync(0xffffffffu, w[s % 3], (s / 3) * 16 + j);
                const uint32_t b1 = __shfl_sync(0xffffffffu, w[s % 3], (s / 3) * 16 + 8 + j);
#pragma unroll
                for (int mt = 0; mt < 2; mt++) mma16816(acc[mt][s & 1], a[s][mt], b0, b1);
            }
            sts32f(part, sel4(j, acc[0][0][0] + acc[0][1][0], acc[0][0][2] + acc[0][1][2], acc[1][0][0] + acc[1][1][0], acc[1][0][2] + acc[1][1][2]));
            CK(1, 0);
            fin_arrive<4>();
            if (warp == 7) TSW(30);
            if (warp == 5) TSW(31);
            if (cta == NE_CTAS && lane < 28) reinterpret_cast<uint4*>(&g_early[bh])[(warp & 1) * 28 + lane] = make_uint4(0u, 0u, 0u, 0u);
            fin_sync<5>();
            continue;
        }
        {
            const int bh = b * NH + (cta >> 2);
            if (tid == 0) wait_row_o(side, bh, UPB);
            aux_sync();
            if (warp < 5) {
                uint32_t ob[12][2];
                load_o<4>(ob, bh, 0, j);
                float acc[2][2][4] = {};
#pragma unroll
                for (int ks = 0; ks < 12; ks++) {
                    const int row = ks * 16 + frow;
#pragma unroll
                    for (int mt = 0; mt < 2; mt++) {
                        uint32_t a[4];
                        ldsm4t(a, sb + SM_A + warp * 12288 + (row * 4 + ((2 * mt + fcol) ^ ((row >> 1) & 3))) * 16);
                        mma16816(acc[mt][ks & 1], a, ob[ks][0], ob[ks][1]);
                    }
                }
                red_f2(&g_st.attn[b][(cta & 3) * 160 + warp * 32 + 8 * j + g].x,
                       sel4(j, acc[0][0][0] + acc[0][1][0], acc[0][0][2] + acc[0][1][2], acc[1][0][0] + acc[1][1][0], acc[1][0][2] + acc[1][1][2]), 1.f);
                TS(8);
            } else if (warp > 5 && (cta & 3) == 0 && tid - 192 < 56) {
                reinterpret_cast<uint4*>(&g_early[bh])[tid - 192] = make_uint4(0u, 0u, 0u, 0u);
            }
        }
        if (is_f) {
            const int kq = warp >> 1, tp = warp & 1;
            uint32_t hfrag = sb + SM_X + min(g, 4) * HPITCH + (kq * 80 + 4 * j) * 4;
            uint4 hv[5] = {};
#pragma unroll
            for (int s = 0; s < 5; s++) lds128_if(hv[s], hfrag + s * 64, true);
            if (WBAR && b == NB - 1) asm volatile("bar.sync 10, %0;" :: "n"((NAUX + NWORK) * 32) : "memory");
            uint32_t ga[10][2][4];
#pragma unroll
            for (int s = 0; s < 10; s++) {
                if (s % 5 == 0 && b == NB - 1) mbar_wait(sb + BAR_G + (kq * 2 + s / 5) * 8, 0);
                const int row = (kq * 10 + s) * 16 + frow;
#pragma unroll
                for (int t = 0; t < 2; t++) ldsm4t(ga[s][t], sb + SM_G + fcol * 40960 + (row * 4 + ((2 * tp + t) ^ ((row >> 1) & 3))) * 16);
            }
            if (warp == NAUX - 1) TSW(9);
            uint32_t fpart = sb + SM_RED + 2 * j * FPITCH + warp * 128 + g * 16;
            uint32_t dsum = sb + SM_RED + (lane >> 3) * FPITCH + tp * 128 + (lane & 7) * 16, csum = sb + SM_RED + 4 * FPITCH + tp * 128 + (lane & 7) * 16;
            uint32_t mom = sb + SM_MOM + (lane >> 3) * 8;
            uint32_t* dst = sided<uint32_t>(side ^ 1, X_A + (2 * fidx + tp) * 128 + (lane ^ 2 * tp) * 4);
            pin(fpart); pin(hfrag); pin(dsum); pin(csum); pin(mom); pin(dst);
            fin_sync<7>();
#pragma unroll
            for (int s = 0; s < 5; s++) lds128_if(hv[s], hfrag + s * 64, g == b);
            float acc[2][2][4] = {};
#pragma unroll
            for (int s = 0; s < 5; s++) {
#pragma unroll
                for (int t = 0; t < 2; t++) mma16816(acc[t][0], ga[2 * s][t], hv[s].x, hv[s].y);
#pragma unroll
                for (int t = 0; t < 2; t++) mma16816(acc[t][1], ga[2 * s + 1][t], hv[s].z, hv[s].w);
            }
#pragma unroll
            for (int e = 0; e < 2; e++)
                sts128f(fpart + e * FPITCH, acc[0][0][e] + acc[0][1][e], acc[0][0][2 + e] + acc[0][1][2 + e],
                        acc[1][0][e] + acc[1][1][e], acc[1][0][2 + e] + acc[1][1][2 + e], 2 * j + e < 5);
            CK(5, 0);
            if (warp < 2) {
                fin_sync<4>();
                CK(6, lds32(dsum));
                float2 m = lds64f(mom);
                m.y = rcp_approx(m.y);
                const float4 d = sum4x4(dsum), cs = sum4x4(csum);
                const float g0 = bf16r(fmaf(m.x, cs.x, -d.x) * m.y), g1 = bf16r(fmaf(m.x, cs.z, -d.z) * m.y);
                const float u0 = bf16r(fmaf(m.x, cs.y, -d.y) * m.y), u1 = bf16r(fmaf(m.x, cs.w, -d.w) * m.y);
                const uint32_t av = pack_neg(bf16r(g0 * sigmoid_approx(g0)) * u0, bf16r(g1 * sigmoid_approx(g1)) * u1);
                asm volatile("{\n.reg .pred p;\nsetp.eq.u32 p, %3, 3;\n@p st.relaxed.gpu.global.u32 [%0], %2;\n@p st.relaxed.gpu.global.u32 [%1], %2;\n}"
                             :: "l"(dst), "l"(other_side(dst)), "r"(av), "r"(b) : "memory");
                CK(7, 0);
                TS(14);
            } else {
                fin_arrive<4>();
            }
        } else if (is_g) {
            if (GEARLY) fin_sync<7>();
            if (b == NB - 1) {
                mbar_wait(sb + BAR_G + warp * 8, 0);
                if (warp == NAUX - 1) TSW(10);
            }
            uint32_t wb[3][2][2][4];
#pragma unroll
            for (int s = 0; s < 12; s++) {
                const int odd = (lane >> 2) & 1, c = ((lane & 2) * 2 + (s & 1) * 2 + (lane >> 4)) ^ (2 * odd);
                const int row = (warp * 12 + (s >> 1) * 2 + odd) * 16 + (lane & 1) * 8 + c;
                ldsm4t(wb[s >> 2][(s >> 1) & 1][s & 1], sb + SM_G + (row * 2 + (fcol ^ ((row >> 2) & 1))) * 16);
            }
            const uint4* asrc[3];
#pragma unroll
            for (int q = 0; q < 3; q++) {
                asrc[q] = sided<uint4>(side, X_A + (warp * 12 + 4 * q + 2 * (g >> 2) + (j >> 1)) * 128 + (g & 3) * 32 + (j & 1) * 16);
                pin(asrc[q]);
            }
            uint32_t ypart = sb + SM_RED2 + (warp * 2 + (j >> 1)) * YPITCH + (j & 1) * 160 + g * 16;
            pin(ypart);
            if (!GEARLY) fin_sync<7>();
            if (GDLY) wait_clk(lds32(sb + SM_MOM) + GDLY);
            uint4 v[3] = {};
            uint32_t mq[3] = {};
#pragma unroll 1
            for (int it = b < NB - 1 ? SPIN_MAX : 0;; it++) {
                asm volatile("{\n.reg .pred p0, p1, p2;\nsetp.eq.u32 p0, %15, 0;\nsetp.eq.u32 p1, %16, 0;\nsetp.eq.u32 p2, %17, 0;\n"
                             "@p0 ld.relaxed.gpu.global.v4.u32 {%0,%1,%2,%3}, [%12];\n"
                             "@p1 ld.relaxed.gpu.global.v4.u32 {%4,%5,%6,%7}, [%13];\n"
                             "@p2 ld.relaxed.gpu.global.v4.u32 {%8,%9,%10,%11}, [%14];\n}"
                             : "+r"(v[0].x), "+r"(v[0].y), "+r"(v[0].z), "+r"(v[0].w), "+r"(v[1].x), "+r"(v[1].y), "+r"(v[1].z), "+r"(v[1].w),
                               "+r"(v[2].x), "+r"(v[2].y), "+r"(v[2].z), "+r"(v[2].w)
                             : "l"(asrc[0]), "l"(asrc[1]), "l"(asrc[2]), "r"(mq[0]), "r"(mq[1]), "r"(mq[2]) : "memory");
#pragma unroll
                for (int q = 0; q < 3; q++) mq[q] = min(min(v[q].x, v[q].y), min(v[q].z, v[q].w));
                const uint32_t lo = min(min(mq[0], mq[1]), mq[2]);
                if (__all_sync(0xffffffffu, lo != 0 || it == SPIN_MAX)) break;
            }
            CK(8, v[0].x);
            float acc[2][2][4] = {};
#pragma unroll
            for (int q = 0; q < 3; q++) {
#pragma unroll
                for (int pr = 0; pr < 2; pr++) {
                    mma16816(acc[pr][0], wb[q][pr][0], v[q].x, v[q].y);
                    mma16816(acc[pr][1], wb[q][pr][1], v[q].z, v[q].w);
                }
            }
            float y[4];
#pragma unroll
            for (int e = 0; e < 4; e++) y[e] = j < 2 ? acc[0][0][e] + acc[0][1][e] : acc[1][0][e] + acc[1][1][e];
            asm volatile("st.shared.v4.f32 [%0], {%1,%2,%3,%4};" :: "r"(ypart), "f"(y[0]), "f"(y[2]), "f"(y[1]), "f"(y[3]) : "memory");
            CK(9, 0);
            fin_arrive<6>();
        } else {
            continue;
        }
        if (b < NB - 1) fin_sync<5>();
    }
}

typedef CUresult (*EncodeFn)(CUtensorMap*, CUtensorMapDataType, cuuint32_t, void*, const cuuint64_t*, const cuuint64_t*,
                             const cuuint32_t*, const cuuint32_t*, CUtensorMapInterleave, CUtensorMapSwizzle,
                             CUtensorMapL2promotion, CUtensorMapFloatOOBfill);

CUtensorMap make_map(EncodeFn enc, void* ptr, uint64_t cols, uint64_t rows, uint32_t bcols, uint32_t brows,
                     CUtensorMapSwizzle sw, CUtensorMapL2promotion promo) {
    CUtensorMap m;
    const cuuint64_t dims[2] = {cols, rows};
    const cuuint64_t strides[1] = {cols * 2};
    const cuuint32_t box[2] = {bcols, brows};
    const cuuint32_t es[2] = {1, 1};
    enc(&m, CU_TENSOR_MAP_DATA_TYPE_BFLOAT16, 2, ptr, dims, strides, box, es, CU_TENSOR_MAP_INTERLEAVE_NONE, sw, promo,
        CU_TENSOR_MAP_FLOAT_OOB_FILL_NONE);
    return m;
}

}

extern "C" void kernel_launch(void* const* d_in, const int* in_sizes, int n_in, void* d_out, int out_size) {
    (void)in_sizes; (void)n_in; (void)out_size;
    static EncodeFn enc = nullptr;
    static int sms = 0;
    if (!enc) {
        cudaDriverEntryPointQueryResult qr;
        cudaGetDriverEntryPoint("cuTensorMapEncodeTiled", (void**)&enc, cudaEnableDefault, &qr);
        int dev = 0;
        cudaGetDevice(&dev);
        cudaDeviceGetAttribute(&sms, cudaDevAttrMultiProcessorCount, dev);
        cudaFuncSetAttribute(fused_decode_kernel, cudaFuncAttributeMaxDynamicSharedMemorySize, SM_TOTAL);
    }
    if (sms < NCTAS) return;
    const CUtensorMapL2promotion WPROMO = CU_TENSOR_MAP_L2_PROMOTION_L2_128B;
    Params p;
    p.k = make_map(enc, d_in[1], 64, (uint64_t)NBH * SK * 3, 64, TILE_ROWS, CU_TENSOR_MAP_SWIZZLE_128B, CU_TENSOR_MAP_L2_PROMOTION_NONE);
    p.v = make_map(enc, d_in[2], 64, (uint64_t)NBH * SK * 3, 64, TILE_ROWS, CU_TENSOR_MAP_SWIZZLE_128B, CU_TENSOR_MAP_L2_PROMOTION_NONE);
    p.wq = make_map(enc, d_in[3], NH * DH, DM, 48, 160, CU_TENSOR_MAP_SWIZZLE_NONE, WPROMO);
    p.wo = make_map(enc, d_in[4], DM, NH * DH, 32, WO_ROWS, CU_TENSOR_MAP_SWIZZLE_64B, WPROMO);
    p.wg = make_map(enc, d_in[7], FF, DM, 32, 80, CU_TENSOR_MAP_SWIZZLE_64B, (CUtensorMapL2promotion)GPROMO);
    p.wu = make_map(enc, d_in[8], FF, DM, 32, 80, CU_TENSOR_MAP_SWIZZLE_64B, (CUtensorMapL2promotion)GPROMO);
    p.wd = make_map(enc, d_in[9], DM, FF, 16, 192, CU_TENSOR_MAP_SWIZZLE_32B, WPROMO);
    p.x = (const __nv_bfloat16*)d_in[0];
    p.wr = (const __nv_bfloat16*)d_in[6];
    p.out = (__nv_bfloat16*)d_out;
    fused_decode_kernel<<<NCTAS, NTHREADS, SM_TOTAL, cudaStreamPerThread>>>(p);
}
```

```cpp
#include <cuda_runtime.h>
#include <cuda_bf16.h>
#include <cuda.h>
#include <stdint.h>

namespace {

constexpr int NB = 4, NH = 32, SK = 8192, DH = 192, DM = 640, FF = 1536;
constexpr int NBH = NB * NH;
constexpr int TILE = 64;
constexpr int UPB = SK / TILE;
constexpr int NUNITS = NBH * UPB;
constexpr int TILE_BYTES = TILE * DH * 2;
constexpr int TILE_ROWS = TILE * 3;
constexpr int NCTAS = 132;
constexpr int NQ_CTAS = 128;
constexpr int NE_CTAS = 112;

#define NWORK 2
#define LAG 3
#define NPOOL 896
#define RED0 120
#define RING 12
#define OREP 1
#define SROW0 124
#define NPROBE 6
#define VTRIG (NPOOL - 240)
#define TRIG_NS 2250
#define GPROMO 2
#define DCLK 150
#define DOFF 2300
#define HNAP 100
#define PAD0 1024
#define PAD1 1024
#define PAD2 1792
#define JIT 1
#define FARFIRST 1
#define OPRE 0
#define ONAP 0
#define NSS 0
#define FWAIT 100
#define SPREAD 1
#define GDLY 0
#define GPRED 1
#define NWL 2
#define WBAR 1
#define GEARLY 0
#define SKEW 16
#define PREN 128
#define QREH 0
#define K0_SPREAD 0
#define GCLK 250
#define K0_DELAY_NS 1600
#define K0_STEP_NS 900
#define WO_GAP_NS 550
#define WO_ROWS 48
#define QNAP 250
#define WO_AT_NS 3600
constexpr int NAUX = 8;
constexpr int NTHREADS = (NAUX + NWORK + 2) * 32;
constexpr int SPIN_MAX = 1 << 22;

constexpr int SM_KV = 0;
constexpr int SM_A = SM_KV + NWORK * TILE_BYTES;
constexpr int SM_WQ = SM_A + 61440;
constexpr int SM_G = SM_WQ;
constexpr int SM_X = SM_G + 81920;
constexpr int XPITCH = 648;
constexpr int HPITCH = 1344;
constexpr int SM_RED = SM_X + 5 * HPITCH;
constexpr int FPITCH = 1040;
constexpr int SM_RED2 = SM_RED;
constexpr int YPITCH = 320;
constexpr int SM_MISC = SM_RED + 6144;
constexpr int BAR_KV = SM_MISC, BAR_WQ = SM_MISC + 32, BAR_W = SM_MISC + 40, SM_SIDE = SM_MISC + 48, BAR_G = SM_MISC + 64, SM_MOM = SM_MISC + 128;
constexpr int SM_TOTAL = SM_MISC + 160;

struct Params {
    CUtensorMap k, v;
    CUtensorMap wq;
    CUtensorMap wo;
    CUtensorMap wg, wu;
    CUtensorMap wd;
    const char* wq_raw;
    const __nv_bfloat16 *x, *wr;
    __nv_bfloat16* out;
};

struct Early {
    uint32_t q[96];
    uint32_t umax[UPB];
};
#define LSTRIDE 16
struct State {
    float4 oacc[SROW0][64];
    float2 attn[NB][DM];
    float2 lsum[SROW0][LSTRIDE];
    unsigned pool[64];
    uint32_t tstart[32];
    uint32_t score[NPOOL][32];
};
constexpr int STATE_V4 = ((sizeof(State) / 32 + NQ_CTAS - 1) / NQ_CTAS) * 2;
static_assert(sizeof(State) % 32 == 0, "State is cleared in whole sectors");
static_assert(sizeof(Early) == 56 * 16, "an Early entry is cleared by 56 threads");
constexpr uint32_t X_O = 0;
constexpr uint32_t X_L = X_O + 4 * OREP * 1024;
constexpr uint32_t X_H = X_L + 4 * OREP * 128;
constexpr uint32_t X_A = X_H + NB * DM * 2;
constexpr uint32_t X_P = X_A + NB * FF * 2;
constexpr uint32_t X_END = X_P + 4096;
static_assert(X_END <= 8 * 4096 && SROW0 == NBH - 4, "");
struct Scratch {
    unsigned char sided[8][2][4096];
    unsigned work[64];
    unsigned cnt_z[32];
    unsigned char pad0[PAD0];
    Early early[NBH];
    unsigned char pad1[PAD1];
    State st;
    unsigned char pad2[PAD2];
    float4 ring[RING][UPB][64];
};
constexpr size_t PAGE = 2u << 20;
static_assert(sizeof(Scratch) <= PAGE, "scratch must fit one page");
__device__ __align__(128) unsigned char g_raw[2 * PAGE];
__device__ __forceinline__ Scratch* scratch() {
    return reinterpret_cast<Scratch*>((reinterpret_cast<uintptr_t>(g_raw) + PAGE - 1) & ~(uintptr_t)(PAGE - 1));
}
template <typename T> __device__ __forceinline__ T* sided(int side, uint32_t x) {
    const uint32_t pair = (x >> 10) & 7;
    return reinterpret_cast<T*>(&scratch()->sided[pair][(side ^ pair) & 1]
                                    [(x & 127) + ((x & 128) << 1) + ((x & 768) << 2) + ((x >> 6) & 128) + ((x >> 5) & 512)]);
}
template <typename T> __device__ __forceinline__ T* other_side(T* p) { return reinterpret_cast<T*>(reinterpret_cast<uintptr_t>(p) ^ 4096); }
#define g_early scratch()->early
#define g_st scratch()->st
#define g_ring scratch()->ring
#define g_cnt_z scratch()->cnt_z
#define g_work scratch()->work
#define TS(i)
#define TSW(i)
#define TS2(i)
#define TSI(n, i)
#define PH(i)
#define CK(i, dep)
#define ARR()
#define PROG(u)
#define LT(i)

__device__ __forceinline__ int row_of(int u) { return (((unsigned)u >> (7 + NWL)) << NWL) | (u & ((1 << NWL) - 1)); }
__device__ __forceinline__ int pos_of(int u) { return ((unsigned)u >> NWL) & (UPB - 1); }
__device__ __forceinline__ int tile_of(int u) { return (row_of(u) * UPB + ((pos_of(u) + (u & ((1 << NWL) - 1)) * SKEW) & (UPB - 1))) * TILE_ROWS; }

__device__ __forceinline__ uint32_t s2u(const void* p) { return (uint32_t)__cvta_generic_to_shared(p); }
__device__ __forceinline__ void mbar_init(uint32_t bar, int cnt) {
    asm volatile("mbarrier.init.shared::cta.b64 [%0], %1;" :: "r"(bar), "r"(cnt) : "memory");
}
__device__ __forceinline__ void mbar_expect_tx(uint32_t bar, uint32_t bytes) {
    asm volatile("mbarrier.arrive.expect_tx.shared::cta.b64 _, [%0], %1;" :: "r"(bar), "r"(bytes) : "memory");
}
__device__ __forceinline__ void mbar_wait(uint32_t bar, uint32_t parity) {
    asm volatile("{\n.reg .pred p;\n.reg .u32 n;\nmov.u32 n, 0;\nWAIT_LOOP:\n"
                 "mbarrier.try_wait.parity.shared::cta.b64 p, [%0], %1;\n"
                 "@p bra WAIT_DONE;\nadd.u32 n, n, 1;\nsetp.lt.u32 p, n, %2;\n@p bra WAIT_LOOP;\nWAIT_DONE:\n}"
                 :: "r"(bar), "r"(parity), "n"(SPIN_MAX) : "memory");
}
__device__ __forceinline__ void tma_tile(uint32_t dst, const CUtensorMap* tm, int row, uint32_t bar, uint64_t pol) {
    asm volatile("cp.async.bulk.tensor.2d.shared::cluster.global.mbarrier::complete_tx::bytes.L2::cache_hint "
                 "[%0], [%1, {%3, %4}], [%2], %5;"
                 :: "r"(dst), "l"(tm), "r"(bar), "r"(0), "r"(row), "l"(pol) : "memory");
}
__device__ __forceinline__ void request_tile(uint32_t dst, const CUtensorMap* tm, int unit, uint32_t bar, uint64_t pol) {
    asm volatile("{\n.reg .pred p;\nelect.sync _|p, 0xffffffff;\n"
                 "@p mbarrier.arrive.expect_tx.shared::cta.b64 _, [%2], %6;\n"
                 "@p cp.async.bulk.tensor.2d.shared::cluster.global.mbarrier::complete_tx::bytes.L2::cache_hint "
                 "[%0], [%1, {%3, %4}], [%2], %5;\n}"
                 :: "r"(dst), "l"(tm), "r"(bar), "r"(0), "r"(tile_of(unit)), "l"(pol), "n"(TILE_BYTES) : "memory");
}
__device__ __forceinline__ uint32_t now_ns() { uint32_t t; asm volatile("mov.u32 %0, %%globaltimer_lo;" : "=r"(t)); return t; }
__device__ __forceinline__ uint32_t now_clk() { uint32_t t; asm volatile("mov.u32 %0, %%clock;" : "=r"(t)); return t; }
__device__ __forceinline__ void wait_clk(uint32_t t) { while (__any_sync(0xffffffffu, (int)(now_clk() - t) < 0)) {} }
constexpr uint64_t EVICT_FIRST = 0x12F0000000000000ull, EVICT_NORMAL = 0x1000000000000000ull;
__device__ __forceinline__ void request_box(uint32_t dst, const CUtensorMap* tm, int col, int row, uint32_t bar, uint64_t pol) {
    asm volatile("{\n.reg .pred p;\nelect.sync _|p, 0xffffffff;\n"
                 "@p cp.async.bulk.tensor.2d.shared::cluster.global.mbarrier::complete_tx::bytes.L2::cache_hint [%0], [%1, {%3, %4}], [%2], %5;\n}"
                 :: "r"(dst), "l"(tm), "r"(bar), "r"(col), "r"(row), "l"(pol) : "memory");
}
__device__ __forceinline__ uint32_t lds32(uint32_t addr) {
    uint32_t v;
    asm volatile("ld.shared.u32 %0, [%1];" : "=r"(v) : "r"(addr) : "memory");
    return v;
}
__device__ __forceinline__ void ldsm4(uint32_t (&r)[4], uint32_t addr) {
    asm volatile("ldmatrix.sync.aligned.m8n8.x4.shared.b16 {%0,%1,%2,%3}, [%4];"
                 : "=r"(r[0]), "=r"(r[1]), "=r"(r[2]), "=r"(r[3]) : "r"(addr) : "memory");
}
__device__ __forceinline__ void ldsm4t(uint32_t (&r)[4], uint32_t addr) {
    asm volatile("ldmatrix.sync.aligned.m8n8.x4.trans.shared.b16 {%0,%1,%2,%3}, [%4];"
                 : "=r"(r[0]), "=r"(r[1]), "=r"(r[2]), "=r"(r[3]) : "r"(addr) : "memory");
}
__device__ __forceinline__ void mma16816(float (&c)[4], const uint32_t (&a)[4], uint32_t b0, uint32_t b1) {
    asm volatile("mma.sync.aligned.m16n8k16.row.col.f32.bf16.bf16.f32 {%0,%1,%2,%3}, {%4,%5,%6,%7}, {%8,%9}, {%0,%1,%2,%3};"
                 : "+f"(c[0]), "+f"(c[1]), "+f"(c[2]), "+f"(c[3])
                 : "r"(a[0]), "r"(a[1]), "r"(a[2]), "r"(a[3]), "r"(b0), "r"(b1));
}
__device__ __forceinline__ uint4 ld_relaxed_v4(const void* p) {
    uint4 v;
    asm volatile("ld.relaxed.gpu.global.v4.u32 {%0,%1,%2,%3}, [%4];" : "=r"(v.x), "=r"(v.y), "=r"(v.z), "=r"(v.w) : "l"(p) : "memory");
    return v;
}
__device__ __forceinline__ float4 ld_relaxed_f4(const void* p) {
    float4 v;
    asm volatile("ld.relaxed.gpu.global.v4.f32 {%0,%1,%2,%3}, [%4];" : "=f"(v.x), "=f"(v.y), "=f"(v.z), "=f"(v.w) : "l"(p) : "memory");
    return v;
}
__device__ __forceinline__ float2 ld_relaxed_f2(const void* p) {
    float2 v;
    asm volatile("ld.relaxed.gpu.global.v2.f32 {%0,%1}, [%2];" : "=f"(v.x), "=f"(v.y) : "l"(p) : "memory");
    return v;
}
__device__ __forceinline__ float4 ld_relaxed_b128(const void* p) {
    float4 v;
    asm volatile("{\n.reg .b128 t;\n.reg .b64 a, b;\nld.relaxed.gpu.global.b128 t, [%4];\nmov.b128 {a, b}, t;\n"
                 "mov.b64 {%0, %1}, a;\nmov.b64 {%2, %3}, b;\n}" : "=f"(v.x), "=f"(v.y), "=f"(v.z), "=f"(v.w) : "l"(p) : "memory");
    return v;
}
__device__ __forceinline__ void st_relaxed_b128(void* p, float x, float y, float z, float w) {
    asm volatile("{\n.reg .b128 t;\n.reg .b64 a, b;\nmov.b64 a, {%1, %2};\nmov.b64 b, {%3, %4};\nmov.b128 t, {a, b};\n"
                 "st.relaxed.gpu.global.b128 [%0], t;\n}" :: "l"(p), "f"(x), "f"(y), "f"(z), "f"(w) : "memory");
}
__device__ __forceinline__ unsigned ld_acquire(const unsigned* p) {
    unsigned v;
    asm volatile("ld.acquire.gpu.global.u32 %0, [%1];" : "=r"(v) : "l"(p) : "memory");
    return v;
}
__device__ __forceinline__ void st_relaxed(void* p, uint32_t v) {
    asm volatile("st.relaxed.gpu.global.u32 [%0], %1;" :: "l"(p), "r"(v) : "memory");
}
__device__ __forceinline__ void red_f2(float* p, float a, float b) {
    asm volatile("red.relaxed.gpu.global.add.v2.f32 [%0], {%1,%2};" :: "l"(p), "f"(a), "f"(b) : "memory");
}
__device__ __forceinline__ void red_f4(float* p, float a, float b, float c, float d) {
    asm volatile("red.relaxed.gpu.global.add.v4.f32 [%0], {%1,%2,%3,%4};" :: "l"(p), "f"(a), "f"(b), "f"(c), "f"(d) : "memory");
}
__device__ __forceinline__ void draw(int& ticket, unsigned* ctr, bool pred) {
    asm volatile("{\n.reg .pred p;\nsetp.ne.u32 p, %2, 0;\n@p atom.relaxed.gpu.global.inc.u32 %0, [%1], 0x7fffffff;\n}"
                 : "+r"(ticket) : "l"(ctr), "r"((uint32_t)pred) : "memory");
}
__device__ __forceinline__ void red_release(unsigned* p) {
    asm volatile("red.release.gpu.global.add.u32 [%0], 1;" :: "l"(p) : "memory");
}
__device__ __forceinline__ uint32_t ld_relaxed_u32(const void* p) {
    uint32_t v;
    asm volatile("ld.relaxed.gpu.global.u32 %0, [%1];" : "=r"(v) : "l"(p) : "memory");
    return v;
}
__device__ __forceinline__ float rcp_approx(float v) {
    float r;
    asm("rcp.approx.ftz.f32 %0, %1;" : "=f"(r) : "f"(v));
    return r;
}
__device__ __forceinline__ float sigmoid_approx(float v) {
    float e;
    asm("ex2.approx.ftz.f32 %0, %1;" : "=f"(e) : "f"(v * -1.4426950408889634f));
    return rcp_approx(1.0f + e);
}
__device__ __forceinline__ float sqrt_approx(float v) {
    float r;
    asm("sqrt.approx.ftz.f32 %0, %1;" : "=f"(r) : "f"(v));
    return r;
}
__device__ __forceinline__ uint2 ld_relaxed_v2(const void* p) {
    uint2 v;
    asm volatile("ld.relaxed.gpu.global.v2.u32 {%0,%1}, [%2];" : "=r"(v.x), "=r"(v.y) : "l"(p) : "memory");
    return v;
}
__device__ __forceinline__ void wait_count(const unsigned* p, unsigned target) {
#pragma unroll 1
    for (int it = 0; it < SPIN_MAX; it++) {
        if (ld_acquire(p) >= target) break;
        __nanosleep(400);
    }
}
__device__ __forceinline__ float4* oacc_at(int side, int row, int grp) {
    return row >= SROW0 ? sided<float4>(side, X_O + (row - SROW0) * 1024 + grp * 16) : &g_st.oacc[row][grp];
}
__device__ __forceinline__ float2* lsum_at(int side, int row) {
    return row >= SROW0 ? sided<float2>(side, X_L + (row - SROW0) * 128) : g_st.lsum[row];
}
__device__ __forceinline__ void wait_row(int side, int bh, float n) {
    const float2* l = lsum_at(side, bh);
#pragma unroll 1
    for (int it = 0; it < SPIN_MAX; it++) {
        const float c = ld_relaxed_f2(l).y;
        if (c >= n) break;
        if (c == 0.f) __nanosleep(600);
    }
}
__device__ __forceinline__ void wait_row_o(int side, int bh, float n) {
    wait_row(side, bh, n);
    if (bh >= RED0) return;
#pragma unroll 1
    for (int it = 0; it < SPIN_MAX; it++) {
        if (__uint_as_float(ld_relaxed_u32(&g_st.oacc[bh][0].w)) == UPB) break;
        __nanosleep(300);
    }
}
__device__ __forceinline__ void spin_ns(int ns) {
    const long long t0 = clock64();
    while (clock64() - t0 < (long long)ns * 2) {}
}
__device__ __forceinline__ uint32_t pack_bf16(float lo, float hi) {
    uint32_t r;
    asm("cvt.rn.bf16x2.f32 %0, %1, %2;" : "=r"(r) : "f"(hi), "f"(lo));
    return r;
}
__device__ __forceinline__ float bf16r(float v) { return __uint_as_float(pack_bf16(0.f, v)); }
__device__ __forceinline__ uint32_t pack_neg(float lo, float hi) {
    const uint32_t w = pack_bf16(-lo, -hi);
    return w ? w : 0x80008000u;
}
__device__ __forceinline__ float lo_f(uint32_t v) { return __uint_as_float(v << 16); }
__device__ __forceinline__ float hi_f(uint32_t v) { return __uint_as_float(v & 0xffff0000u); }
__device__ __forceinline__ float warp_sum(float v) {
#pragma unroll
    for (int o = 16; o; o >>= 1) v += __shfl_xor_sync(0xffffffffu, v, o);
    return v;
}
__device__ __forceinline__ void layernorm20(float (&v)[20]) {
    float s = 0.f;
#pragma unroll
    for (int i = 0; i < 20; i++) s += v[i];
    const float mean = warp_sum(s) * (1.0f / DM);
    float q = 0.f;
#pragma unroll
    for (int i = 0; i < 20; i++) { const float d = v[i] - mean; q += d * d; }
    const float var = bf16r(warp_sum(q) * (1.0f / DM));
    const float m = bf16r(mean);
    const float rden = 1.0f / bf16r(sqrtf(bf16r(var + 1e-5f)));
#pragma unroll
    for (int i = 0; i < 20; i++) v[i] = bf16r(bf16r(v[i] - m) * rden);
}

__device__ __forceinline__ float sel4(int j, float a, float b, float c, float d) {
    float lo, hi, r;
    asm("{\n.reg .pred p;\nsetp.ne.s32 p, %3, 0;\nselp.f32 %0, %2, %1, p;\n}" : "=f"(lo) : "f"(a), "f"(b), "r"(j & 1));
    asm("{\n.reg .pred p;\nsetp.ne.s32 p, %3, 0;\nselp.f32 %0, %2, %1, p;\n}" : "=f"(hi) : "f"(c), "f"(d), "r"(j & 1));
    asm("{\n.reg .pred p;\nsetp.ne.s32 p, %3, 0;\nselp.f32 %0, %2, %1, p;\n}" : "=f"(r) : "f"(lo), "f"(hi), "r"(j & 2));
    return r;
}
template <typename T> __device__ __forceinline__ void pin(T*& p) { asm volatile("" : "+l"(p)); }
__device__ __forceinline__ void pin(uint32_t& v) { asm volatile("" : "+r"(v)); }
__device__ __forceinline__ void pin(float& v) { asm volatile("" : "+f"(v)); }
__device__ __forceinline__ uint32_t after(uint32_t n, float v) {
    asm volatile("{\n.reg .pred p;\nsetp.eq.u32 p, %1, 0x7fc1a5a5;\n@p add.u32 %0, %0, 32;\n}" : "+r"(n) : "r"(__float_as_uint(v)));
    return n;
}
__device__ __forceinline__ float2 lds64f(uint32_t addr) {
    float2 v;
    asm volatile("ld.shared.v2.f32 {%0,%1}, [%2];" : "=f"(v.x), "=f"(v.y) : "r"(addr) : "memory");
    return v;
}
__device__ __forceinline__ float4 lds128f(uint32_t addr) {
    float4 v;
    asm volatile("ld.shared.v4.f32 {%0,%1,%2,%3}, [%4];" : "=f"(v.x), "=f"(v.y), "=f"(v.z), "=f"(v.w) : "r"(addr) : "memory");
    return v;
}
__device__ __forceinline__ void sts64f(uint32_t addr, float a, float b, bool pred) {
    asm volatile("{\n.reg .pred p;\nsetp.ne.u32 p, %3, 0;\n@p st.shared.v2.f32 [%0], {%1,%2};\n}" :: "r"(addr), "f"(a), "f"(b), "r"((uint32_t)pred) : "memory");
}
__device__ __forceinline__ void sts128f(uint32_t addr, float a, float b, float c, float d, bool pred) {
    asm volatile("{\n.reg .pred p;\nsetp.ne.u32 p, %5, 0;\n@p st.shared.v4.f32 [%0], {%1,%2,%3,%4};\n}"
                 :: "r"(addr), "f"(a), "f"(b), "f"(c), "f"(d), "r"((uint32_t)pred) : "memory");
}
__device__ __forceinline__ void lds128_if(uint4& v, uint32_t addr, bool pred) {
    asm volatile("{\n.reg .pred p;\nsetp.ne.u32 p, %5, 0;\n@p ld.shared.v4.u32 {%0,%1,%2,%3}, [%4];\n}"
                 : "+r"(v.x), "+r"(v.y), "+r"(v.z), "+r"(v.w) : "r"(addr), "r"((uint32_t)pred) : "memory");
}
__device__ __forceinline__ void sts32f(uint32_t addr, float v) { asm volatile("st.shared.f32 [%0], %1;" :: "r"(addr), "f"(v) : "memory"); }
template <int ID> __device__ __forceinline__ void fin_arrive() { asm volatile("bar.arrive %0, 288;" :: "n"(ID) : "memory"); }
template <int ID> __device__ __forceinline__ void fin_sync() { asm volatile("bar.sync %0, 288;" :: "n"(ID) : "memory"); }
template <int ID> __device__ __forceinline__ void fin_sync(uint32_t n) { asm volatile("bar.sync %0, %1;" :: "n"(ID), "r"(n) : "memory"); }
__device__ __forceinline__ float2 sum8(uint32_t addr) {
    float2 t[8];
#pragma unroll
    for (int w = 0; w < 8; w++) t[w] = lds64f(addr + w * 128);
    return make_float2(((t[0].x + t[1].x) + (t[2].x + t[3].x)) + ((t[4].x + t[5].x) + (t[6].x + t[7].x)),
                       ((t[0].y + t[1].y) + (t[2].y + t[3].y)) + ((t[4].y + t[5].y) + (t[6].y + t[7].y)));
}
__device__ __forceinline__ float4 sum4x4(uint32_t addr) {
    float4 t[4];
#pragma unroll
    for (int w = 0; w < 4; w++) t[w] = lds128f(addr + w * 256);
    return make_float4((t[0].x + t[1].x) + (t[2].x + t[3].x), (t[0].y + t[1].y) + (t[2].y + t[3].y),
                       (t[0].z + t[1].z) + (t[2].z + t[3].z), (t[0].w + t[1].w) + (t[2].w + t[3].w));
}
template <int NJ>
__device__ __forceinline__ void load_o(uint32_t (&ob)[3 * NJ][2], int bh, int J0, int j) {
    float4 v[NJ][4];
    float2 l;
#pragma unroll 1
    for (int it = 0; it < SPIN_MAX; it++) {
#pragma unroll
        for (int J = 0; J < NJ; J++) {
#pragma unroll
            for (int e = 0; e < 4; e++) v[J][e] = ld_relaxed_f4(&g_st.oacc[bh][(J0 + J) * 16 + e * 4 + j]);
        }
        l = ld_relaxed_f2(g_st.lsum[bh]);
        bool ok = l.y == UPB;
#pragma unroll
        for (int J = 0; J < NJ; J++) {
#pragma unroll
            for (int e = 0; e < 4; e++) ok &= v[J][e].w == UPB;
        }
        if (__all_sync(0xffffffffu, ok)) break;
    }
    const float rl = __fdividef(1.0f, l.x);
#pragma unroll
    for (int J = 0; J < NJ; J++) {
        ob[3 * J][0] = pack_bf16(v[J][0].x * rl, v[J][1].x * rl);     ob[3 * J][1] = pack_bf16(v[J][2].x * rl, v[J][3].x * rl);
        ob[3 * J + 1][0] = pack_bf16(v[J][0].y * rl, v[J][1].y * rl); ob[3 * J + 1][1] = pack_bf16(v[J][2].y * rl, v[J][3].y * rl);
        ob[3 * J + 2][0] = pack_bf16(v[J][0].z * rl, v[J][1].z * rl); ob[3 * J + 2][1] = pack_bf16(v[J][2].z * rl, v[J][3].z * rl);
    }
}
__device__ __forceinline__ void aux_sync() { asm volatile("bar.sync 1, 256;" ::: "memory"); }

__global__ void __launch_bounds__(NTHREADS, 1)
fused_decode_kernel(const __grid_constant__ Params p) {
    extern __shared__ __align__(1024) unsigned char smem[];
    if (threadIdx.x < PREN) asm volatile("prefetch.global.L2 [%0];" :: "l"(p.wq_raw + (blockIdx.x * PREN + threadIdx.x) * 128));
    const uint32_t sb = s2u(smem);
    const int tid = threadIdx.x, warp = __shfl_sync(0xffffffffu, tid >> 5, 0), lane = tid & 31;
    const int cta = blockIdx.x;
    constexpr int grid = NCTAS;
    const int g = lane >> 2, j = lane & 3;
    const bool is_l = cta >= NE_CTAS, is_f = cta < 96 && !(cta & 1), is_g = cta < 80 && (cta & 1);
    const int fidx = cta >> 1;

    TS(0);
    if (warp == 4 && cta < NQ_CTAS) {
        asm volatile("{\n.reg .pred p;\nelect.sync _|p, 0xffffffff;\n"
                     "@p mbarrier.init.shared::cta.b64 [%0], 1;\n"
                     "@p fence.mbarrier_init.release.cluster;\n"
                     "@p mbarrier.arrive.expect_tx.shared::cta.b64 _, [%0], 61440;\n}" :: "r"(sb + BAR_WQ) : "memory");
#pragma unroll
        for (int i = 0; i < 4; i++) request_box(sb + SM_WQ + i * 15360, &p.wq, cta * 48, i * 160, sb + BAR_WQ, EVICT_NORMAL);
    }
    if (tid == 160) {
#pragma unroll
        for (int w = 0; w < NWORK; w++) mbar_init(sb + BAR_KV + w * 8, 1);
        mbar_init(sb + BAR_W, 1);
#pragma unroll
        for (int w = 0; w < 8; w++) mbar_init(sb + BAR_G + w * 8, 1);
        asm volatile("fence.mbarrier_init.release.cluster;" ::: "memory");
    }
    __syncthreads();
    if (warp == NAUX + NWORK + 1) {
        uint32_t t = now_clk() + 2 * WO_AT_NS;
        if (lane == 0) mbar_expect_tx(sb + BAR_W, cta < NE_CTAS ? 61440 : 49152);
        const int col = cta < NE_CTAS ? (cta & 3) * 160 : (cta - NE_CTAS) * 32, row = cta < NE_CTAS ? (cta >> 2) * DH : 28 * DH;
#pragma unroll 1
        for (int r = 0; r < DH; r += WO_ROWS) {
            wait_clk(t);
#pragma unroll 1
            for (int i = 0; i < (cta < NE_CTAS ? 5 : 4); i++)
                request_box(sb + SM_A + i * 12288 + r * 64, &p.wo, cta < NE_CTAS ? col + i * 32 : col, (cta < NE_CTAS ? row : row + i * DH) + r, sb + BAR_W, EVICT_FIRST);
            t += 2 * WO_GAP_NS;
        }
        if (!is_f && !is_g) return;
        if (lane < 8) mbar_expect_tx(sb + BAR_G + lane * 8, is_f ? 10240 : 6144);
        asm volatile("bar.sync 9, 288;" ::: "memory");
        asm volatile("fence.proxy.async.shared::cta;" ::: "memory");
#pragma unroll 1
        for (int it = 0; it < SPIN_MAX; it++) {
            t = ld_relaxed_u32(g_st.tstart);
            if (__all_sync(0xffffffffu, t != 0)) break;
            __nanosleep(400);
        }
#pragma unroll 1
        for (int it = 0; it < SPIN_MAX; it++) if (__all_sync(0xffffffffu, t - now_ns() > 2 * TRIG_NS)) break;
        TSW(11);
        t = now_clk() + (is_f ? 0 : DOFF);
#pragma unroll 1
        for (int i = 0; i < 8; i++, t += is_f ? GCLK : DCLK) {
            wait_clk(t);
            if (is_f) {
                request_box(sb + SM_G + i * 5120, &p.wg, fidx * 32, i * 80, sb + BAR_G + i * 8, EVICT_NORMAL);
                request_box(sb + SM_G + 40960 + i * 5120, &p.wu, fidx * 32, i * 80, sb + BAR_G + i * 8, EVICT_NORMAL);
            } else {
                request_box(sb + SM_G + i * 6144, &p.wd, fidx * 16, i * 192, sb + BAR_G + i * 8, EVICT_NORMAL);
            }
        }
        return;
    }
    if (warp == NAUX + NWORK) {
        if (cta < NQ_CTAS) {
#pragma unroll
            for (int i = lane; i < STATE_V4; i += 32)
                if (cta * STATE_V4 + i < (int)(sizeof(State) / 16)) reinterpret_cast<uint4*>(&g_st)[cta * STATE_V4 + i] = make_uint4(0u, 0u, 0u, 0u);
            if (cta * 512 < X_END) {
                uint4* z = sided<uint4>(0, cta * 512 + lane * 16);
                *z = make_uint4(0u, 0u, 0u, 0u);
                *other_side(z) = make_uint4(0u, 0u, 0u, 0u);
            }
            __syncwarp();
            if (lane == 0) red_release(g_cnt_z);
        }
        if (lane == 0) { TS2(2); wait_count(g_cnt_z, NQ_CTAS); TS2(29); }
        __syncwarp();
        asm volatile("bar.arrive 2, %0;" :: "n"((NWORK + 1) * 32) : "memory");
        uint32_t rtt[2] = {0xffffffffu, 0xffffffffu};
        if (lane == 0) {
#pragma unroll 1
            for (int r = 0; r < 2 * NPROBE; r++) {
                int v = 0;
                uint32_t t1 = 0;
                unsigned* ctr = sided<unsigned>(r & 1, X_P + ((cta * 32 + (r >> 1) * 768) & 4095));
                pin(ctr);
                const uint32_t t0 = now_clk();
                draw(v, ctr, true);
                asm volatile("{\n.reg .pred q;\nsetp.ge.s32 q, %1, 0;\n@q mov.u32 %0, %%clock;\n}" : "+r"(t1) : "r"(v) : "memory");
                if (r & 1) rtt[1] = min(rtt[1], t1 - t0); else rtt[0] = min(rtt[0], t1 - t0);
            }
            sts32f(sb + SM_SIDE, __int_as_float(rtt[1] < rtt[0]));
        }
        const int side = __shfl_sync(0xffffffffu, rtt[1] < rtt[0], 0);
        fin_arrive<3>();
        int job = cta;
        auto sum_rows = [&](int row_end) {
#pragma unroll 1
            for (; job < 8 * min(row_end, RED0); job += NCTAS) {
                const int row = job >> 3, grp = (job & 7) * 8 + (lane & 7);
                if (lane == 0) wait_row(side, row, UPB);
                __syncwarp();
                const float4* src = &g_ring[row % RING][lane >> 3][grp];
                float sx = 0.f, sy = 0.f, sz = 0.f;
#pragma unroll 1
                for (int i = 0; i < 2; i++, src += 64 * 64) {
                    float4 v[16];
#pragma unroll 1
                    for (int it = 0; it < SPIN_MAX; it++) {
                        bool ok = true;
#pragma unroll
                        for (int k = 0; k < 16; k++) v[k] = ld_relaxed_b128(src + k * 4 * 64);
#pragma unroll
                        for (int k = 0; k < 16; k++) ok &= v[k].w == (float)(row + 1);
                        if (__all_sync(0xffffffffu, ok)) break;
                    }
#pragma unroll
                    for (int k = 0; k < 16; k++) { sx += v[k].x; sy += v[k].y; sz += v[k].z; }
                }
#pragma unroll
                for (int o = 8; o < 32; o <<= 1) {
                    sx += __shfl_xor_sync(0xffffffffu, sx, o); sy += __shfl_xor_sync(0xffffffffu, sy, o); sz += __shfl_xor_sync(0xffffffffu, sz, o);
                }
                if (lane < 8) st_relaxed_b128(&g_st.oacc[row][grp], sx, sy, sz, UPB);
            }
        };
        {
            uint32_t wr[10];
            float wsum = 0.f;
#pragma unroll
            for (int i = 0; i < 10; i++) {
                const int w = 4 * lane + 128 * (i >> 2) + (i & 3) - (i >= 8 ? 2 * lane : 0);
                wr[i] = *reinterpret_cast<const uint32_t*>(p.wr + (w >> 4) * 32 + (w & 3) * 8 + ((w >> 1) & 6));
                wsum += lo_f(wr[i]) + hi_f(wr[i]);
            }
            wsum = warp_sum(wsum);
            const int lb = lane >> 3, lc = lane & 7;
            uint32_t ypart = sb + SM_RED2 + (lb >> 1) * 160 + lc * 16 + (lb & 1) * 8;
            __nv_bfloat16* out = p.out + lb * DM + fidx * 16 + lc;
            float nmean_l = 0.f, rden_l = 0.f, sig_l = 0.f;
#pragma unroll 1
            for (int b = 0; b < NB; b++) {
                const uint32_t hx = X_H + b * (DM * 2), hrow = sb + SM_X + b * HPITCH;
                const uint4 *src0 = sided<uint4>(side, hx + 16 * lane), *src1 = sided<uint4>(side, hx + 512 + 16 * lane);
                const uint2* src2 = sided<uint2>(side, hx + 1024 + 8 * lane);
                sum_rows((b + 1) * NH);
                if (!is_l && !is_f && !is_g) continue;
                pin(src0); pin(src1); pin(src2); pin(ypart); pin(out);
                if (lane == 0) wait_row(side, b * NH + (is_l ? 28 : NH - 1), is_l ? 1 : FWAIT);
                __syncwarp();
                if (is_l) {
                    const int col = (cta - NE_CTAS) * 32 + 2 * (lane & 15);
                    uint32_t lpart = sb + SM_RED + (lane & 15) * 8;
                    const uint32_t xv = *reinterpret_cast<const uint32_t*>(p.x + b * DM + col);
                    uint32_t* hdst = sided<uint32_t>(lane >> 4, hx + 4 * ((col >> 5) * 16 + (col & 6) * 2 + ((col >> 3) & 3)));
                    float4 early;
#pragma unroll 1
                    for (int it = 0; it < SPIN_MAX; it++) {
                        early = ld_relaxed_f4(&g_st.attn[b][col]);
                        if (__all_sync(0xffffffffu, early.y == NE_CTAS / 4 && early.w == NE_CTAS / 4)) break;
                    }
                    if (lane == 0) TS2(23);
                    float x0 = lo_f(xv), x1 = hi_f(xv);
                    pin(hdst); pin(lpart); pin(x0); pin(x1);
                    fin_sync<4>();
                    CK(2, lds32(sb + SM_RED));
                    const float2 late = sum8(lpart);
                    st_relaxed(hdst, pack_neg(x0 + bf16r(early.x + late.x), x1 + bf16r(early.z + late.y)));
                    CK(3, 0);
                    if (lane == 0) TS2(15);
                    fin_sync<5>();
                    continue;
                }
                uint4 h0, h1;
                uint2 h2;
                float mm[5][4];
#pragma unroll 1
                for (int it = 0; it < SPIN_MAX; it++) {
                    h0 = ld_relaxed_v4(src0);
                    h1 = ld_relaxed_v4(src1);
                    h2 = ld_relaxed_v2(src2);
                    asm volatile("st.shared.v4.u32 [%0], {%1,%2,%3,%4};" :: "r"(hrow + lane * 16), "r"(h0.x), "r"(h0.y), "r"(h0.z), "r"(h0.w) : "memory");
                    asm volatile("st.shared.v4.u32 [%0], {%1,%2,%3,%4};" :: "r"(hrow + 512 + lane * 16), "r"(h1.x), "r"(h1.y), "r"(h1.z), "r"(h1.w) : "memory");
                    asm volatile("st.shared.v2.u32 [%0], {%1,%2};" :: "r"(hrow + 1024 + lane * 8), "r"(h2.x), "r"(h2.y) : "memory");
                    const uint32_t w[10] = {h0.x, h0.y, h0.z, h0.w, h1.x, h1.y, h1.z, h1.w, h2.x, h2.y};
#pragma unroll
                    for (int i = 0; i < 5; i++) {
                        const uint32_t a[4] = {w[2 * i], 0x3f803f80u, w[2 * i + 1], 0x3f803f80u};
                        mm[i][0] = mm[i][1] = mm[i][2] = mm[i][3] = 0.f;
                        mma16816(mm[i], a, w[2 * i], w[2 * i + 1]);
                    }
                    const uint32_t lo = min(min(min(h0.x, h0.y), min(h0.z, h0.w)), min(min(min(h1.x, h1.y), min(h1.z, h1.w)), min(h2.x, h2.y)));
                    if (GDLY && !is_f) sts32f(sb + SM_MOM, __uint_as_float(now_clk()));
                    const bool ok = __all_sync(0xffffffffu, lo != 0 || it == SPIN_MAX - 1);
                    asm volatile("{\n.reg .pred p;\nsetp.ne.u32 p, %0, 0;\n@p bar.arrive 7, 288;\n}" :: "r"((uint32_t)ok) : "memory");
                    if (ok) break;
                    if (!is_f) __nanosleep(HNAP);
                }
                CK(4, h0.x);
                if (lane == 0 && is_f) TS2(12);
                const uint32_t hw[10] = {h0.x, h0.y, h0.z, h0.w, h1.x, h1.y, h1.z, h1.w, h2.x, h2.y};
                float m1 = ((mm[0][2] + mm[1][2]) + (mm[2][2] + mm[3][2])) + ((mm[0][3] + mm[1][3]) + (mm[2][3] + mm[3][3])) + (mm[4][2] + mm[4][3]);
                float m2 = (g & 1) ? ((mm[0][1] + mm[1][1]) + (mm[2][1] + mm[3][1])) + mm[4][1] : ((mm[0][0] + mm[1][0]) + (mm[2][0] + mm[3][0])) + mm[4][0];
                m2 += __shfl_xor_sync(0xffffffffu, m2, 4);
                m1 = (m1 + __shfl_xor_sync(0xffffffffu, m1, 1)) + (__shfl_xor_sync(0xffffffffu, m1, 2) + __shfl_xor_sync(0xffffffffu, m1, 3));
                m2 = (__shfl_sync(0xffffffffu, m2, 0) + __shfl_sync(0xffffffffu, m2, 9)) + (__shfl_sync(0xffffffffu, m2, 18) + __shfl_sync(0xffffffffu, m2, 27));
                m1 *= 1.0f / DM;
                const float nmean = bf16r(m1);
                const float var = bf16r(fmaxf(fmaf(-m1, m1, m2 * (1.0f / DM)), 0.f));
                const float den = bf16r(sqrt_approx(bf16r(var + 1e-5f)));
                if (is_f) {
                    sts64f(sb + SM_MOM + b * 8, nmean, den, lane == 0);
                    CK(5, 0);
                    fin_arrive<4>();
                } else {
                    const float rden = rcp_approx(den);
                    if (lb == b) { nmean_l = nmean; rden_l = rden; }
                    __syncwarp();
                    const float2 hw2 = lds64f(sb + SM_X + lb * HPITCH + ((fidx >> 1) * 16 + (lc & 6) * 2 + (fidx & 1) * 2) * 4);
                    const float nh0 = (lc & 1) ? hi_f(__float_as_uint(hw2.x)) : lo_f(__float_as_uint(hw2.x));
                    const float nh1 = (lc & 1) ? hi_f(__float_as_uint(hw2.y)) : lo_f(__float_as_uint(hw2.y));
                    float rr = 0.f;
#pragma unroll
                    for (int i = 0; i < 10; i++) rr = fmaf(lo_f(hw[i]), lo_f(wr[i]), fmaf(hi_f(hw[i]), hi_f(wr[i]), rr));
                    const float sig = bf16r(sigmoid_approx(bf16r((nmean * wsum - warp_sum(rr)) * rden)));
                    if (lb == b) sig_l = sig;
                    const float ln0 = bf16r(bf16r(nmean_l - nh0) * rden_l), ln1 = bf16r(bf16r(nmean_l - nh1) * rden_l);
                    fin_sync<6>(after(after(after(288, sig_l), ln0), ln1));
                    CK(10, lds32(ypart));
                    float2 t[16];
#pragma unroll
                    for (int i = 0; i < 16; i++) t[i] = lds64f(ypart + i * YPITCH);
#pragma unroll
                    for (int o = 1; o < 16; o <<= 1) {
#pragma unroll
                        for (int i = 0; i < 16; i += 2 * o) { t[i].x += t[i + o].x; t[i].y += t[i + o].y; }
                    }
                    const uint32_t ov = pack_bf16(bf16r(ln0 + bf16r(bf16r(-t[0].x) * sig_l)) - nh0, bf16r(ln1 + bf16r(bf16r(-t[0].y) * sig_l)) - nh1);
                    asm volatile("{\n.reg .pred p;\n.reg .b16 lo, hi;\nsetp.eq.u32 p, %2, 3;\nmov.b32 {lo, hi}, %1;\n"
                                 "@p st.global.u16 [%0], lo;\n@p st.global.u16 [%0 + 16], hi;\n}" :: "l"(out), "r"(ov), "r"(b) : "memory");
                    CK(11, 0);
                    if (lane == 0) TS2(13);
                }
                if (b < NB - 1) fin_sync<5>();
            }
            if (cta == 0 && lane == 0) { g_work[0] = 0; g_cnt_z[0] = 0; }
        }
        return;
    }
    if (warp >= NAUX) {
        const int wk = warp - NAUX;
        const uint32_t bar = sb + BAR_KV + wk * 8;
        const uint32_t buf = sb + SM_KV + wk * TILE_BYTES;
        uint64_t pol;
        asm volatile("createpolicy.fractional.L2::evict_first.b64 %0, 1.0;" : "=l"(pol));
        const int nstatic = NWORK * grid;
        constexpr int POOL0 = NUNITS - NPOOL;
        int uk = wk * grid + cta;
        if (lane == 0) {
            spin_ns(K0_DELAY_NS + wk * K0_STEP_NS + cta * K0_SPREAD);
            mbar_expect_tx(bar, TILE_BYTES);
            tma_tile(buf, &p.k, tile_of(uk), bar, pol);
        }
        __syncwarp();
        uint32_t koff[3], voff[3];
        {
            const int r = lane & 7, hf = (lane >> 3) & 1;
            const int kkey = hf ? 8 + (r ^ 1) : r;
            const int vh = lane >> 4;
            const int vkey = ((r & 1) ? 8 : 0) + (vh ? (r ^ 1) : r);
#pragma unroll
            for (int b = 0; b < 3; b++) {
                const int rk = 3 * kkey + b, rv = 3 * vkey + b;
                koff[b] = buf + rk * 128 + (((lane >> 4) ^ (rk & 7)) << 4);
                voff[b] = buf + rv * 128 + ((hf ^ (rv & 7)) << 4);
            }
        }
        uint32_t phase = 0;
        uint4 qf[6];
        auto load_q = [&](int u) {
            const uint32_t* q = &g_early[row_of(u)].q[j * 4];
#pragma unroll
            for (int i = 0; i < 6; i++) qf[i] = ld_relaxed_v4(q + i * 16);
        };
        load_q(uk);
        int uq[LAG];
        uint32_t sq[LAG];
#pragma unroll
        for (int i = 0; i < LAG; i++) { uq[i] = -1; sq[i] = 0; }
        uint4 mv = make_uint4(0u, 0u, 0u, 0u);
        uint32_t svp = 0;
        float freed = UPB;
        while (true) {
            const int uv = uq[0];
            uint32_t sv = sq[0];
#pragma unroll
            for (int i = 0; i + 1 < LAG; i++) { uq[i] = uq[i + 1]; sq[i] = sq[i + 1]; }
            uq[LAG - 1] = uk;
            if (uk < NUNITS) {
                PH(7);
#pragma unroll 1
                for (int it = 0; it < SPIN_MAX; it++) {
                    uint32_t lo = 0xffffffffu;
#pragma unroll
                    for (int i = 0; i < 6; i++) lo = min(min(lo, min(qf[i].x, qf[i].y)), min(qf[i].z, qf[i].w));
                    if (__all_sync(0xffffffffu, lo != 0)) break;
                    __nanosleep(QNAP);
                    load_q(uk);
                }
                mbar_wait(bar, phase); phase ^= 1;
                PH(0); ARR();
                TSI(0, 16); TSI(1, 18);
                float acc[2][4][4] = {};
#pragma unroll
                for (int ks = 0; ks < 12; ks++) {
                    const uint4 qq = qf[ks >> 1];
                    const uint32_t b0 = (ks & 1) ? qq.z : qq.x, b1 = (ks & 1) ? qq.w : qq.y;
#pragma unroll
                    for (int mt = 0; mt < 4; mt++) {
                        uint32_t a[4];
                        ldsm4(a, (koff[ks >> 2] ^ ((ks & 3) << 5)) + mt * 6144);
                        mma16816(acc[ks & 1][mt], a, b0, b1);
                    }
                }
                PH(1);
                TSI(0, 17); TSI(1, 19);
                if (uv < NUNITS) request_tile(buf, uv >= 0 ? &p.v : &p.k, uv >= 0 ? uv : uk + nstatic, bar, pol);
                const float sa = sel4(j, acc[0][0][0], acc[0][1][0], acc[0][2][0], acc[0][3][0]) + sel4(j, acc[1][0][0], acc[1][1][0], acc[1][2][0], acc[1][3][0]);
                const float sc = sel4(j, acc[0][0][2], acc[0][1][2], acc[0][2][2], acc[0][3][2]) + sel4(j, acc[1][0][2], acc[1][1][2], acc[1][2][2], acc[1][3][2]);
                const uint32_t raw = pack_bf16(sa, sc);
                const float scale = -0.07216878364870322f;
                const uint32_t sk = pack_bf16(lo_f(raw) * scale, hi_f(raw) * scale);
                sq[LAG - 1] = sk;
                if (uk >= POOL0) st_relaxed(&g_st.score[uk - POOL0][lane], sk ? sk : 0x80008000u);
                int a = (int)(sk << 16), b = (int)(sk & 0xffff0000u);
                a ^= (a >> 31) & 0x7fff0000; b ^= (b >> 31) & 0x7fff0000;
                const int mx = __reduce_max_sync(0xffffffffu, max(a, b));
                if (lane == 0) st_relaxed(&g_early[row_of(uk)].umax[pos_of(uk)], (uint32_t)mx | 1u);
            }
            if (uv < 0) {
                uk += nstatic;
                load_q(uk);
                continue;
            }
            if (uv >= NUNITS) break;
            const int bh = row_of(uv);
#pragma unroll 1
            for (int it = 0; it < SPIN_MAX; it++) {
                if (__all_sync(0xffffffffu, (mv.x & mv.y & mv.z & mv.w & 1u) && (uv < POOL0 || svp != 0) && freed == UPB)) break;
                mv = ld_relaxed_v4(&g_early[bh].umax[lane * 4]);
                if (bh >= RING && bh < RED0) freed = __uint_as_float(ld_relaxed_u32(&g_st.oacc[bh - RING][(lane & 7) * 8].w));
                if (uv >= POOL0) svp = ld_relaxed_u32(&g_st.score[uv - POOL0][lane]);
            }
            if (uv >= POOL0) sv = svp;
            PH(2);
            int un = NUNITS, vn = 0;
            draw(un, g_work, uk < NUNITS && lane == 0);
            int mx = __reduce_max_sync(0xffffffffu, max(max((int)mv.x, (int)mv.y), max((int)mv.z, (int)mv.w))) & 0xffff0000;
            mx ^= (mx >> 31) & 0x7fff0000;
            const float m = __int_as_float(mx);
            const float l2e = 1.4426950408889634f;
            const uint32_t pp = pack_bf16(exp2f((lo_f(sv) - m) * l2e), exp2f((hi_f(sv) - m) * l2e));
            uint32_t pb[8];
#pragma unroll
            for (int t = 0; t < 4; t++) {
                pb[2 * t] = __shfl_sync(0xffffffffu, pp, 8 * j + t);
                pb[2 * t + 1] = __shfl_sync(0xffffffffu, pp, 8 * j + 4 + t);
            }
            float lacc[4] = {};
            const uint32_t ones[4] = {0x3f803f80u, 0x3f803f80u, 0x3f803f80u, 0x3f803f80u};
#pragma unroll
            for (int t = 0; t < 4; t++) mma16816(lacc, ones, pb[2 * t], pb[2 * t + 1]);
            if (uv < nstatic) {
                asm volatile("bar.sync 2, %0;" :: "n"((NWORK + 1) * 32) : "memory");
                TSW(3);
            }
            const int grp = 16 * j + 4 * (g & 1) + (g >> 1);
            const int acc_row = bh >= NBH - 4 ? bh + 4 * (pos_of(uv) % OREP) : bh;
            float4* dst = bh < RED0 ? &g_ring[bh % RING][pos_of(uv)][grp] : oacc_at(FARFIRST ? lds32(sb + SM_SIDE) ^ 1 : 0, acc_row, grp);
            float4* dst2 = other_side(dst);
            float2* ldst = lsum_at(lane & 1, acc_row);
            if (bh >= SROW0 && lane < 2) red_f2(&ldst->x, lacc[0], 1.f);
            float tag = bh < RED0 ? (float)(bh + 1) : 1.f;
            un = __shfl_sync(0xffffffffu, un, 0) + (LAG + 1) * nstatic;
            uint32_t pooled = uq[0] >= POOL0 && lane == 0;
            pin(dst); pin(dst2); pin(ldst); pin(tag); pin(voff[0]); pin(voff[1]); pin(voff[2]); pin(pooled);
            PH(3);
            LT(1);
            mbar_wait(bar, phase); phase ^= 1;
            PH(4); ARR();
            LT(2);
            draw(vn, g_st.pool, pooled);
            float acc[12][4] = {};
#pragma unroll
            for (int t = 0; t < 4; t++) {
#pragma unroll
                for (int mt = 0; mt < 12; mt++) {
                    uint32_t a[4];
                    ldsm4t(a, (voff[mt >> 2] ^ ((mt & 3) << 5)) + t * 6144);
                    mma16816(acc[mt], a, pb[2 * t], pb[2 * t + 1]);
                }
            }
            PH(5);
            if (lane == 0) PROG(un);
            if (un < NUNITS) request_tile(buf, &p.k, un, bar, pol);
            float o[6];
#pragma unroll
            for (int e = 0; e < 6; e++) {
                const int q = e % 3, c = (e / 3) * 2;
                o[e] = sel4(j, acc[q][c], acc[3 + q][c], acc[6 + q][c], acc[9 + q][c]);
            }
            if (bh >= SROW0) {
                red_f4(&dst->x, o[0], o[1], o[2], tag);
                red_f4(&dst[16].x, o[3], o[4], o[5], tag);
                red_f4(&dst2->x, o[0], o[1], o[2], tag);
                red_f4(&dst2[16].x, o[3], o[4], o[5], tag);
            } else {
                if (bh >= RED0) {
                    red_f4(&dst->x, o[0], o[1], o[2], tag);
                    red_f4(&dst[8].x, o[3], o[4], o[5], tag);
                } else {
                    st_relaxed_b128(dst, o[0], o[1], o[2], tag);
                    st_relaxed_b128(dst + 8, o[3], o[4], o[5], tag);
                }
                if (lane == 0) red_f2(&ldst->x, lacc[0], 1.f);
            }
            if (uq[0] >= POOL0) {
                vn = __shfl_sync(0xffffffffu, vn, 0);
                uq[0] = POOL0 + vn;
                if (vn == VTRIG && lane == 0) st_relaxed(g_st.tstart, (now_ns() + TRIG_NS) | 1u);
            }
            if (un < NUNITS) load_q(un);
            PH(6);
            if (uq[0] >= NUNITS && un >= NUNITS) break;
            uk = un;
            if (uq[0] < NUNITS) {
                const int nb = row_of(uq[0]);
                mv = ld_relaxed_v4(&g_early[nb].umax[lane * 4]);
                freed = nb >= RING && nb < RED0 ? __uint_as_float(ld_relaxed_u32(&g_st.oacc[nb - RING][(lane & 7) * 8].w)) : UPB;
                if (uq[0] >= POOL0) svp = ld_relaxed_u32(&g_st.score[uq[0] - POOL0][lane]);
                if (un >= NUNITS) {
                    request_tile(buf, &p.v, uq[0], bar, pol);
                    LT(0);
                }
            }
        }
        if (WBAR && is_f) asm volatile("bar.arrive 10, %0;" :: "n"((NAUX + NWORK) * 32) : "memory");
        return;
    }

    __nv_bfloat16* xs = reinterpret_cast<__nv_bfloat16*>(smem + SM_X);
    float* red = reinterpret_cast<float*>(smem + SM_RED);
    const int frow = (lane & 7) + ((lane >> 4) << 3), fcol = (lane >> 3) & 1;
    if (cta < NQ_CTAS) {
        uint2 xr[5];
        if (warp < NB) {
#pragma unroll
            for (int i = 0; i < 5; i++) xr[i] = *reinterpret_cast<const uint2*>(p.x + warp * DM + i * 128 + lane * 4);
        }
        TS(26);
        if (warp < NB) {
            float v[20];
#pragma unroll
            for (int i = 0; i < 5; i++) {
                v[4 * i] = lo_f(xr[i].x); v[4 * i + 1] = hi_f(xr[i].x); v[4 * i + 2] = lo_f(xr[i].y); v[4 * i + 3] = hi_f(xr[i].y);
            }
            layernorm20(v);
#pragma unroll
            for (int i = 0; i < 5; i++)
                *reinterpret_cast<uint2*>(xs + warp * XPITCH + i * 128 + lane * 4) =
                    make_uint2(pack_bf16(v[4 * i], v[4 * i + 1]), pack_bf16(v[4 * i + 2], v[4 * i + 3]));
        }
        TS(27);
#pragma unroll 1
        for (int pass = QREH ? 0 : 1; pass < 2; pass++) {
        aux_sync();
        if (pass) mbar_wait(sb + BAR_WQ, 0);
        TS(1);
        const uint32_t xfrag = sb + SM_X + ((g & 3) * XPITCH + 2 * j) * 2;
        float acc[3][4] = {};
#pragma unroll
        for (int s = 0; s < 5; s++) {
            const int ks = warp * 5 + s;
            const uint32_t b0 = lds32(xfrag + ks * 32), b1 = lds32(xfrag + ks * 32 + 16);
            const int row = ks * 16 + frow;
#pragma unroll
            for (int mt = 0; mt < 3; mt++) {
                uint32_t a[4];
                ldsm4t(a, sb + SM_WQ + (row * 6 + 2 * mt + fcol) * 16);
                mma16816(acc[mt], a, b0, b1);
            }
        }
        if (j < 2) {
#pragma unroll
            for (int mt = 0; mt < 3; mt++) {
                *reinterpret_cast<float2*>(red + (warp * 48 + mt * 16 + g) * 4 + 2 * j) = make_float2(acc[mt][0], acc[mt][1]);
                *reinterpret_cast<float2*>(red + (warp * 48 + mt * 16 + 8 + g) * 4 + 2 * j) = make_float2(acc[mt][2], acc[mt][3]);
            }
        }
        aux_sync();
        if (tid < 96) {
            const int b = tid & 3, cp = tid >> 2;
            float s0 = 0.f, s1 = 0.f;
#pragma unroll
            for (int w = 0; w < 8; w++) { s0 += red[(w * 48 + 2 * cp) * 4 + b]; s1 += red[(w * 48 + 2 * cp + 1) * 4 + b]; }
            const int h = cta >> 2, d = (cta & 3) * 48 + 2 * cp;
            const int ch = d >> 3, jj = (d & 7) >> 1;
            asm volatile("{\n.reg .pred p;\nsetp.ne.u32 p, %2, 0;\n@p st.relaxed.gpu.global.u32 [%0], %1;\n}"
                         :: "l"(&g_early[b * NH + h].q[(ch >> 2) * 16 + jj * 4 + (ch & 3)]), "r"(pack_neg(s0, s1)), "r"(pass) : "memory");
        }
        }
        TS(28);
    }
    if (tid < 160) *reinterpret_cast<uint2*>(smem + SM_X + 4 * HPITCH + tid * 8) = make_uint2(0x3f803f80u, 0x3f803f80u);
    fin_sync<3>();
    const int side = lds32(sb + SM_SIDE);
    mbar_wait(sb + BAR_W, 0);
    TS(7);
    uint32_t part = sb + SM_RED + (warp * 32 + 8 * j + g) * 4;

#pragma unroll 1
    for (int b = 0; b < NB; b++) {
        if (b == NB - 1 && (is_f || is_g)) asm volatile("bar.arrive 9, 288;" ::: "memory");
        if (is_l) {
            uint32_t a[6][2][4];
#pragma unroll
            for (int s = 0; s < 6; s++) {
                const int row = (warp * 6 + s) * 16 + frow;
#pragma unroll
                for (int mt = 0; mt < 2; mt++) ldsm4t(a[s][mt], sb + SM_A + (row * 4 + ((2 * mt + fcol) ^ ((row >> 1) & 3))) * 16);
            }
            const int bh = b * NH + 28 + (warp >> 1);
            const float4* osrc[OREP];
            const float2* lsrc[OREP];
#pragma unroll
            for (int c = 0; c < OREP; c++) {
                const int row = b == NB - 1 ? bh + 4 * c : bh;
                osrc[c] = oacc_at(side, row, (warp & 1) * 32 + lane);
                lsrc[c] = lsum_at(side, row);
                pin(osrc[c]); pin(lsrc[c]);
            }
            if (lane == 0) wait_row_o(side, bh, 1);
            __syncwarp();
            float2 lv;
#pragma unroll 1
            for (int it = 0; it < SPIN_MAX; it++) {
                lv = ld_relaxed_f2(lsrc[0]);
#pragma unroll
                for (int c = 1; c < OREP; c++) {
                    const float2 lc = ld_relaxed_f2(lsrc[c]);
                    if (b == NB - 1) { lv.x += lc.x; lv.y += lc.y; }
                }
                if (__all_sync(0xffffffffu, lv.y == UPB)) break;
            }
            if (warp == 7) TSW(25);
            float rl = rcp_approx(lv.x);
            float4 ov;
            pin(part); pin(rl);
            if (OPRE && lane == 0) {
#pragma unroll 1
                for (int it = 0; it < SPIN_MAX; it++) {
                    if (__uint_as_float(ld_relaxed_u32(&osrc[0]->w)) >= UPB * OPRE / (16 * OREP)) break;
                    if (ONAP) __nanosleep(ONAP);
                }
            }
            __syncwarp();
#pragma unroll 1
            for (int it = 0;; it++) {
                float4 oc[OREP];
#pragma unroll
                for (int c = 0; c < OREP; c++) oc[c] = ld_relaxed_f4(osrc[c]);
                ov = oc[0];
                if (b == NB - 1) {
#pragma unroll
                    for (int c = 1; c < OREP; c++) { ov.x += oc[c].x; ov.y += oc[c].y; ov.z += oc[c].z; ov.w += oc[c].w; }
                }
                if (__all_sync(0xffffffffu, ov.w == UPB || it == SPIN_MAX)) break;
            }
            CK(0, __float_as_uint(ov.x));
            const float px = __shfl_xor_sync(0xffffffffu, ov.x, 4), py = __shfl_xor_sync(0xffffffffu, ov.y, 4),
                        pz = __shfl_xor_sync(0xffffffffu, ov.z, 4);
            const uint32_t w[3] = {pack_bf16(ov.x * rl, px * rl), pack_bf16(ov.y * rl, py * rl), pack_bf16(ov.z * rl, pz * rl)};
            float acc[2][2][4] = {};
#pragma unroll
            for (int s = 0; s < 6; s++) {
                const uint32_t b0 = __shfl_sync(0xffffffffu, w[s % 3], (s / 3) * 16 + j);
                const uint32_t b1 = __shfl_sync(0xffffffffu, w[s % 3], (s / 3) * 16 + 8 + j);
#pragma unroll
                for (int mt = 0; mt < 2; mt++) mma16816(acc[mt][s & 1], a[s][mt], b0, b1);
            }
            sts32f(part, sel4(j, acc[0][0][0] + acc[0][1][0], acc[0][0][2] + acc[0][1][2], acc[1][0][0] + acc[1][1][0], acc[1][0][2] + acc[1][1][2]));
            CK(1, 0);
            fin_arrive<4>();
            if (warp == 7) TSW(30);
            if (warp == 5) TSW(31);
            if (cta == NE_CTAS && lane < 28) reinterpret_cast<uint4*>(&g_early[bh])[(warp & 1) * 28 + lane] = make_uint4(0u, 0u, 0u, 0u);
            fin_sync<5>();
            continue;
        }
        {
            const int bh = b * NH + (cta >> 2);
            if (tid == 0) wait_row_o(side, bh, UPB);
            aux_sync();
            if (warp < 5) {
                uint32_t ob[12][2];
                load_o<4>(ob, bh, 0, j);
                float acc[2][2][4] = {};
#pragma unroll
                for (int ks = 0; ks < 12; ks++) {
                    const int row = ks * 16 + frow;
#pragma unroll
                    for (int mt = 0; mt < 2; mt++) {
                        uint32_t a[4];
                        ldsm4t(a, sb + SM_A + warp * 12288 + (row * 4 + ((2 * mt + fcol) ^ ((row >> 1) & 3))) * 16);
                        mma16816(acc[mt][ks & 1], a, ob[ks][0], ob[ks][1]);
                    }
                }
                red_f2(&g_st.attn[b][(cta & 3) * 160 + warp * 32 + 8 * j + g].x,
                       sel4(j, acc[0][0][0] + acc[0][1][0], acc[0][0][2] + acc[0][1][2], acc[1][0][0] + acc[1][1][0], acc[1][0][2] + acc[1][1][2]), 1.f);
                TS(8);
            } else if (warp > 5 && (cta & 3) == 0 && tid - 192 < 56) {
                reinterpret_cast<uint4*>(&g_early[bh])[tid - 192] = make_uint4(0u, 0u, 0u, 0u);
            }
        }
        if (is_f) {
            const int kq = warp >> 1, tp = warp & 1;
            uint32_t hfrag = sb + SM_X + min(g, 4) * HPITCH + (kq * 80 + 4 * j) * 4;
            uint4 hv[5] = {};
#pragma unroll
            for (int s = 0; s < 5; s++) lds128_if(hv[s], hfrag + s * 64, true);
            if (WBAR && b == NB - 1) asm volatile("bar.sync 10, %0;" :: "n"((NAUX + NWORK) * 32) : "memory");
            uint32_t ga[10][2][4];
#pragma unroll
            for (int s = 0; s < 10; s++) {
                if (s % 5 == 0 && b == NB - 1) mbar_wait(sb + BAR_G + (kq * 2 + s / 5) * 8, 0);
                const int row = (kq * 10 + s) * 16 + frow;
#pragma unroll
                for (int t = 0; t < 2; t++) ldsm4t(ga[s][t], sb + SM_G + fcol * 40960 + (row * 4 + ((2 * tp + t) ^ ((row >> 1) & 3))) * 16);
            }
            if (warp == NAUX - 1) TSW(9);
            uint32_t fpart = sb + SM_RED + 2 * j * FPITCH + warp * 128 + g * 16;
            uint32_t dsum = sb + SM_RED + (lane >> 3) * FPITCH + tp * 128 + (lane & 7) * 16, csum = sb + SM_RED + 4 * FPITCH + tp * 128 + (lane & 7) * 16;
            uint32_t mom = sb + SM_MOM + (lane >> 3) * 8;
            uint32_t* dst = sided<uint32_t>(side ^ 1, X_A + (2 * fidx + tp) * 128 + (lane ^ 2 * tp) * 4);
            pin(fpart); pin(hfrag); pin(dsum); pin(csum); pin(mom); pin(dst);
            fin_sync<7>();
#pragma unroll
            for (int s = 0; s < 5; s++) lds128_if(hv[s], hfrag + s * 64, g == b);
            float acc[2][2][4] = {};
#pragma unroll
            for (int s = 0; s < 5; s++) {
#pragma unroll
                for (int t = 0; t < 2; t++) mma16816(acc[t][0], ga[2 * s][t], hv[s].x, hv[s].y);
#pragma unroll
                for (int t = 0; t < 2; t++) mma16816(acc[t][1], ga[2 * s + 1][t], hv[s].z, hv[s].w);
            }
#pragma unroll
            for (int e = 0; e < 2; e++)
                sts128f(fpart + e * FPITCH, acc[0][0][e] + acc[0][1][e], acc[0][0][2 + e] + acc[0][1][2 + e],
                        acc[1][0][e] + acc[1][1][e], acc[1][0][2 + e] + acc[1][1][2 + e], 2 * j + e < 5);
            CK(5, 0);
            if (warp < 2) {
                fin_sync<4>();
                CK(6, lds32(dsum));
                float2 m = lds64f(mom);
                m.y = rcp_approx(m.y);
                const float4 d = sum4x4(dsum), cs = sum4x4(csum);
                const float g0 = bf16r(fmaf(m.x, cs.x, -d.x) * m.y), g1 = bf16r(fmaf(m.x, cs.z, -d.z) * m.y);
                const float u0 = bf16r(fmaf(m.x, cs.y, -d.y) * m.y), u1 = bf16r(fmaf(m.x, cs.w, -d.w) * m.y);
                const uint32_t av = pack_neg(bf16r(g0 * sigmoid_approx(g0)) * u0, bf16r(g1 * sigmoid_approx(g1)) * u1);
                asm volatile("{\n.reg .pred p;\nsetp.eq.u32 p, %3, 3;\n@p st.relaxed.gpu.global.u32 [%0], %2;\n@p st.relaxed.gpu.global.u32 [%1], %2;\n}"
                             :: "l"(dst), "l"(other_side(dst)), "r"(av), "r"(b) : "memory");
                CK(7, 0);
                TS(14);
            } else {
                fin_arrive<4>();
            }
        } else if (is_g) {
            if (GEARLY) fin_sync<7>();
            if (b == NB - 1) {
                mbar_wait(sb + BAR_G + warp * 8, 0);
                if (warp == NAUX - 1) TSW(10);
            }
            uint32_t wb[3][2][2][4];
#pragma unroll
            for (int s = 0; s < 12; s++) {
                const int odd = (lane >> 2) & 1, c = ((lane & 2) * 2 + (s & 1) * 2 + (lane >> 4)) ^ (2 * odd);
                const int row = (warp * 12 + (s >> 1) * 2 + odd) * 16 + (lane & 1) * 8 + c;
                ldsm4t(wb[s >> 2][(s >> 1) & 1][s & 1], sb + SM_G + (row * 2 + (fcol ^ ((row >> 2) & 1))) * 16);
            }
            const uint4* asrc[3];
#pragma unroll
            for (int q = 0; q < 3; q++) {
                asrc[q] = sided<uint4>(side, X_A + (warp * 12 + 4 * q + 2 * (g >> 2) + (j >> 1)) * 128 + (g & 3) * 32 + (j & 1) * 16);
                pin(asrc[q]);
            }
            uint32_t ypart = sb + SM_RED2 + (warp * 2 + (j >> 1)) * YPITCH + (j & 1) * 160 + g * 16;
            pin(ypart);
            if (!GEARLY) fin_sync<7>();
            if (GDLY) wait_clk(lds32(sb + SM_MOM) + GDLY);
            uint4 v[3] = {};
            uint32_t mq[3] = {};
#pragma unroll 1
            for (int it = b < NB - 1 ? SPIN_MAX : 0;; it++) {
                asm volatile("{\n.reg .pred p0, p1, p2;\nsetp.eq.u32 p0, %15, 0;\nsetp.eq.u32 p1, %16, 0;\nsetp.eq.u32 p2, %17, 0;\n"
                             "@p0 ld.relaxed.gpu.global.v4.u32 {%0,%1,%2,%3}, [%12];\n"
                             "@p1 ld.relaxed.gpu.global.v4.u32 {%4,%5,%6,%7}, [%13];\n"
                             "@p2 ld.relaxed.gpu.global.v4.u32 {%8,%9,%10,%11}, [%14];\n}"
                             : "+r"(v[0].x), "+r"(v[0].y), "+r"(v[0].z), "+r"(v[0].w), "+r"(v[1].x), "+r"(v[1].y), "+r"(v[1].z), "+r"(v[1].w),
                               "+r"(v[2].x), "+r"(v[2].y), "+r"(v[2].z), "+r"(v[2].w)
                             : "l"(asrc[0]), "l"(asrc[1]), "l"(asrc[2]), "r"(mq[0]), "r"(mq[1]), "r"(mq[2]) : "memory");
#pragma unroll
                for (int q = 0; q < 3; q++) mq[q] = min(min(v[q].x, v[q].y), min(v[q].z, v[q].w));
                const uint32_t lo = min(min(mq[0], mq[1]), mq[2]);
                if (__all_sync(0xffffffffu, lo != 0 || it == SPIN_MAX)) break;
            }
            CK(8, v[0].x);
            float acc[2][2][4] = {};
#pragma unroll
            for (int q = 0; q < 3; q++) {
#pragma unroll
                for (int pr = 0; pr < 2; pr++) {
                    mma16816(acc[pr][0], wb[q][pr][0], v[q].x, v[q].y);
                    mma16816(acc[pr][1], wb[q][pr][1], v[q].z, v[q].w);
                }
            }
            float y[4];
#pragma unroll
            for (int e = 0; e < 4; e++) y[e] = j < 2 ? acc[0][0][e] + acc[0][1][e] : acc[1][0][e] + acc[1][1][e];
            asm volatile("st.shared.v4.f32 [%0], {%1,%2,%3,%4};" :: "r"(ypart), "f"(y[0]), "f"(y[2]), "f"(y[1]), "f"(y[3]) : "memory");
            CK(9, 0);
            fin_arrive<6>();
        } else {
            continue;
        }
        if (b < NB - 1) fin_sync<5>();
    }
}

typedef CUresult (*EncodeFn)(CUtensorMap*, CUtensorMapDataType, cuuint32_t, void*, const cuuint64_t*, const cuuint64_t*,
                             const cuuint32_t*, const cuuint32_t*, CUtensorMapInterleave, CUtensorMapSwizzle,
                             CUtensorMapL2promotion, CUtensorMapFloatOOBfill);

CUtensorMap make_map(EncodeFn enc, void* ptr, uint64_t cols, uint64_t rows, uint32_t bcols, uint32_t brows,
                     CUtensorMapSwizzle sw, CUtensorMapL2promotion promo) {
    CUtensorMap m;
    const cuuint64_t dims[2] = {cols, rows};
    const cuuint64_t strides[1] = {cols * 2};
    const cuuint32_t box[2] = {bcols, brows};
    const cuuint32_t es[2] = {1, 1};
    enc(&m, CU_TENSOR_MAP_DATA_TYPE_BFLOAT16, 2, ptr, dims, strides, box, es, CU_TENSOR_MAP_INTERLEAVE_NONE, sw, promo,
        CU_TENSOR_MAP_FLOAT_OOB_FILL_NONE);
    return m;
}

}

extern "C" void kernel_launch(void* const* d_in, const int* in_sizes, int n_in, void* d_out, int out_size) {
    (void)in_sizes; (void)n_in; (void)out_size;
    static EncodeFn enc = nullptr;
    static int sms = 0;
    if (!enc) {
        cudaDriverEntryPointQueryResult qr;
        cudaGetDriverEntryPoint("cuTensorMapEncodeTiled", (void**)&enc, cudaEnableDefault, &qr);
        int dev = 0;
        cudaGetDevice(&dev);
        cudaDeviceGetAttribute(&sms, cudaDevAttrMultiProcessorCount, dev);
        cudaFuncSetAttribute(fused_decode_kernel, cudaFuncAttributeMaxDynamicSharedMemorySize, SM_TOTAL);
    }
    if (sms < NCTAS) return;
    const CUtensorMapL2promotion WPROMO = CU_TENSOR_MAP_L2_PROMOTION_L2_128B;
    Params p;
    p.k = make_map(enc, d_in[1], 64, (uint64_t)NBH * SK * 3, 64, TILE_ROWS, CU_TENSOR_MAP_SWIZZLE_128B, CU_TENSOR_MAP_L2_PROMOTION_NONE);
    p.v = make_map(enc, d_in[2], 64, (uint64_t)NBH * SK * 3, 64, TILE_ROWS, CU_TENSOR_MAP_SWIZZLE_128B, CU_TENSOR_MAP_L2_PROMOTION_NONE);
    p.wq = make_map(enc, d_in[3], NH * DH, DM, 48, 160, CU_TENSOR_MAP_SWIZZLE_NONE, WPROMO);
    p.wo = make_map(enc, d_in[4], DM, NH * DH, 32, WO_ROWS, CU_TENSOR_MAP_SWIZZLE_64B, WPROMO);
    p.wg = make_map(enc, d_in[7], FF, DM, 32, 80, CU_TENSOR_MAP_SWIZZLE_64B, (CUtensorMapL2promotion)GPROMO);
    p.wu = make_map(enc, d_in[8], FF, DM, 32, 80, CU_TENSOR_MAP_SWIZZLE_64B, (CUtensorMapL2promotion)GPROMO);
    p.wd = make_map(enc, d_in[9], DM, FF, 16, 192, CU_TENSOR_MAP_SWIZZLE_32B, WPROMO);
    p.wq_raw = (const char*)d_in[3];
    p.x = (const __nv_bfloat16*)d_in[0];
    p.wr = (const __nv_bfloat16*)d_in[6];
    p.out = (__nv_bfloat16*)d_out;
    fused_decode_kernel<<<NCTAS, NTHREADS, SM_TOTAL, cudaStreamPerThread>>>(p);
}
```

```cpp
#include <cuda_runtime.h>
#include <cuda_bf16.h>
#include <cuda.h>
#include <stdint.h>

namespace {

constexpr int NB = 4, NH = 32, SK = 8192, DH = 192, DM = 640, FF = 1536;
constexpr int NBH = NB * NH;
constexpr int TILE = 64;
constexpr int UPB = SK / TILE;
constexpr int NUNITS = NBH * UPB;
constexpr int TILE_BYTES = TILE * DH * 2;
constexpr int TILE_ROWS = TILE * 3;
constexpr int NCTAS = 132;
constexpr int NQ_CTAS = 128;
constexpr int NE_CTAS = 112;

constexpr int SROW0 = NBH - 4;

#define NWORK 2
#define NWL 2
#define SKEW 16
#define LAG 3
#define NPOOL 896
#define RED0 120
#define RING 12
#define K0_DELAY_NS 1600
#define K0_STEP_NS 900
#define WO_AT_NS 3600
#define WO_GAP_NS 550
#define VTRIG (NPOOL - 240)
#define TRIG_NS 2250
#define GCLK 250
#define DOFF 2300
#define DCLK 150
constexpr int NAUX = 8;
constexpr int NTHREADS = (NAUX + NWORK + 2) * 32;
constexpr int SPIN_MAX = 1 << 22;

constexpr int SM_KV = 0;
constexpr int SM_A = SM_KV + NWORK * TILE_BYTES;
constexpr int SM_WQ = SM_A + 61440;
constexpr int SM_G = SM_WQ;
constexpr int SM_X = SM_G + 81920;
constexpr int XPITCH = 648;
constexpr int HPITCH = 1344;
constexpr int SM_RED = SM_X + 5 * HPITCH;
constexpr int FPITCH = 1040;
constexpr int SM_RED2 = SM_RED;
constexpr int YPITCH = 320;
constexpr int SM_MISC = SM_RED + 6144;
constexpr int BAR_KV = SM_MISC, BAR_WQ = SM_MISC + 32, BAR_W = SM_MISC + 40, SM_SIDE = SM_MISC + 48, BAR_G = SM_MISC + 64, SM_MOM = SM_MISC + 128;
constexpr int SM_TOTAL = SM_MISC + 160;

struct Scratch;
struct Params {
    CUtensorMap k, v;
    CUtensorMap wq;
    CUtensorMap wo;
    CUtensorMap wg, wu;
    CUtensorMap wd;
    Scratch* scratch;
    const char* wq_raw;
    const __nv_bfloat16 *x, *wr;
    __nv_bfloat16* out;
};

struct Early {
    uint32_t q[96];
    uint32_t umax[UPB];
};
struct State {
    float4 oacc[SROW0][64];
    float2 attn[NB][DM];
    float2 lsum[SROW0][16];
    unsigned pool[64];
    uint32_t tstart[32];
    uint32_t score[NPOOL][32];
};
constexpr int STATE_V4 = ((sizeof(State) / 32 + NQ_CTAS - 1) / NQ_CTAS) * 2;
static_assert(sizeof(State) % 32 == 0, "State is cleared in whole sectors");
static_assert(sizeof(Early) == 56 * 16, "an Early entry is cleared by 56 threads");
constexpr uint32_t X_O = 0;
constexpr uint32_t X_L = X_O + 4 * 1024;
constexpr uint32_t X_H = X_L + 4 * 128;
constexpr uint32_t X_A = X_H + NB * DM * 2;
constexpr uint32_t X_P = X_A + NB * FF * 2;
constexpr uint32_t X_END = X_P + 4096;
static_assert(X_END <= 8 * 4096 && RED0 <= SROW0, "");
struct Scratch {
    unsigned char sided[8][2][4096];
    unsigned work[64];
    unsigned cnt_z[32];
    unsigned char pad0[1024];
    Early early[NBH];
    unsigned char pad1[1024];
    State st;
    unsigned char pad2[1792];
    float4 ring[RING][UPB][64];
};
constexpr size_t PAGE = 2u << 20;
static_assert(sizeof(Scratch) <= PAGE, "scratch must fit one page");
__device__ __align__(128) unsigned char g_raw[2 * PAGE];
template <typename T> __device__ __forceinline__ T* sided(const Params& p, int side, uint32_t x) {
    const uint32_t pair = (x >> 10) & 7;
    return reinterpret_cast<T*>(&p.scratch->sided[pair][(side ^ pair) & 1]
                                    [(x & 127) + ((x & 128) << 1) + ((x & 768) << 2) + ((x >> 6) & 128) + ((x >> 5) & 512)]);
}
template <typename T> __device__ __forceinline__ T* other_side(T* p) { return reinterpret_cast<T*>(reinterpret_cast<uintptr_t>(p) ^ 4096); }
#define g_early p.scratch->early
#define g_st p.scratch->st
#define g_ring p.scratch->ring
#define g_cnt_z p.scratch->cnt_z
#define g_work p.scratch->work
#define TS(i)
#define TSW(i)
#define TS2(i)
#define TSI(n, i)
#define PH(i)
#define CK(i, dep)
#define ARR()
#define PROG(u)
#define LT(i)

__device__ __forceinline__ int row_of(int u) { return (((unsigned)u >> (7 + NWL)) << NWL) | (u & ((1 << NWL) - 1)); }
__device__ __forceinline__ int pos_of(int u) { return ((unsigned)u >> NWL) & (UPB - 1); }
__device__ __forceinline__ int tile_of(int u) { return (row_of(u) * UPB + ((pos_of(u) + (u & ((1 << NWL) - 1)) * SKEW) & (UPB - 1))) * TILE_ROWS; }

__device__ __forceinline__ uint32_t s2u(const void* p) { return (uint32_t)__cvta_generic_to_shared(p); }
__device__ __forceinline__ void mbar_init(uint32_t bar, int cnt) {
    asm volatile("mbarrier.init.shared::cta.b64 [%0], %1;" :: "r"(bar), "r"(cnt) : "memory");
}
__device__ __forceinline__ void mbar_expect_tx(uint32_t bar, uint32_t bytes) {
    asm volatile("mbarrier.arrive.expect_tx.shared::cta.b64 _, [%0], %1;" :: "r"(bar), "r"(bytes) : "memory");
}
__device__ __forceinline__ void mbar_wait(uint32_t bar, uint32_t parity) {
    asm volatile("{\n.reg .pred p;\n.reg .u32 n;\nmov.u32 n, 0;\nWAIT_LOOP:\n"
                 "mbarrier.try_wait.parity.shared::cta.b64 p, [%0], %1;\n"
                 "@p bra WAIT_DONE;\nadd.u32 n, n, 1;\nsetp.lt.u32 p, n, %2;\n@p bra WAIT_LOOP;\nWAIT_DONE:\n}"
                 :: "r"(bar), "r"(parity), "n"(SPIN_MAX) : "memory");
}
__device__ __forceinline__ void request_tile(uint32_t dst, const CUtensorMap* tm, int unit, uint32_t bar, uint64_t pol) {
    asm volatile("{\n.reg .pred p;\nelect.sync _|p, 0xffffffff;\n"
                 "@p mbarrier.arrive.expect_tx.shared::cta.b64 _, [%2], %6;\n"
                 "@p cp.async.bulk.tensor.2d.shared::cluster.global.mbarrier::complete_tx::bytes.L2::cache_hint "
                 "[%0], [%1, {%3, %4}], [%2], %5;\n}"
                 :: "r"(dst), "l"(tm), "r"(bar), "r"(0), "r"(tile_of(unit)), "l"(pol), "n"(TILE_BYTES) : "memory");
}
__device__ __forceinline__ uint32_t now_ns() { uint32_t t; asm volatile("mov.u32 %0, %%globaltimer_lo;" : "=r"(t)); return t; }
__device__ __forceinline__ uint32_t now_clk() { uint32_t t; asm volatile("mov.u32 %0, %%clock;" : "=r"(t)); return t; }
__device__ __forceinline__ void wait_clk(uint32_t t) { while (__any_sync(0xffffffffu, (int)(now_clk() - t) < 0)) {} }
__device__ __forceinline__ uint64_t evict_first() {
    uint64_t pol;
    asm volatile("createpolicy.fractional.L2::evict_first.b64 %0, 1.0;" : "=l"(pol));
    return pol;
}
__device__ __forceinline__ void request_box(uint32_t dst, const CUtensorMap* tm, int col, int row, uint32_t bar) {
    asm volatile("{\n.reg .pred p;\nelect.sync _|p, 0xffffffff;\n"
                 "@p cp.async.bulk.tensor.2d.shared::cluster.global.mbarrier::complete_tx::bytes [%0], [%1, {%3, %4}], [%2];\n}"
                 :: "r"(dst), "l"(tm), "r"(bar), "r"(col), "r"(row) : "memory");
}
__device__ __forceinline__ void request_box(uint32_t dst, const CUtensorMap* tm, int col, int row, uint32_t bar, uint64_t pol) {
    asm volatile("{\n.reg .pred p;\nelect.sync _|p, 0xffffffff;\n"
                 "@p cp.async.bulk.tensor.2d.shared::cluster.global.mbarrier::complete_tx::bytes.L2::cache_hint [%0], [%1, {%3, %4}], [%2], %5;\n}"
                 :: "r"(dst), "l"(tm), "r"(bar), "r"(col), "r"(row), "l"(pol) : "memory");
}
__device__ __forceinline__ uint32_t lds32(uint32_t addr) {
    uint32_t v;
    asm volatile("ld.shared.u32 %0, [%1];" : "=r"(v) : "r"(addr) : "memory");
    return v;
}
__device__ __forceinline__ void ldsm4(uint32_t (&r)[4], uint32_t addr) {
    asm volatile("ldmatrix.sync.aligned.m8n8.x4.shared.b16 {%0,%1,%2,%3}, [%4];"
                 : "=r"(r[0]), "=r"(r[1]), "=r"(r[2]), "=r"(r[3]) : "r"(addr) : "memory");
}
__device__ __forceinline__ void ldsm4t(uint32_t (&r)[4], uint32_t addr) {
    asm volatile("ldmatrix.sync.aligned.m8n8.x4.trans.shared.b16 {%0,%1,%2,%3}, [%4];"
                 : "=r"(r[0]), "=r"(r[1]), "=r"(r[2]), "=r"(r[3]) : "r"(addr) : "memory");
}
__device__ __forceinline__ void mma16816(float (&c)[4], const uint32_t (&a)[4], uint32_t b0, uint32_t b1) {
    asm volatile("mma.sync.aligned.m16n8k16.row.col.f32.bf16.bf16.f32 {%0,%1,%2,%3}, {%4,%5,%6,%7}, {%8,%9}, {%0,%1,%2,%3};"
                 : "+f"(c[0]), "+f"(c[1]), "+f"(c[2]), "+f"(c[3])
                 : "r"(a[0]), "r"(a[1]), "r"(a[2]), "r"(a[3]), "r"(b0), "r"(b1));
}
__device__ __forceinline__ uint4 ld_relaxed_v4(const void* p) {
    uint4 v;
    asm volatile("ld.relaxed.gpu.global.v4.u32 {%0,%1,%2,%3}, [%4];" : "=r"(v.x), "=r"(v.y), "=r"(v.z), "=r"(v.w) : "l"(p) : "memory");
    return v;
}
__device__ __forceinline__ float4 ld_relaxed_f4(const void* p) {
    float4 v;
    asm volatile("ld.relaxed.gpu.global.v4.f32 {%0,%1,%2,%3}, [%4];" : "=f"(v.x), "=f"(v.y), "=f"(v.z), "=f"(v.w) : "l"(p) : "memory");
    return v;
}
__device__ __forceinline__ float2 ld_relaxed_f2(const void* p) {
    float2 v;
    asm volatile("ld.relaxed.gpu.global.v2.f32 {%0,%1}, [%2];" : "=f"(v.x), "=f"(v.y) : "l"(p) : "memory");
    return v;
}
__device__ __forceinline__ float4 ld_relaxed_b128(const void* p) {
    float4 v;
    asm volatile("{\n.reg .b128 t;\n.reg .b64 a, b;\nld.relaxed.gpu.global.b128 t, [%4];\nmov.b128 {a, b}, t;\n"
                 "mov.b64 {%0, %1}, a;\nmov.b64 {%2, %3}, b;\n}" : "=f"(v.x), "=f"(v.y), "=f"(v.z), "=f"(v.w) : "l"(p) : "memory");
    return v;
}
__device__ __forceinline__ void st_relaxed_b128(void* p, float x, float y, float z, float w) {
    asm volatile("{\n.reg .b128 t;\n.reg .b64 a, b;\nmov.b64 a, {%1, %2};\nmov.b64 b, {%3, %4};\nmov.b128 t, {a, b};\n"
                 "st.relaxed.gpu.global.b128 [%0], t;\n}" :: "l"(p), "f"(x), "f"(y), "f"(z), "f"(w) : "memory");
}
__device__ __forceinline__ unsigned ld_acquire(const unsigned* p) {
    unsigned v;
    asm volatile("ld.acquire.gpu.global.u32 %0, [%1];" : "=r"(v) : "l"(p) : "memory");
    return v;
}
__device__ __forceinline__ void st_relaxed(void* p, uint32_t v) {
    asm volatile("st.relaxed.gpu.global.u32 [%0], %1;" :: "l"(p), "r"(v) : "memory");
}
__device__ __forceinline__ void red_f2(float* p, float a, float b) {
    asm volatile("red.relaxed.gpu.global.add.v2.f32 [%0], {%1,%2};" :: "l"(p), "f"(a), "f"(b) : "memory");
}
__device__ __forceinline__ void red_f4(float* p, float a, float b, float c, float d) {
    asm volatile("red.relaxed.gpu.global.add.v4.f32 [%0], {%1,%2,%3,%4};" :: "l"(p), "f"(a), "f"(b), "f"(c), "f"(d) : "memory");
}
__device__ __forceinline__ void draw(int& ticket, unsigned* ctr, bool pred) {
    asm volatile("{\n.reg .pred p;\nsetp.ne.u32 p, %2, 0;\n@p atom.relaxed.gpu.global.inc.u32 %0, [%1], 0x7fffffff;\n}"
                 : "+r"(ticket) : "l"(ctr), "r"((uint32_t)pred) : "memory");
}
__device__ __forceinline__ void red_release(unsigned* p) {
    asm volatile("red.release.gpu.global.add.u32 [%0], 1;" :: "l"(p) : "memory");
}
__device__ __forceinline__ uint32_t ld_relaxed_u32(const void* p) {
    uint32_t v;
    asm volatile("ld.relaxed.gpu.global.u32 %0, [%1];" : "=r"(v) : "l"(p) : "memory");
    return v;
}
__device__ __forceinline__ float rcp_approx(float v) {
    float r;
    asm("rcp.approx.ftz.f32 %0, %1;" : "=f"(r) : "f"(v));
    return r;
}
__device__ __forceinline__ float sigmoid_approx(float v) {
    float e;
    asm("ex2.approx.ftz.f32 %0, %1;" : "=f"(e) : "f"(v * -1.4426950408889634f));
    return rcp_approx(1.0f + e);
}
__device__ __forceinline__ float sqrt_approx(float v) {
    float r;
    asm("sqrt.approx.ftz.f32 %0, %1;" : "=f"(r) : "f"(v));
    return r;
}
__device__ __forceinline__ uint2 ld_relaxed_v2(const void* p) {
    uint2 v;
    asm volatile("ld.relaxed.gpu.global.v2.u32 {%0,%1}, [%2];" : "=r"(v.x), "=r"(v.y) : "l"(p) : "memory");
    return v;
}
__device__ __forceinline__ void wait_count(const unsigned* p, unsigned target) {
#pragma unroll 1
    for (int it = 0; it < SPIN_MAX; it++) {
        if (ld_acquire(p) >= target) break;
        __nanosleep(400);
    }
}
__device__ __forceinline__ float4* oacc_at(const Params& p, int side, int row, int grp) {
    return row >= SROW0 ? sided<float4>(p, side, X_O + (row - SROW0) * 1024 + grp * 16) : &g_st.oacc[row][grp];
}
__device__ __forceinline__ float2* lsum_at(const Params& p, int side, int row) {
    return row >= SROW0 ? sided<float2>(p, side, X_L + (row - SROW0) * 128) : g_st.lsum[row];
}
__device__ __forceinline__ void wait_row(const Params& p, int side, int bh, float n) {
    const float2* l = lsum_at(p, side, bh);
#pragma unroll 1
    for (int it = 0; it < SPIN_MAX; it++) {
        const float c = ld_relaxed_f2(l).y;
        if (c >= n) break;
        if (c == 0.f) __nanosleep(600);
    }
}
__device__ __forceinline__ void wait_row_o(const Params& p, int side, int bh, float n) {
    wait_row(p, side, bh, n);
    if (bh >= RED0) return;
#pragma unroll 1
    for (int it = 0; it < SPIN_MAX; it++) {
        if (__uint_as_float(ld_relaxed_u32(&g_st.oacc[bh][0].w)) == UPB) break;
        __nanosleep(300);
    }
}
__device__ __forceinline__ uint32_t pack_bf16(float lo, float hi) {
    uint32_t r;
    asm("cvt.rn.bf16x2.f32 %0, %1, %2;" : "=r"(r) : "f"(hi), "f"(lo));
    return r;
}
__device__ __forceinline__ float bf16r(float v) { return __uint_as_float(pack_bf16(0.f, v)); }
__device__ __forceinline__ uint32_t pack_neg(float lo, float hi) {
    const uint32_t w = pack_bf16(-lo, -hi);
    return w ? w : 0x80008000u;
}
__device__ __forceinline__ float lo_f(uint32_t v) { return __uint_as_float(v << 16); }
__device__ __forceinline__ float hi_f(uint32_t v) { return __uint_as_float(v & 0xffff0000u); }
__device__ __forceinline__ float warp_sum(float v) {
#pragma unroll
    for (int o = 16; o; o >>= 1) v += __shfl_xor_sync(0xffffffffu, v, o);
    return v;
}
__device__ __forceinline__ void layernorm20(float (&v)[20]) {
    float s = 0.f;
#pragma unroll
    for (int i = 0; i < 20; i++) s += v[i];
    const float mean = warp_sum(s) * (1.0f / DM);
    float q = 0.f;
#pragma unroll
    for (int i = 0; i < 20; i++) { const float d = v[i] - mean; q += d * d; }
    const float var = bf16r(warp_sum(q) * (1.0f / DM));
    const float m = bf16r(mean);
    const float rden = 1.0f / bf16r(sqrtf(bf16r(var + 1e-5f)));
#pragma unroll
    for (int i = 0; i < 20; i++) v[i] = bf16r(bf16r(v[i] - m) * rden);
}

__device__ __forceinline__ float sel4(int j, float a, float b, float c, float d) {
    float lo, hi, r;
    asm("{\n.reg .pred p;\nsetp.ne.s32 p, %3, 0;\nselp.f32 %0, %2, %1, p;\n}" : "=f"(lo) : "f"(a), "f"(b), "r"(j & 1));
    asm("{\n.reg .pred p;\nsetp.ne.s32 p, %3, 0;\nselp.f32 %0, %2, %1, p;\n}" : "=f"(hi) : "f"(c), "f"(d), "r"(j & 1));
    asm("{\n.reg .pred p;\nsetp.ne.s32 p, %3, 0;\nselp.f32 %0, %2, %1, p;\n}" : "=f"(r) : "f"(lo), "f"(hi), "r"(j & 2));
    return r;
}
template <typename T> __device__ __forceinline__ void pin(T*& p) { asm volatile("" : "+l"(p)); }
__device__ __forceinline__ void pin(uint32_t& v) { asm volatile("" : "+r"(v)); }
__device__ __forceinline__ void pin(float& v) { asm volatile("" : "+f"(v)); }
__device__ __forceinline__ uint32_t after(uint32_t n, float v) {
    asm volatile("{\n.reg .pred p;\nsetp.eq.u32 p, %1, 0x7fc1a5a5;\n@p add.u32 %0, %0, 32;\n}" : "+r"(n) : "r"(__float_as_uint(v)));
    return n;
}
__device__ __forceinline__ float2 lds64f(uint32_t addr) {
    float2 v;
    asm volatile("ld.shared.v2.f32 {%0,%1}, [%2];" : "=f"(v.x), "=f"(v.y) : "r"(addr) : "memory");
    return v;
}
__device__ __forceinline__ float4 lds128f(uint32_t addr) {
    float4 v;
    asm volatile("ld.shared.v4.f32 {%0,%1,%2,%3}, [%4];" : "=f"(v.x), "=f"(v.y), "=f"(v.z), "=f"(v.w) : "r"(addr) : "memory");
    return v;
}
__device__ __forceinline__ void sts64f(uint32_t addr, float a, float b, bool pred) {
    asm volatile("{\n.reg .pred p;\nsetp.ne.u32 p, %3, 0;\n@p st.shared.v2.f32 [%0], {%1,%2};\n}" :: "r"(addr), "f"(a), "f"(b), "r"((uint32_t)pred) : "memory");
}
__device__ __forceinline__ void sts128f(uint32_t addr, float a, float b, float c, float d, bool pred) {
    asm volatile("{\n.reg .pred p;\nsetp.ne.u32 p, %5, 0;\n@p st.shared.v4.f32 [%0], {%1,%2,%3,%4};\n}"
                 :: "r"(addr), "f"(a), "f"(b), "f"(c), "f"(d), "r"((uint32_t)pred) : "memory");
}
__device__ __forceinline__ void lds128_if(uint4& v, uint32_t addr, bool pred) {
    asm volatile("{\n.reg .pred p;\nsetp.ne.u32 p, %5, 0;\n@p ld.shared.v4.u32 {%0,%1,%2,%3}, [%4];\n}"
                 : "+r"(v.x), "+r"(v.y), "+r"(v.z), "+r"(v.w) : "r"(addr), "r"((uint32_t)pred) : "memory");
}
__device__ __forceinline__ void sts32f(uint32_t addr, float v) { asm volatile("st.shared.f32 [%0], %1;" :: "r"(addr), "f"(v) : "memory"); }
template <int ID> __device__ __forceinline__ void fin_arrive() { asm volatile("bar.arrive %0, 288;" :: "n"(ID) : "memory"); }
template <int ID> __device__ __forceinline__ void fin_sync() { asm volatile("bar.sync %0, 288;" :: "n"(ID) : "memory"); }
template <int ID> __device__ __forceinline__ void fin_sync(uint32_t n) { asm volatile("bar.sync %0, %1;" :: "n"(ID), "r"(n) : "memory"); }
__device__ __forceinline__ float2 sum8(uint32_t addr) {
    float2 t[8];
#pragma unroll
    for (int w = 0; w < 8; w++) t[w] = lds64f(addr + w * 128);
    return make_float2(((t[0].x + t[1].x) + (t[2].x + t[3].x)) + ((t[4].x + t[5].x) + (t[6].x + t[7].x)),
                       ((t[0].y + t[1].y) + (t[2].y + t[3].y)) + ((t[4].y + t[5].y) + (t[6].y + t[7].y)));
}
__device__ __forceinline__ float4 sum4x4(uint32_t addr) {
    float4 t[4];
#pragma unroll
    for (int w = 0; w < 4; w++) t[w] = lds128f(addr + w * 256);
    return make_float4((t[0].x + t[1].x) + (t[2].x + t[3].x), (t[0].y + t[1].y) + (t[2].y + t[3].y),
                       (t[0].z + t[1].z) + (t[2].z + t[3].z), (t[0].w + t[1].w) + (t[2].w + t[3].w));
}
template <int NJ>
__device__ __forceinline__ void load_o(const Params& p, uint32_t (&ob)[3 * NJ][2], int bh, int J0, int j) {
    float4 v[NJ][4];
    float2 l;
#pragma unroll 1
    for (int it = 0; it < SPIN_MAX; it++) {
#pragma unroll
        for (int J = 0; J < NJ; J++) {
#pragma unroll
            for (int e = 0; e < 4; e++) v[J][e] = ld_relaxed_f4(&g_st.oacc[bh][(J0 + J) * 16 + e * 4 + j]);
        }
        l = ld_relaxed_f2(g_st.lsum[bh]);
        bool ok = l.y == UPB;
#pragma unroll
        for (int J = 0; J < NJ; J++) {
#pragma unroll
            for (int e = 0; e < 4; e++) ok &= v[J][e].w == UPB;
        }
        if (__all_sync(0xffffffffu, ok)) break;
    }
    const float rl = __fdividef(1.0f, l.x);
#pragma unroll
    for (int J = 0; J < NJ; J++) {
        ob[3 * J][0] = pack_bf16(v[J][0].x * rl, v[J][1].x * rl);     ob[3 * J][1] = pack_bf16(v[J][2].x * rl, v[J][3].x * rl);
        ob[3 * J + 1][0] = pack_bf16(v[J][0].y * rl, v[J][1].y * rl); ob[3 * J + 1][1] = pack_bf16(v[J][2].y * rl, v[J][3].y * rl);
        ob[3 * J + 2][0] = pack_bf16(v[J][0].z * rl, v[J][1].z * rl); ob[3 * J + 2][1] = pack_bf16(v[J][2].z * rl, v[J][3].z * rl);
    }
}
__device__ __forceinline__ void aux_sync() { asm volatile("bar.sync 1, 256;" ::: "memory"); }

__global__ void __launch_bounds__(NTHREADS, 1)
fused_decode_kernel(const __grid_constant__ Params p) {
    extern __shared__ __align__(1024) unsigned char smem[];
    if (threadIdx.x < 128) asm volatile("prefetch.global.L2 [%0];" :: "l"(p.wq_raw + (blockIdx.x * 128 + threadIdx.x) * 128));
    const uint32_t sb = s2u(smem);
    const int tid = threadIdx.x, warp = __shfl_sync(0xffffffffu, tid >> 5, 0), lane = tid & 31;
    const int cta = blockIdx.x;
    constexpr int grid = NCTAS;
    const int g = lane >> 2, j = lane & 3;
    const bool is_l = cta >= NE_CTAS, is_f = cta < 96 && !(cta & 1), is_g = cta < 80 && (cta & 1);
    const int fidx = cta >> 1;

    TS(0);
    if (warp == 4 && cta < NQ_CTAS) {
        asm volatile("{\n.reg .pred p;\nelect.sync _|p, 0xffffffff;\n"
                     "@p mbarrier.init.shared::cta.b64 [%0], 1;\n"
                     "@p fence.mbarrier_init.release.cluster;\n"
                     "@p mbarrier.arrive.expect_tx.shared::cta.b64 _, [%0], 61440;\n}" :: "r"(sb + BAR_WQ) : "memory");
#pragma unroll
        for (int i = 0; i < 4; i++) request_box(sb + SM_WQ + i * 15360, &p.wq, cta * 48, i * 160, sb + BAR_WQ);
    }
    if (tid == 160) {
#pragma unroll
        for (int w = 0; w < NWORK; w++) mbar_init(sb + BAR_KV + w * 8, 1);
        mbar_init(sb + BAR_W, 1);
#pragma unroll
        for (int w = 0; w < 8; w++) mbar_init(sb + BAR_G + w * 8, 1);
        asm volatile("fence.mbarrier_init.release.cluster;" ::: "memory");
    }
    __syncthreads();
    if (warp == NAUX + NWORK + 1) {
        uint32_t t = now_clk() + 2 * WO_AT_NS;
        const uint64_t pol = evict_first();
        if (lane == 0) mbar_expect_tx(sb + BAR_W, is_l ? 49152 : 61440);
#pragma unroll 1
        for (int r = 0; r < DH; r += 48, t += 2 * WO_GAP_NS) {
            wait_clk(t);
#pragma unroll 1
            for (int i = 0; i < (is_l ? 4 : 5); i++)
                request_box(sb + SM_A + i * 12288 + r * 64, &p.wo, is_l ? (cta - NE_CTAS) * 32 : (cta & 3) * 160 + i * 32,
                            (is_l ? 28 + i : cta >> 2) * DH + r, sb + BAR_W, pol);
        }
        if (!is_f && !is_g) return;
        if (lane < 8) mbar_expect_tx(sb + BAR_G + lane * 8, is_f ? 10240 : 6144);
        asm volatile("bar.sync 9, 288;" ::: "memory");
        asm volatile("fence.proxy.async.shared::cta;" ::: "memory");
#pragma unroll 1
        for (int it = 0; it < SPIN_MAX; it++) {
            t = ld_relaxed_u32(g_st.tstart);
            if (__all_sync(0xffffffffu, t != 0)) break;
            __nanosleep(400);
        }
#pragma unroll 1
        for (int it = 0; it < SPIN_MAX; it++) if (__all_sync(0xffffffffu, t - now_ns() > 2 * TRIG_NS)) break;
        TSW(11);
        t = now_clk() + (is_f ? 0 : DOFF);
#pragma unroll 1
        for (int i = 0; i < 8; i++, t += is_f ? GCLK : DCLK) {
            wait_clk(t);
            if (is_f) {
                request_box(sb + SM_G + i * 5120, &p.wg, fidx * 32, i * 80, sb + BAR_G + i * 8);
                request_box(sb + SM_G + 40960 + i * 5120, &p.wu, fidx * 32, i * 80, sb + BAR_G + i * 8);
            } else {
                request_box(sb + SM_G + i * 6144, &p.wd, fidx * 16, i * 192, sb + BAR_G + i * 8);
            }
        }
        return;
    }
    if (warp == NAUX + NWORK) {
        if (cta < NQ_CTAS) {
            wait_clk(now_clk() + 4000);
#pragma unroll
            for (int i = lane; i < STATE_V4; i += 32)
                if (cta * STATE_V4 + i < (int)(sizeof(State) / 16)) reinterpret_cast<uint4*>(&g_st)[cta * STATE_V4 + i] = make_uint4(0u, 0u, 0u, 0u);
            if (cta * 512 < X_END) {
                uint4* z = sided<uint4>(p, 0, cta * 512 + lane * 16);
                *z = make_uint4(0u, 0u, 0u, 0u);
                *other_side(z) = make_uint4(0u, 0u, 0u, 0u);
            }
            __syncwarp();
            if (lane == 0) red_release(g_cnt_z);
        }
        if (lane == 0) { TS2(2); wait_count(g_cnt_z, NQ_CTAS); TS2(29); }
        __syncwarp();
        asm volatile("bar.arrive 2, %0;" :: "n"((NWORK + 1) * 32) : "memory");
        uint32_t rtt[2] = {0xffffffffu, 0xffffffffu};
        if (lane == 0) {
#pragma unroll 1
            for (int r = 0; r < 12; r++) {
                int v = 0;
                uint32_t t1 = 0;
                unsigned* ctr = sided<unsigned>(p, r & 1, X_P + ((cta * 32 + (r >> 1) * 768) & 4095));
                pin(ctr);
                const uint32_t t0 = now_clk();
                draw(v, ctr, true);
                asm volatile("{\n.reg .pred q;\nsetp.ge.s32 q, %1, 0;\n@q mov.u32 %0, %%clock;\n}" : "+r"(t1) : "r"(v) : "memory");
                if (r & 1) rtt[1] = min(rtt[1], t1 - t0); else rtt[0] = min(rtt[0], t1 - t0);
            }
            sts32f(sb + SM_SIDE, __int_as_float(rtt[1] < rtt[0]));
        }
        const int side = __shfl_sync(0xffffffffu, rtt[1] < rtt[0], 0);
        fin_arrive<3>();
        int job = cta;
        auto sum_rows = [&](int row_end) {
#pragma unroll 1
            for (; job < 8 * min(row_end, RED0); job += NCTAS) {
                const int row = job >> 3, grp = (job & 7) * 8 + (lane & 7);
                if (lane == 0) wait_row(p, side, row, UPB);
                __syncwarp();
                const float4* src = &g_ring[row % RING][lane >> 3][grp];
                float sx = 0.f, sy = 0.f, sz = 0.f;
#pragma unroll 1
                for (int i = 0; i < 2; i++, src += 64 * 64) {
                    float4 v[16];
#pragma unroll 1
                    for (int it = 0; it < SPIN_MAX; it++) {
                        bool ok = true;
#pragma unroll
                        for (int k = 0; k < 16; k++) v[k] = ld_relaxed_b128(src + k * 4 * 64);
#pragma unroll
                        for (int k = 0; k < 16; k++) ok &= v[k].w == (float)(row + 1);
                        if (__all_sync(0xffffffffu, ok)) break;
                    }
#pragma unroll
                    for (int k = 0; k < 16; k++) { sx += v[k].x; sy += v[k].y; sz += v[k].z; }
                }
#pragma unroll
                for (int o = 8; o < 32; o <<= 1) {
                    sx += __shfl_xor_sync(0xffffffffu, sx, o); sy += __shfl_xor_sync(0xffffffffu, sy, o); sz += __shfl_xor_sync(0xffffffffu, sz, o);
                }
                if (lane < 8) st_relaxed_b128(&g_st.oacc[row][grp], sx, sy, sz, UPB);
            }
        };
        {
            uint32_t wr[10];
            float wsum = 0.f;
#pragma unroll
            for (int i = 0; i < 10; i++) {
                const int w = 4 * lane + 128 * (i >> 2) + (i & 3) - (i >= 8 ? 2 * lane : 0);
                wr[i] = *reinterpret_cast<const uint32_t*>(p.wr + (w >> 4) * 32 + (w & 3) * 8 + ((w >> 1) & 6));
                wsum += lo_f(wr[i]) + hi_f(wr[i]);
            }
            wsum = warp_sum(wsum);
            const int lb = lane >> 3, lc = lane & 7;
            uint32_t ypart = sb + SM_RED2 + (lb >> 1) * 160 + lc * 16 + (lb & 1) * 8;
            __nv_bfloat16* out = p.out + lb * DM + fidx * 16 + lc;
            float nmean_l = 0.f, rden_l = 0.f, sig_l = 0.f;
#pragma unroll 1
            for (int b = 0; b < NB; b++) {
                const uint32_t hx = X_H + b * (DM * 2), hrow = sb + SM_X + b * HPITCH;
                const uint4 *src0 = sided<uint4>(p, side, hx + 16 * lane), *src1 = sided<uint4>(p, side, hx + 512 + 16 * lane);
                const uint2* src2 = sided<uint2>(p, side, hx + 1024 + 8 * lane);
                sum_rows((b + 1) * NH);
                if (!is_l && !is_f && !is_g) continue;
                pin(src0); pin(src1); pin(src2); pin(ypart); pin(out);
                if (lane == 0) wait_row(p, side, b * NH + (is_l ? 28 : NH - 1), is_l ? 1 : 100);
                __syncwarp();
                if (is_l) {
                    const int col = (cta - NE_CTAS) * 32 + 2 * (lane & 15);
                    uint32_t lpart = sb + SM_RED + (lane & 15) * 8;
                    const uint32_t xv = *reinterpret_cast<const uint32_t*>(p.x + b * DM + col);
                    uint32_t* hdst = sided<uint32_t>(p, lane >> 4, hx + 4 * ((col >> 5) * 16 + (col & 6) * 2 + ((col >> 3) & 3)));
                    float4 early;
#pragma unroll 1
                    for (int it = 0; it < SPIN_MAX; it++) {
                        early = ld_relaxed_f4(&g_st.attn[b][col]);
                        if (__all_sync(0xffffffffu, early.y == NE_CTAS / 4 && early.w == NE_CTAS / 4)) break;
                    }
                    if (lane == 0) TS2(23);
                    float x0 = lo_f(xv), x1 = hi_f(xv);
                    pin(hdst); pin(lpart); pin(x0); pin(x1);
                    fin_sync<4>();
                    CK(2, lds32(sb + SM_RED));
                    const float2 late = sum8(lpart);
                    st_relaxed(hdst, pack_neg(x0 + bf16r(early.x + late.x), x1 + bf16r(early.z + late.y)));
                    CK(3, 0);
                    if (lane == 0) TS2(15);
                    fin_sync<5>();
                    continue;
                }
                uint4 h0, h1;
                uint2 h2;
                float mm[5][4];
#pragma unroll 1
                for (int it = 0; it < SPIN_MAX; it++) {
                    h0 = ld_relaxed_v4(src0);
                    h1 = ld_relaxed_v4(src1);
                    h2 = ld_relaxed_v2(src2);
                    asm volatile("st.shared.v4.u32 [%0], {%1,%2,%3,%4};" :: "r"(hrow + lane * 16), "r"(h0.x), "r"(h0.y), "r"(h0.z), "r"(h0.w) : "memory");
                    asm volatile("st.shared.v4.u32 [%0], {%1,%2,%3,%4};" :: "r"(hrow + 512 + lane * 16), "r"(h1.x), "r"(h1.y), "r"(h1.z), "r"(h1.w) : "memory");
                    asm volatile("st.shared.v2.u32 [%0], {%1,%2};" :: "r"(hrow + 1024 + lane * 8), "r"(h2.x), "r"(h2.y) : "memory");
                    const uint32_t w[10] = {h0.x, h0.y, h0.z, h0.w, h1.x, h1.y, h1.z, h1.w, h2.x, h2.y};
#pragma unroll
                    for (int i = 0; i < 5; i++) {
                        const uint32_t a[4] = {w[2 * i], 0x3f803f80u, w[2 * i + 1], 0x3f803f80u};
                        mm[i][0] = mm[i][1] = mm[i][2] = mm[i][3] = 0.f;
                        mma16816(mm[i], a, w[2 * i], w[2 * i + 1]);
                    }
                    const uint32_t lo = min(min(min(h0.x, h0.y), min(h0.z, h0.w)), min(min(min(h1.x, h1.y), min(h1.z, h1.w)), min(h2.x, h2.y)));
                    const bool ok = __all_sync(0xffffffffu, lo != 0 || it == SPIN_MAX - 1);
                    asm volatile("{\n.reg .pred p;\nsetp.ne.u32 p, %0, 0;\n@p bar.arrive 7, 288;\n}" :: "r"((uint32_t)ok) : "memory");
                    if (ok) break;
                    if (!is_f) __nanosleep(100);
                }
                CK(4, h0.x);
                if (lane == 0 && is_f) TS2(12);
                const uint32_t hw[10] = {h0.x, h0.y, h0.z, h0.w, h1.x, h1.y, h1.z, h1.w, h2.x, h2.y};
                float m1 = ((mm[0][2] + mm[1][2]) + (mm[2][2] + mm[3][2])) + ((mm[0][3] + mm[1][3]) + (mm[2][3] + mm[3][3])) + (mm[4][2] + mm[4][3]);
                float m2 = (g & 1) ? ((mm[0][1] + mm[1][1]) + (mm[2][1] + mm[3][1])) + mm[4][1] : ((mm[0][0] + mm[1][0]) + (mm[2][0] + mm[3][0])) + mm[4][0];
                m2 += __shfl_xor_sync(0xffffffffu, m2, 4);
                m1 = (m1 + __shfl_xor_sync(0xffffffffu, m1, 1)) + (__shfl_xor_sync(0xffffffffu, m1, 2) + __shfl_xor_sync(0xffffffffu, m1, 3));
                m2 = (__shfl_sync(0xffffffffu, m2, 0) + __shfl_sync(0xffffffffu, m2, 9)) + (__shfl_sync(0xffffffffu, m2, 18) + __shfl_sync(0xffffffffu, m2, 27));
                m1 *= 1.0f / DM;
                const float nmean = bf16r(m1);
                const float var = bf16r(fmaxf(fmaf(-m1, m1, m2 * (1.0f / DM)), 0.f));
                const float den = bf16r(sqrt_approx(bf16r(var + 1e-5f)));
                if (is_f) {
                    sts64f(sb + SM_MOM + b * 8, nmean, den, lane == 0);
                    CK(5, 0);
                    fin_arrive<4>();
                } else {
                    const float rden = rcp_approx(den);
                    if (lb == b) { nmean_l = nmean; rden_l = rden; }
                    __syncwarp();
                    const float2 hw2 = lds64f(sb + SM_X + lb * HPITCH + ((fidx >> 1) * 16 + (lc & 6) * 2 + (fidx & 1) * 2) * 4);
                    const float nh0 = (lc & 1) ? hi_f(__float_as_uint(hw2.x)) : lo_f(__float_as_uint(hw2.x));
                    const float nh1 = (lc & 1) ? hi_f(__float_as_uint(hw2.y)) : lo_f(__float_as_uint(hw2.y));
                    float rr = 0.f;
#pragma unroll
                    for (int i = 0; i < 10; i++) rr = fmaf(lo_f(hw[i]), lo_f(wr[i]), fmaf(hi_f(hw[i]), hi_f(wr[i]), rr));
                    const float sig = bf16r(sigmoid_approx(bf16r((nmean * wsum - warp_sum(rr)) * rden)));
                    if (lb == b) sig_l = sig;
                    const float ln0 = bf16r(bf16r(nmean_l - nh0) * rden_l), ln1 = bf16r(bf16r(nmean_l - nh1) * rden_l);
                    fin_sync<6>(after(after(after(288, sig_l), ln0), ln1));
                    CK(10, lds32(ypart));
                    float2 t[16];
#pragma unroll
                    for (int i = 0; i < 16; i++) t[i] = lds64f(ypart + i * YPITCH);
#pragma unroll
                    for (int o = 1; o < 16; o <<= 1) {
#pragma unroll
                        for (int i = 0; i < 16; i += 2 * o) { t[i].x += t[i + o].x; t[i].y += t[i + o].y; }
                    }
                    const uint32_t ov = pack_bf16(bf16r(ln0 + bf16r(bf16r(-t[0].x) * sig_l)) - nh0, bf16r(ln1 + bf16r(bf16r(-t[0].y) * sig_l)) - nh1);
                    asm volatile("{\n.reg .pred p;\n.reg .b16 lo, hi;\nsetp.eq.u32 p, %2, 3;\nmov.b32 {lo, hi}, %1;\n"
                                 "@p st.global.u16 [%0], lo;\n@p st.global.u16 [%0 + 16], hi;\n}" :: "l"(out), "r"(ov), "r"(b) : "memory");
                    CK(11, 0);
                    if (lane == 0) TS2(13);
                }
                if (b < NB - 1) fin_sync<5>();
            }
            if (cta == 0 && lane == 0) { g_work[0] = 0; g_cnt_z[0] = 0; }
        }
        return;
    }
    if (warp >= NAUX) {
        const int wk = warp - NAUX;
        const uint32_t bar = sb + BAR_KV + wk * 8;
        const uint32_t buf = sb + SM_KV + wk * TILE_BYTES;
        const uint64_t pol = evict_first();
        const int nstatic = NWORK * grid;
        constexpr int POOL0 = NUNITS - NPOOL;
        int uk = wk * grid + cta;
        wait_clk(now_clk() + 2 * (K0_DELAY_NS + wk * K0_STEP_NS));
        request_tile(buf, &p.k, uk, bar, pol);
        uint32_t koff[3], voff[3];
        {
            const int r = lane & 7, hf = (lane >> 3) & 1;
            const int kkey = hf ? 8 + (r ^ 1) : r;
            const int vh = lane >> 4;
            const int vkey = ((r & 1) ? 8 : 0) + (vh ? (r ^ 1) : r);
#pragma unroll
            for (int b = 0; b < 3; b++) {
                const int rk = 3 * kkey + b, rv = 3 * vkey + b;
                koff[b] = buf + rk * 128 + (((lane >> 4) ^ (rk & 7)) << 4);
                voff[b] = buf + rv * 128 + ((hf ^ (rv & 7)) << 4);
            }
        }
        uint32_t phase = 0;
        uint4 qf[6];
        auto load_q = [&](int u) {
            const uint32_t* q = &g_early[row_of(u)].q[j * 4];
#pragma unroll
            for (int i = 0; i < 6; i++) qf[i] = ld_relaxed_v4(q + i * 16);
        };
        load_q(uk);
        int uq[LAG];
        uint32_t sq[LAG];
#pragma unroll
        for (int i = 0; i < LAG; i++) { uq[i] = -1; sq[i] = 0; }
        uint4 mv = make_uint4(0u, 0u, 0u, 0u);
        uint32_t svp = 0;
        float freed = UPB;
        while (true) {
            const int uv = uq[0];
            uint32_t sv = sq[0];
#pragma unroll
            for (int i = 0; i + 1 < LAG; i++) { uq[i] = uq[i + 1]; sq[i] = sq[i + 1]; }
            uq[LAG - 1] = uk;
            if (uk < NUNITS) {
                PH(7);
#pragma unroll 1
                for (int it = 0; it < SPIN_MAX; it++) {
                    uint32_t lo = 0xffffffffu;
#pragma unroll
                    for (int i = 0; i < 6; i++) lo = min(min(lo, min(qf[i].x, qf[i].y)), min(qf[i].z, qf[i].w));
                    if (__all_sync(0xffffffffu, lo != 0)) break;
                    __nanosleep(250);
                    load_q(uk);
                }
                mbar_wait(bar, phase); phase ^= 1;
                PH(0); ARR();
                TSI(0, 16); TSI(1, 18);
                float acc[2][4][4] = {};
#pragma unroll
                for (int ks = 0; ks < 12; ks++) {
                    const uint4 qq = qf[ks >> 1];
                    const uint32_t b0 = (ks & 1) ? qq.z : qq.x, b1 = (ks & 1) ? qq.w : qq.y;
#pragma unroll
                    for (int mt = 0; mt < 4; mt++) {
                        uint32_t a[4];
                        ldsm4(a, (koff[ks >> 2] ^ ((ks & 3) << 5)) + mt * 6144);
                        mma16816(acc[ks & 1][mt], a, b0, b1);
                    }
                }
                PH(1);
                TSI(0, 17); TSI(1, 19);
                if (uv < NUNITS) request_tile(buf, uv >= 0 ? &p.v : &p.k, uv >= 0 ? uv : uk + nstatic, bar, pol);
                const float sa = sel4(j, acc[0][0][0], acc[0][1][0], acc[0][2][0], acc[0][3][0]) + sel4(j, acc[1][0][0], acc[1][1][0], acc[1][2][0], acc[1][3][0]);
                const float sc = sel4(j, acc[0][0][2], acc[0][1][2], acc[0][2][2], acc[0][3][2]) + sel4(j, acc[1][0][2], acc[1][1][2], acc[1][2][2], acc[1][3][2]);
                const uint32_t raw = pack_bf16(sa, sc);
                const float scale = -0.07216878364870322f;
                const uint32_t sk = pack_bf16(lo_f(raw) * scale, hi_f(raw) * scale);
                sq[LAG - 1] = sk;
                if (uk >= POOL0) st_relaxed(&g_st.score[uk - POOL0][lane], sk ? sk : 0x80008000u);
                int a = (int)(sk << 16), b = (int)(sk & 0xffff0000u);
                a ^= (a >> 31) & 0x7fff0000; b ^= (b >> 31) & 0x7fff0000;
                const int mx = __reduce_max_sync(0xffffffffu, max(a, b));
                if (lane == 0) st_relaxed(&g_early[row_of(uk)].umax[pos_of(uk)], (uint32_t)mx | 1u);
            }
            if (uv < 0) {
                uk += nstatic;
                load_q(uk);
                continue;
            }
            if (uv >= NUNITS) break;
            const int bh = row_of(uv);
#pragma unroll 1
            for (int it = 0; it < SPIN_MAX; it++) {
                if (__all_sync(0xffffffffu, (mv.x & mv.y & mv.z & mv.w & 1u) && (uv < POOL0 || svp != 0) && freed == UPB)) break;
                mv = ld_relaxed_v4(&g_early[bh].umax[lane * 4]);
                if (bh >= RING && bh < RED0) freed = __uint_as_float(ld_relaxed_u32(&g_st.oacc[bh - RING][(lane & 7) * 8].w));
                if (uv >= POOL0) svp = ld_relaxed_u32(&g_st.score[uv - POOL0][lane]);
            }
            if (uv >= POOL0) sv = svp;
            PH(2);
            int un = NUNITS, vn = 0;
            draw(un, g_work, uk < NUNITS && lane == 0);
            int mx = __reduce_max_sync(0xffffffffu, max(max((int)mv.x, (int)mv.y), max((int)mv.z, (int)mv.w))) & 0xffff0000;
            mx ^= (mx >> 31) & 0x7fff0000;
            const float m = __int_as_float(mx);
            const float l2e = 1.4426950408889634f;
            const uint32_t pp = pack_bf16(exp2f((lo_f(sv) - m) * l2e), exp2f((hi_f(sv) - m) * l2e));
            uint32_t pb[8];
#pragma unroll
            for (int t = 0; t < 4; t++) {
                pb[2 * t] = __shfl_sync(0xffffffffu, pp, 8 * j + t);
                pb[2 * t + 1] = __shfl_sync(0xffffffffu, pp, 8 * j + 4 + t);
            }
            float lacc[4] = {};
            const uint32_t ones[4] = {0x3f803f80u, 0x3f803f80u, 0x3f803f80u, 0x3f803f80u};
#pragma unroll
            for (int t = 0; t < 4; t++) mma16816(lacc, ones, pb[2 * t], pb[2 * t + 1]);
            if (uv < nstatic) {
                asm volatile("bar.sync 2, %0;" :: "n"((NWORK + 1) * 32) : "memory");
                TSW(3);
            }
            const int grp = 16 * j + 4 * (g & 1) + (g >> 1);
            float4* dst = bh < RED0 ? &g_ring[bh % RING][pos_of(uv)][grp] : oacc_at(p, lds32(sb + SM_SIDE) ^ 1, bh, grp);
            float4* dst2 = other_side(dst);
            float2* ldst = lsum_at(p, lane & 1, bh);
            if (bh >= SROW0 && lane < 2) red_f2(&ldst->x, lacc[0], 1.f);
            float tag = bh < RED0 ? (float)(bh + 1) : 1.f;
            un = __shfl_sync(0xffffffffu, un, 0) + (LAG + 1) * nstatic;
            uint32_t pooled = uq[0] >= POOL0 && lane == 0;
            pin(dst); pin(dst2); pin(ldst); pin(tag); pin(voff[0]); pin(voff[1]); pin(voff[2]); pin(pooled);
            PH(3);
            LT(1);
            mbar_wait(bar, phase); phase ^= 1;
            PH(4); ARR();
            LT(2);
            draw(vn, g_st.pool, pooled);
            float acc[12][4] = {};
#pragma unroll
            for (int t = 0; t < 4; t++) {
#pragma unroll
                for (int mt = 0; mt < 12; mt++) {
                    uint32_t a[4];
                    ldsm4t(a, (voff[mt >> 2] ^ ((mt & 3) << 5)) + t * 6144);
                    mma16816(acc[mt], a, pb[2 * t], pb[2 * t + 1]);
                }
            }
            PH(5);
            if (lane == 0) PROG(un);
            if (un < NUNITS) request_tile(buf, &p.k, un, bar, pol);
            float o[6];
#pragma unroll
            for (int e = 0; e < 6; e++) {
                const int q = e % 3, c = (e / 3) * 2;
                o[e] = sel4(j, acc[q][c], acc[3 + q][c], acc[6 + q][c], acc[9 + q][c]);
            }
            if (bh >= SROW0) {
                red_f4(&dst->x, o[0], o[1], o[2], tag);
                red_f4(&dst[16].x, o[3], o[4], o[5], tag);
                red_f4(&dst2->x, o[0], o[1], o[2], tag);
                red_f4(&dst2[16].x, o[3], o[4], o[5], tag);
            } else {
                if (bh >= RED0) {
                    red_f4(&dst->x, o[0], o[1], o[2], tag);
                    red_f4(&dst[8].x, o[3], o[4], o[5], tag);
                } else {
                    st_relaxed_b128(dst, o[0], o[1], o[2], tag);
                    st_relaxed_b128(dst + 8, o[3], o[4], o[5], tag);
                }
                if (lane == 0) red_f2(&ldst->x, lacc[0], 1.f);
            }
            if (uq[0] >= POOL0) {
                vn = __shfl_sync(0xffffffffu, vn, 0);
                uq[0] = POOL0 + vn;
                if (vn == VTRIG && lane == 0) st_relaxed(g_st.tstart, (now_ns() + TRIG_NS) | 1u);
            }
            if (un < NUNITS) load_q(un);
            PH(6);
            if (uq[0] >= NUNITS && un >= NUNITS) break;
            uk = un;
            if (uq[0] < NUNITS) {
                const int nb = row_of(uq[0]);
                mv = ld_relaxed_v4(&g_early[nb].umax[lane * 4]);
                freed = nb >= RING && nb < RED0 ? __uint_as_float(ld_relaxed_u32(&g_st.oacc[nb - RING][(lane & 7) * 8].w)) : UPB;
                if (uq[0] >= POOL0) svp = ld_relaxed_u32(&g_st.score[uq[0] - POOL0][lane]);
                if (un >= NUNITS) {
                    request_tile(buf, &p.v, uq[0], bar, pol);
                    LT(0);
                }
            }
        }
        if (is_f) asm volatile("bar.arrive 10, %0;" :: "n"((NAUX + NWORK) * 32) : "memory");
        return;
    }

    __nv_bfloat16* xs = reinterpret_cast<__nv_bfloat16*>(smem + SM_X);
    float* red = reinterpret_cast<float*>(smem + SM_RED);
    const int frow = (lane & 7) + ((lane >> 4) << 3), fcol = (lane >> 3) & 1;
    if (cta < NQ_CTAS) {
        uint2 xr[5];
        if (warp < NB) {
#pragma unroll
            for (int i = 0; i < 5; i++) xr[i] = *reinterpret_cast<const uint2*>(p.x + warp * DM + i * 128 + lane * 4);
        }
        TS(26);
        if (warp < NB) {
            float v[20];
#pragma unroll
            for (int i = 0; i < 5; i++) {
                v[4 * i] = lo_f(xr[i].x); v[4 * i + 1] = hi_f(xr[i].x); v[4 * i + 2] = lo_f(xr[i].y); v[4 * i + 3] = hi_f(xr[i].y);
            }
            layernorm20(v);
#pragma unroll
            for (int i = 0; i < 5; i++)
                *reinterpret_cast<uint2*>(xs + warp * XPITCH + i * 128 + lane * 4) =
                    make_uint2(pack_bf16(v[4 * i], v[4 * i + 1]), pack_bf16(v[4 * i + 2], v[4 * i + 3]));
        }
        TS(27);
        aux_sync();
        mbar_wait(sb + BAR_WQ, 0);
        TS(1);
        const uint32_t xfrag = sb + SM_X + ((g & 3) * XPITCH + 2 * j) * 2;
        float acc[3][4] = {};
#pragma unroll
        for (int s = 0; s < 5; s++) {
            const int ks = warp * 5 + s;
            const uint32_t b0 = lds32(xfrag + ks * 32), b1 = lds32(xfrag + ks * 32 + 16);
            const int row = ks * 16 + frow;
#pragma unroll
            for (int mt = 0; mt < 3; mt++) {
                uint32_t a[4];
                ldsm4t(a, sb + SM_WQ + (row * 6 + 2 * mt + fcol) * 16);
                mma16816(acc[mt], a, b0, b1);
            }
        }
        if (j < 2) {
#pragma unroll
            for (int mt = 0; mt < 3; mt++) {
                *reinterpret_cast<float2*>(red + (warp * 48 + mt * 16 + g) * 4 + 2 * j) = make_float2(acc[mt][0], acc[mt][1]);
                *reinterpret_cast<float2*>(red + (warp * 48 + mt * 16 + 8 + g) * 4 + 2 * j) = make_float2(acc[mt][2], acc[mt][3]);
            }
        }
        aux_sync();
        if (tid < 96) {
            const int b = tid & 3, cp = tid >> 2;
            float s0 = 0.f, s1 = 0.f;
#pragma unroll
            for (int w = 0; w < 8; w++) { s0 += red[(w * 48 + 2 * cp) * 4 + b]; s1 += red[(w * 48 + 2 * cp + 1) * 4 + b]; }
            const int h = cta >> 2, d = (cta & 3) * 48 + 2 * cp;
            const int ch = d >> 3, jj = (d & 7) >> 1;
            st_relaxed(&g_early[b * NH + h].q[(ch >> 2) * 16 + jj * 4 + (ch & 3)], pack_neg(s0, s1));
        }
        TS(28);
    }
    if (tid < 160) *reinterpret_cast<uint2*>(smem + SM_X + 4 * HPITCH + tid * 8) = make_uint2(0x3f803f80u, 0x3f803f80u);
    fin_sync<3>();
    const int side = lds32(sb + SM_SIDE);
    mbar_wait(sb + BAR_W, 0);
    TS(7);
    uint32_t part = sb + SM_RED + (warp * 32 + 8 * j + g) * 4;

#pragma unroll 1
    for (int b = 0; b < NB; b++) {
        if (b == NB - 1 && (is_f || is_g)) asm volatile("bar.arrive 9, 288;" ::: "memory");
        if (is_l) {
            uint32_t a[6][2][4];
#pragma unroll
            for (int s = 0; s < 6; s++) {
                const int row = (warp * 6 + s) * 16 + frow;
#pragma unroll
                for (int mt = 0; mt < 2; mt++) ldsm4t(a[s][mt], sb + SM_A + (row * 4 + ((2 * mt + fcol) ^ ((row >> 1) & 3))) * 16);
            }
            const int bh = b * NH + 28 + (warp >> 1);
            const float4* osrc = oacc_at(p, side, bh, (warp & 1) * 32 + lane);
            const float2* lsrc = lsum_at(p, side, bh);
            if (lane == 0) wait_row_o(p, side, bh, 1);
            __syncwarp();
            float2 lv;
#pragma unroll 1
            for (int it = 0; it < SPIN_MAX; it++) {
                lv = ld_relaxed_f2(lsrc);
                if (__all_sync(0xffffffffu, lv.y == UPB)) break;
            }
            if (warp == 7) TSW(25);
            float rl = rcp_approx(lv.x);
            float4 ov;
            pin(osrc); pin(part); pin(rl);
#pragma unroll 1
            for (int it = 0;; it++) {
                ov = ld_relaxed_f4(osrc);
                if (__all_sync(0xffffffffu, ov.w == UPB || it == SPIN_MAX)) break;
            }
            CK(0, __float_as_uint(ov.x));
            const float px = __shfl_xor_sync(0xffffffffu, ov.x, 4), py = __shfl_xor_sync(0xffffffffu, ov.y, 4),
                        pz = __shfl_xor_sync(0xffffffffu, ov.z, 4);
            const uint32_t w[3] = {pack_bf16(ov.x * rl, px * rl), pack_bf16(ov.y * rl, py * rl), pack_bf16(ov.z * rl, pz * rl)};
            float acc[2][2][4] = {};
#pragma unroll
            for (int s = 0; s < 6; s++) {
                const uint32_t b0 = __shfl_sync(0xffffffffu, w[s % 3], (s / 3) * 16 + j);
                const uint32_t b1 = __shfl_sync(0xffffffffu, w[s % 3], (s / 3) * 16 + 8 + j);
#pragma unroll
                for (int mt = 0; mt < 2; mt++) mma16816(acc[mt][s & 1], a[s][mt], b0, b1);
            }
            sts32f(part, sel4(j, acc[0][0][0] + acc[0][1][0], acc[0][0][2] + acc[0][1][2], acc[1][0][0] + acc[1][1][0], acc[1][0][2] + acc[1][1][2]));
            CK(1, 0);
            fin_arrive<4>();
            if (warp == 7) TSW(30);
            if (warp == 5) TSW(31);
            if (cta == NE_CTAS && lane < 28) reinterpret_cast<uint4*>(&g_early[bh])[(warp & 1) * 28 + lane] = make_uint4(0u, 0u, 0u, 0u);
            fin_sync<5>();
            continue;
        }
        {
            const int bh = b * NH + (cta >> 2);
            if (tid == 0) wait_row_o(p, side, bh, UPB);
            aux_sync();
            if (warp < 5) {
                uint32_t ob[12][2];
                load_o<4>(p, ob, bh, 0, j);
                float acc[2][2][4] = {};
#pragma unroll
                for (int ks = 0; ks < 12; ks++) {
                    const int row = ks * 16 + frow;
#pragma unroll
                    for (int mt = 0; mt < 2; mt++) {
                        uint32_t a[4];
                        ldsm4t(a, sb + SM_A + warp * 12288 + (row * 4 + ((2 * mt + fcol) ^ ((row >> 1) & 3))) * 16);
                        mma16816(acc[mt][ks & 1], a, ob[ks][0], ob[ks][1]);
                    }
                }
                red_f2(&g_st.attn[b][(cta & 3) * 160 + warp * 32 + 8 * j + g].x,
                       sel4(j, acc[0][0][0] + acc[0][1][0], acc[0][0][2] + acc[0][1][2], acc[1][0][0] + acc[1][1][0], acc[1][0][2] + acc[1][1][2]), 1.f);
                TS(8);
            } else if (warp > 5 && (cta & 3) == 0 && tid - 192 < 56) {
                reinterpret_cast<uint4*>(&g_early[bh])[tid - 192] = make_uint4(0u, 0u, 0u, 0u);
            }
        }
        if (is_f) {
            const int kq = warp >> 1, tp = warp & 1;
            uint32_t hfrag = sb + SM_X + min(g, 4) * HPITCH + (kq * 80 + 4 * j) * 4;
            uint4 hv[5] = {};
#pragma unroll
            for (int s = 0; s < 5; s++) lds128_if(hv[s], hfrag + s * 64, true);
            if (b == NB - 1) asm volatile("bar.sync 10, %0;" :: "n"((NAUX + NWORK) * 32) : "memory");
            uint32_t ga[10][2][4];
#pragma unroll
            for (int s = 0; s < 10; s++) {
                if (s % 5 == 0 && b == NB - 1) mbar_wait(sb + BAR_G + (kq * 2 + s / 5) * 8, 0);
                const int row = (kq * 10 + s) * 16 + frow;
#pragma unroll
                for (int t = 0; t < 2; t++) ldsm4t(ga[s][t], sb + SM_G + fcol * 40960 + (row * 4 + ((2 * tp + t) ^ ((row >> 1) & 3))) * 16);
            }
            if (warp == NAUX - 1) TSW(9);
            uint32_t fpart = sb + SM_RED + 2 * j * FPITCH + warp * 128 + g * 16;
            uint32_t dsum = sb + SM_RED + (lane >> 3) * FPITCH + tp * 128 + (lane & 7) * 16, csum = sb + SM_RED + 4 * FPITCH + tp * 128 + (lane & 7) * 16;
            uint32_t mom = sb + SM_MOM + (lane >> 3) * 8;
            uint32_t* dst = sided<uint32_t>(p, side ^ 1, X_A + (2 * fidx + tp) * 128 + (lane ^ 2 * tp) * 4);
            pin(fpart); pin(hfrag); pin(dsum); pin(csum); pin(mom); pin(dst);
            fin_sync<7>();
#pragma unroll
            for (int s = 0; s < 5; s++) lds128_if(hv[s], hfrag + s * 64, g == b);
            float acc[2][2][4] = {};
#pragma unroll
            for (int s = 0; s < 5; s++) {
#pragma unroll
                for (int t = 0; t < 2; t++) mma16816(acc[t][0], ga[2 * s][t], hv[s].x, hv[s].y);
#pragma unroll
                for (int t = 0; t < 2; t++) mma16816(acc[t][1], ga[2 * s + 1][t], hv[s].z, hv[s].w);
            }
#pragma unroll
            for (int e = 0; e < 2; e++)
                sts128f(fpart + e * FPITCH, acc[0][0][e] + acc[0][1][e], acc[0][0][2 + e] + acc[0][1][2 + e],
                        acc[1][0][e] + acc[1][1][e], acc[1][0][2 + e] + acc[1][1][2 + e], 2 * j + e < 5);
            CK(5, 0);
            if (warp < 2) {
                fin_sync<4>();
                CK(6, lds32(dsum));
                float2 m = lds64f(mom);
                m.y = rcp_approx(m.y);
                const float4 d = sum4x4(dsum), cs = sum4x4(csum);
                const float g0 = bf16r(fmaf(m.x, cs.x, -d.x) * m.y), g1 = bf16r(fmaf(m.x, cs.z, -d.z) * m.y);
                const float u0 = bf16r(fmaf(m.x, cs.y, -d.y) * m.y), u1 = bf16r(fmaf(m.x, cs.w, -d.w) * m.y);
                const uint32_t av = pack_neg(bf16r(g0 * sigmoid_approx(g0)) * u0, bf16r(g1 * sigmoid_approx(g1)) * u1);
                asm volatile("{\n.reg .pred p;\nsetp.eq.u32 p, %3, 3;\n@p st.relaxed.gpu.global.u32 [%0], %2;\n@p st.relaxed.gpu.global.u32 [%1], %2;\n}"
                             :: "l"(dst), "l"(other_side(dst)), "r"(av), "r"(b) : "memory");
                CK(7, 0);
                TS(14);
            } else {
                fin_arrive<4>();
            }
        } else if (is_g) {
            if (b == NB - 1) {
                mbar_wait(sb + BAR_G + warp * 8, 0);
                if (warp == NAUX - 1) TSW(10);
            }
            uint32_t wb[3][2][2][4];
#pragma unroll
            for (int s = 0; s < 12; s++) {
                const int odd = (lane >> 2) & 1, c = ((lane & 2) * 2 + (s & 1) * 2 + (lane >> 4)) ^ (2 * odd);
                const int row = (warp * 12 + (s >> 1) * 2 + odd) * 16 + (lane & 1) * 8 + c;
                ldsm4t(wb[s >> 2][(s >> 1) & 1][s & 1], sb + SM_G + (row * 2 + (fcol ^ ((row >> 2) & 1))) * 16);
            }
            const uint4* asrc[3];
#pragma unroll
            for (int q = 0; q < 3; q++) {
                asrc[q] = sided<uint4>(p, side, X_A + (warp * 12 + 4 * q + 2 * (g >> 2) + (j >> 1)) * 128 + (g & 3) * 32 + (j & 1) * 16);
                pin(asrc[q]);
            }
            uint32_t ypart = sb + SM_RED2 + (warp * 2 + (j >> 1)) * YPITCH + (j & 1) * 160 + g * 16;
            pin(ypart);
            fin_sync<7>();
            uint4 v[3] = {};
            uint32_t mq[3] = {};
#pragma unroll 1
            for (int it = b < NB - 1 ? SPIN_MAX : 0;; it++) {
                asm volatile("{\n.reg .pred p0, p1, p2;\nsetp.eq.u32 p0, %15, 0;\nsetp.eq.u32 p1, %16, 0;\nsetp.eq.u32 p2, %17, 0;\n"
                             "@p0 ld.relaxed.gpu.global.v4.u32 {%0,%1,%2,%3}, [%12];\n"
                             "@p1 ld.relaxed.gpu.global.v4.u32 {%4,%5,%6,%7}, [%13];\n"
                             "@p2 ld.relaxed.gpu.global.v4.u32 {%8,%9,%10,%11}, [%14];\n}"
                             : "+r"(v[0].x), "+r"(v[0].y), "+r"(v[0].z), "+r"(v[0].w), "+r"(v[1].x), "+r"(v[1].y), "+r"(v[1].z), "+r"(v[1].w),
                               "+r"(v[2].x), "+r"(v[2].y), "+r"(v[2].z), "+r"(v[2].w)
                             : "l"(asrc[0]), "l"(asrc[1]), "l"(asrc[2]), "r"(mq[0]), "r"(mq[1]), "r"(mq[2]) : "memory");
#pragma unroll
                for (int q = 0; q < 3; q++) mq[q] = min(min(v[q].x, v[q].y), min(v[q].z, v[q].w));
                const uint32_t lo = min(min(mq[0], mq[1]), mq[2]);
                if (__all_sync(0xffffffffu, lo != 0 || it == SPIN_MAX)) break;
            }
            CK(8, v[0].x);
            float acc[2][2][4] = {};
#pragma unroll
            for (int q = 0; q < 3; q++) {
#pragma unroll
                for (int pr = 0; pr < 2; pr++) {
                    mma16816(acc[pr][0], wb[q][pr][0], v[q].x, v[q].y);
                    mma16816(acc[pr][1], wb[q][pr][1], v[q].z, v[q].w);
                }
            }
            float y[4];
#pragma unroll
            for (int e = 0; e < 4; e++) y[e] = j < 2 ? acc[0][0][e] + acc[0][1][e] : acc[1][0][e] + acc[1][1][e];
            asm volatile("st.shared.v4.f32 [%0], {%1,%2,%3,%4};" :: "r"(ypart), "f"(y[0]), "f"(y[2]), "f"(y[1]), "f"(y[3]) : "memory");
            CK(9, 0);
            fin_arrive<6>();
        } else {
            continue;
        }
        if (b < NB - 1) fin_sync<5>();
    }
}

typedef CUresult (*EncodeFn)(CUtensorMap*, CUtensorMapDataType, cuuint32_t, void*, const cuuint64_t*, const cuuint64_t*,
                             const cuuint32_t*, const cuuint32_t*, CUtensorMapInterleave, CUtensorMapSwizzle,
                             CUtensorMapL2promotion, CUtensorMapFloatOOBfill);

CUtensorMap make_map(EncodeFn enc, void* ptr, uint64_t cols, uint64_t rows, uint32_t bcols, uint32_t brows,
                     CUtensorMapSwizzle sw, CUtensorMapL2promotion promo) {
    CUtensorMap m;
    const cuuint64_t dims[2] = {cols, rows};
    const cuuint64_t strides[1] = {cols * 2};
    const cuuint32_t box[2] = {bcols, brows};
    const cuuint32_t es[2] = {1, 1};
    enc(&m, CU_TENSOR_MAP_DATA_TYPE_BFLOAT16, 2, ptr, dims, strides, box, es, CU_TENSOR_MAP_INTERLEAVE_NONE, sw, promo,
        CU_TENSOR_MAP_FLOAT_OOB_FILL_NONE);
    return m;
}

}

extern "C" void kernel_launch(void* const* d_in, const int* in_sizes, int n_in, void* d_out, int out_size) {
    (void)in_sizes; (void)n_in; (void)out_size;
    static EncodeFn enc = nullptr;
    static int sms = 0;
    static void* raw = nullptr;
    if (!enc) {
        cudaDriverEntryPointQueryResult qr;
        cudaGetDriverEntryPoint("cuTensorMapEncodeTiled", (void**)&enc, cudaEnableDefault, &qr);
        int dev = 0;
        cudaGetDevice(&dev);
        cudaDeviceGetAttribute(&sms, cudaDevAttrMultiProcessorCount, dev);
        cudaGetSymbolAddress(&raw, g_raw);
        cudaFuncSetAttribute(fused_decode_kernel, cudaFuncAttributeMaxDynamicSharedMemorySize, SM_TOTAL);
    }
    if (sms < NCTAS) return;
    const CUtensorMapL2promotion WPROMO = CU_TENSOR_MAP_L2_PROMOTION_L2_128B;
    Params p;
    p.k = make_map(enc, d_in[1], 64, (uint64_t)NBH * SK * 3, 64, TILE_ROWS, CU_TENSOR_MAP_SWIZZLE_128B, CU_TENSOR_MAP_L2_PROMOTION_NONE);
    p.v = make_map(enc, d_in[2], 64, (uint64_t)NBH * SK * 3, 64, TILE_ROWS, CU_TENSOR_MAP_SWIZZLE_128B, CU_TENSOR_MAP_L2_PROMOTION_NONE);
    p.wq = make_map(enc, d_in[3], NH * DH, DM, 48, 160, CU_TENSOR_MAP_SWIZZLE_NONE, WPROMO);
    p.wo = make_map(enc, d_in[4], DM, NH * DH, 32, 48, CU_TENSOR_MAP_SWIZZLE_64B, WPROMO);
    p.wg = make_map(enc, d_in[7], FF, DM, 32, 80, CU_TENSOR_MAP_SWIZZLE_64B, WPROMO);
    p.wu = make_map(enc, d_in[8], FF, DM, 32, 80, CU_TENSOR_MAP_SWIZZLE_64B, WPROMO);
    p.wd = make_map(enc, d_in[9], DM, FF, 16, 192, CU_TENSOR_MAP_SWIZZLE_32B, WPROMO);
    p.scratch = reinterpret_cast<Scratch*>((reinterpret_cast<uintptr_t>(raw) + PAGE - 1) & ~(uintptr_t)(PAGE - 1));
    p.wq_raw = (const char*)d_in[3];
    p.x = (const __nv_bfloat16*)d_in[0];
    p.wr = (const __nv_bfloat16*)d_in[6];
    p.out = (__nv_bfloat16*)d_out;
    fused_decode_kernel<<<NCTAS, NTHREADS, SM_TOTAL, cudaStreamPerThread>>>(p);
}
```

```cpp
#include <cuda_runtime.h>
#include <cuda_bf16.h>
#include <cuda.h>
#include <stdint.h>

namespace {

constexpr int NB = 4, NH = 32, SK = 8192, DH = 192, DM = 640, FF = 1536;
constexpr int NBH = NB * NH;
constexpr int TILE = 64;
constexpr int UPB = SK / TILE;
constexpr int NUNITS = NBH * UPB;
constexpr int TILE_BYTES = TILE * DH * 2;
constexpr int TILE_ROWS = TILE * 3;
constexpr int NCTAS = 132;
constexpr int NQ_CTAS = 128;
constexpr int NE_CTAS = 112;

constexpr int SROW0 = NBH - 4;

#define NWORK 2
#define NWL 2
#define SKEW 16
#define LAG 3
#define NPOOL 896
#define RED0 120
#define RING 12
#define K0_DELAY_NS 1600
#define K0_STEP_NS 900
#define WO_AT_NS 3600
#define WO_GAP_NS 550
#define VTRIG (NPOOL - 240)
#define TRIG_NS 2200
#define GCLK 250
#define DOFF 2100
#define DCLK 150
constexpr int NAUX = 8;
constexpr int NTHREADS = (NAUX + NWORK + 2) * 32;
constexpr int SPIN_MAX = 1 << 22;

constexpr int SM_KV = 0;
constexpr int SM_A = SM_KV + NWORK * TILE_BYTES;
constexpr int SM_WQ = SM_A + 61440;
constexpr int SM_G = SM_WQ;
constexpr int SM_X = SM_G + 81920;
constexpr int XPITCH = 648;
constexpr int HPITCH = 1344;
constexpr int SM_RED = SM_X + 5 * HPITCH;
constexpr int FPITCH = 1040;
constexpr int SM_RED2 = SM_RED;
constexpr int YPITCH = 320;
constexpr int SM_MISC = SM_RED + 6144;
constexpr int BAR_KV = SM_MISC, BAR_WQ = SM_MISC + 32, BAR_W = SM_MISC + 40, SM_SIDE = SM_MISC + 48, BAR_G = SM_MISC + 64, SM_MOM = SM_MISC + 128;
constexpr int SM_TOTAL = SM_MISC + 160;

struct Scratch;
struct Params {
    CUtensorMap k, v;
    CUtensorMap wq;
    CUtensorMap wo;
    CUtensorMap wg, wu;
    CUtensorMap wd;
    Scratch* scratch;
    const char* wq_raw;
    const __nv_bfloat16 *x, *wr;
    __nv_bfloat16* out;
};

struct Early {
    uint32_t q[96];
    uint32_t umax[UPB];
};
struct State {
    float4 oacc[SROW0][64];
    float2 attn[NB][DM];
    float2 lsum[SROW0][16];
    unsigned pool[64];
    uint32_t tstart[32];
    uint32_t score[NPOOL][32];
};
constexpr int STATE_V4 = ((sizeof(State) / 32 + NQ_CTAS - 1) / NQ_CTAS) * 2;
static_assert(sizeof(State) % 32 == 0, "State is cleared in whole sectors");
static_assert(sizeof(Early) == 56 * 16, "an Early entry is cleared by 56 threads");
constexpr uint32_t X_O = 0;
constexpr uint32_t X_L = X_O + 4 * 1024;
constexpr uint32_t X_H = X_L + 4 * 128;
constexpr uint32_t X_A = X_H + NB * DM * 2;
constexpr uint32_t X_P = X_A + NB * FF * 2;
constexpr uint32_t X_END = X_P + 4096;
static_assert(X_END <= 8 * 4096 && RED0 <= SROW0, "");
struct Scratch {
    unsigned char sided[8][2][4096];
    unsigned work[64];
    unsigned cnt_z[32];
    unsigned char pad0[1024];
    Early early[NBH];
    unsigned char pad1[1024];
    State st;
    unsigned char pad2[1792];
    float4 ring[RING][UPB][64];
};
constexpr size_t PAGE = 2u << 20;
static_assert(sizeof(Scratch) <= PAGE, "scratch must fit one page");
__device__ __align__(128) unsigned char g_raw[2 * PAGE];
template <typename T> __device__ __forceinline__ T* sided(const Params& p, int side, uint32_t x) {
    const uint32_t pair = (x >> 10) & 7;
    return reinterpret_cast<T*>(&p.scratch->sided[pair][(side ^ pair) & 1]
                                    [(x & 127) + ((x & 128) << 1) + ((x & 768) << 2) + ((x >> 6) & 128) + ((x >> 5) & 512)]);
}
template <typename T> __device__ __forceinline__ T* other_side(T* p) { return reinterpret_cast<T*>(reinterpret_cast<uintptr_t>(p) ^ 4096); }
#define g_early p.scratch->early
#define g_st p.scratch->st
#define g_ring p.scratch->ring
#define g_cnt_z p.scratch->cnt_z
#define g_work p.scratch->work
#define TS(i)
#define TSW(i)
#define TS2(i)
#define TSI(n, i)
#define PH(i)
#define CK(i, dep)
#define ARR()
#define PROG(u)
#define LT(i)

__device__ __forceinline__ int row_of(int u) { return (((unsigned)u >> (7 + NWL)) << NWL) | (u & ((1 << NWL) - 1)); }
__device__ __forceinline__ int pos_of(int u) { return ((unsigned)u >> NWL) & (UPB - 1); }
__device__ __forceinline__ int tile_of(int u) { return (row_of(u) * UPB + ((pos_of(u) + (u & ((1 << NWL) - 1)) * SKEW) & (UPB - 1))) * TILE_ROWS; }

__device__ __forceinline__ uint32_t s2u(const void* p) { return (uint32_t)__cvta_generic_to_shared(p); }
__device__ __forceinline__ void mbar_init(uint32_t bar, int cnt) {
    asm volatile("mbarrier.init.shared::cta.b64 [%0], %1;" :: "r"(bar), "r"(cnt) : "memory");
}
__device__ __forceinline__ void mbar_expect_tx(uint32_t bar, uint32_t bytes) {
    asm volatile("mbarrier.arrive.expect_tx.shared::cta.b64 _, [%0], %1;" :: "r"(bar), "r"(bytes) : "memory");
}
__device__ __forceinline__ void mbar_wait(uint32_t bar, uint32_t parity) {
    asm volatile("{\n.reg .pred p;\n.reg .u32 n;\nmov.u32 n, 0;\nWAIT_LOOP:\n"
                 "mbarrier.try_wait.parity.shared::cta.b64 p, [%0], %1;\n"
                 "@p bra WAIT_DONE;\nadd.u32 n, n, 1;\nsetp.lt.u32 p, n, %2;\n@p bra WAIT_LOOP;\nWAIT_DONE:\n}"
                 :: "r"(bar), "r"(parity), "n"(SPIN_MAX) : "memory");
}
__device__ __forceinline__ void request_tile(uint32_t dst, const CUtensorMap* tm, int unit, uint32_t bar, uint64_t pol) {
    asm volatile("{\n.reg .pred p;\nelect.sync _|p, 0xffffffff;\n"
                 "@p mbarrier.arrive.expect_tx.shared::cta.b64 _, [%2], %6;\n"
                 "@p cp.async.bulk.tensor.2d.shared::cluster.global.mbarrier::complete_tx::bytes.L2::cache_hint "
                 "[%0], [%1, {%3, %4}], [%2], %5;\n}"
                 :: "r"(dst), "l"(tm), "r"(bar), "r"(0), "r"(tile_of(unit)), "l"(pol), "n"(TILE_BYTES) : "memory");
}
__device__ __forceinline__ uint32_t now_ns() { uint32_t t; asm volatile("mov.u32 %0, %%globaltimer_lo;" : "=r"(t)); return t; }
__device__ __forceinline__ uint32_t now_clk() { uint32_t t; asm volatile("mov.u32 %0, %%clock;" : "=r"(t)); return t; }
__device__ __forceinline__ void wait_clk(uint32_t t) { while (__any_sync(0xffffffffu, (int)(now_clk() - t) < 0)) {} }
__device__ __forceinline__ uint64_t evict_first() {
    uint64_t pol;
    asm volatile("createpolicy.fractional.L2::evict_first.b64 %0, 1.0;" : "=l"(pol));
    return pol;
}
__device__ __forceinline__ void request_box(uint32_t dst, const CUtensorMap* tm, int col, int row, uint32_t bar) {
    asm volatile("{\n.reg .pred p;\nelect.sync _|p, 0xffffffff;\n"
                 "@p cp.async.bulk.tensor.2d.shared::cluster.global.mbarrier::complete_tx::bytes [%0], [%1, {%3, %4}], [%2];\n}"
                 :: "r"(dst), "l"(tm), "r"(bar), "r"(col), "r"(row) : "memory");
}
__device__ __forceinline__ void request_box(uint32_t dst, const CUtensorMap* tm, int col, int row, uint32_t bar, uint64_t pol) {
    asm volatile("{\n.reg .pred p;\nelect.sync _|p, 0xffffffff;\n"
                 "@p cp.async.bulk.tensor.2d.shared::cluster.global.mbarrier::complete_tx::bytes.L2::cache_hint [%0], [%1, {%3, %4}], [%2], %5;\n}"
                 :: "r"(dst), "l"(tm), "r"(bar), "r"(col), "r"(row), "l"(pol) : "memory");
}
__device__ __forceinline__ uint32_t lds32(uint32_t addr) {
    uint32_t v;
    asm volatile("ld.shared.u32 %0, [%1];" : "=r"(v) : "r"(addr) : "memory");
    return v;
}
__device__ __forceinline__ void ldsm4(uint32_t (&r)[4], uint32_t addr) {
    asm volatile("ldmatrix.sync.aligned.m8n8.x4.shared.b16 {%0,%1,%2,%3}, [%4];"
                 : "=r"(r[0]), "=r"(r[1]), "=r"(r[2]), "=r"(r[3]) : "r"(addr) : "memory");
}
__device__ __forceinline__ void ldsm4t(uint32_t (&r)[4], uint32_t addr) {
    asm volatile("ldmatrix.sync.aligned.m8n8.x4.trans.shared.b16 {%0,%1,%2,%3}, [%4];"
                 : "=r"(r[0]), "=r"(r[1]), "=r"(r[2]), "=r"(r[3]) : "r"(addr) : "memory");
}
__device__ __forceinline__ void mma16816(float (&c)[4], const uint32_t (&a)[4], uint32_t b0, uint32_t b1) {
    asm volatile("mma.sync.aligned.m16n8k16.row.col.f32.bf16.bf16.f32 {%0,%1,%2,%3}, {%4,%5,%6,%7}, {%8,%9}, {%0,%1,%2,%3};"
                 : "+f"(c[0]), "+f"(c[1]), "+f"(c[2]), "+f"(c[3])
                 : "r"(a[0]), "r"(a[1]), "r"(a[2]), "r"(a[3]), "r"(b0), "r"(b1));
}
__device__ __forceinline__ uint4 ld_relaxed_v4(const void* p) {
    uint4 v;
    asm volatile("ld.relaxed.gpu.global.v4.u32 {%0,%1,%2,%3}, [%4];" : "=r"(v.x), "=r"(v.y), "=r"(v.z), "=r"(v.w) : "l"(p) : "memory");
    return v;
}
__device__ __forceinline__ float4 ld_relaxed_f4(const void* p) {
    float4 v;
    asm volatile("ld.relaxed.gpu.global.v4.f32 {%0,%1,%2,%3}, [%4];" : "=f"(v.x), "=f"(v.y), "=f"(v.z), "=f"(v.w) : "l"(p) : "memory");
    return v;
}
__device__ __forceinline__ float2 ld_relaxed_f2(const void* p) {
    float2 v;
    asm volatile("ld.relaxed.gpu.global.v2.f32 {%0,%1}, [%2];" : "=f"(v.x), "=f"(v.y) : "l"(p) : "memory");
    return v;
}
__device__ __forceinline__ float4 ld_relaxed_b128(const void* p) {
    float4 v;
    asm volatile("{\n.reg .b128 t;\n.reg .b64 a, b;\nld.relaxed.gpu.global.b128 t, [%4];\nmov.b128 {a, b}, t;\n"
                 "mov.b64 {%0, %1}, a;\nmov.b64 {%2, %3}, b;\n}" : "=f"(v.x), "=f"(v.y), "=f"(v.z), "=f"(v.w) : "l"(p) : "memory");
    return v;
}
__device__ __forceinline__ void st_relaxed_b128(void* p, float x, float y, float z, float w) {
    asm volatile("{\n.reg .b128 t;\n.reg .b64 a, b;\nmov.b64 a, {%1, %2};\nmov.b64 b, {%3, %4};\nmov.b128 t, {a, b};\n"
                 "st.relaxed.gpu.global.b128 [%0], t;\n}" :: "l"(p), "f"(x), "f"(y), "f"(z), "f"(w) : "memory");
}
__device__ __forceinline__ unsigned ld_acquire(const unsigned* p) {
    unsigned v;
    asm volatile("ld.acquire.gpu.global.u32 %0, [%1];" : "=r"(v) : "l"(p) : "memory");
    return v;
}
__device__ __forceinline__ void st_relaxed(void* p, uint32_t v) {
    asm volatile("st.relaxed.gpu.global.u32 [%0], %1;" :: "l"(p), "r"(v) : "memory");
}
__device__ __forceinline__ void red_f2(float* p, float a, float b) {
    asm volatile("red.relaxed.gpu.global.add.v2.f32 [%0], {%1,%2};" :: "l"(p), "f"(a), "f"(b) : "memory");
}
__device__ __forceinline__ void red_f4(float* p, float a, float b, float c, float d) {
    asm volatile("red.relaxed.gpu.global.add.v4.f32 [%0], {%1,%2,%3,%4};" :: "l"(p), "f"(a), "f"(b), "f"(c), "f"(d) : "memory");
}
__device__ __forceinline__ void draw(int& ticket, unsigned* ctr, bool pred) {
    asm volatile("{\n.reg .pred p;\nsetp.ne.u32 p, %2, 0;\n@p atom.relaxed.gpu.global.inc.u32 %0, [%1], 0x7fffffff;\n}"
                 : "+r"(ticket) : "l"(ctr), "r"((uint32_t)pred) : "memory");
}
__device__ __forceinline__ void red_release(unsigned* p) {
    asm volatile("red.release.gpu.global.add.u32 [%0], 1;" :: "l"(p) : "memory");
}
__device__ __forceinline__ uint32_t ld_relaxed_u32(const void* p) {
    uint32_t v;
    asm volatile("ld.relaxed.gpu.global.u32 %0, [%1];" : "=r"(v) : "l"(p) : "memory");
    return v;
}
__device__ __forceinline__ float rcp_approx(float v) {
    float r;
    asm("rcp.approx.ftz.f32 %0, %1;" : "=f"(r) : "f"(v));
    return r;
}
__device__ __forceinline__ float sigmoid_approx(float v) {
    float e;
    asm("ex2.approx.ftz.f32 %0, %1;" : "=f"(e) : "f"(v * -1.4426950408889634f));
    return rcp_approx(1.0f + e);
}
__device__ __forceinline__ float sqrt_approx(float v) {
    float r;
    asm("sqrt.approx.ftz.f32 %0, %1;" : "=f"(r) : "f"(v));
    return r;
}
__device__ __forceinline__ uint2 ld_relaxed_v2(const void* p) {
    uint2 v;
    asm volatile("ld.relaxed.gpu.global.v2.u32 {%0,%1}, [%2];" : "=r"(v.x), "=r"(v.y) : "l"(p) : "memory");
    return v;
}
__device__ __forceinline__ void wait_count(const unsigned* p, unsigned target) {
#pragma unroll 1
    for (int it = 0; it < SPIN_MAX; it++) {
        if (ld_acquire(p) >= target) break;
        __nanosleep(400);
    }
}
__device__ __forceinline__ float4* oacc_at(const Params& p, int side, int row, int grp) {
    return row >= SROW0 ? sided<float4>(p, side, X_O + (row - SROW0) * 1024 + grp * 16) : &g_st.oacc[row][grp];
}
__device__ __forceinline__ float2* lsum_at(const Params& p, int side, int row) {
    return row >= SROW0 ? sided<float2>(p, side, X_L + (row - SROW0) * 128) : g_st.lsum[row];
}
__device__ __forceinline__ void wait_row(const Params& p, int side, int bh, float n) {
    const float2* l = lsum_at(p, side, bh);
#pragma unroll 1
    for (int it = 0; it < SPIN_MAX; it++) {
        const float c = ld_relaxed_f2(l).y;
        if (c >= n) break;
        if (c == 0.f) __nanosleep(600);
    }
}
__device__ __forceinline__ void wait_row_o(const Params& p, int side, int bh, float n) {
    wait_row(p, side, bh, n);
    if (bh >= RED0) return;
#pragma unroll 1
    for (int it = 0; it < SPIN_MAX; it++) {
        if (__uint_as_float(ld_relaxed_u32(&g_st.oacc[bh][0].w)) == UPB) break;
        __nanosleep(300);
    }
}
__device__ __forceinline__ uint32_t pack_bf16(float lo, float hi) {
    uint32_t r;
    asm("cvt.rn.bf16x2.f32 %0, %1, %2;" : "=r"(r) : "f"(hi), "f"(lo));
    return r;
}
__device__ __forceinline__ float bf16r(float v) { return __uint_as_float(pack_bf16(0.f, v)); }
__device__ __forceinline__ uint32_t pack_neg(float lo, float hi) {
    const uint32_t w = pack_bf16(-lo, -hi);
    return w ? w : 0x80008000u;
}
__device__ __forceinline__ float lo_f(uint32_t v) { return __uint_as_float(v << 16); }
__device__ __forceinline__ float hi_f(uint32_t v) { return __uint_as_float(v & 0xffff0000u); }
__device__ __forceinline__ float warp_sum(float v) {
#pragma unroll
    for (int o = 16; o; o >>= 1) v += __shfl_xor_sync(0xffffffffu, v, o);
    return v;
}
__device__ __forceinline__ void layernorm20(float (&v)[20]) {
    float s = 0.f;
#pragma unroll
    for (int i = 0; i < 20; i++) s += v[i];
    const float mean = warp_sum(s) * (1.0f / DM);
    float q = 0.f;
#pragma unroll
    for (int i = 0; i < 20; i++) { const float d = v[i] - mean; q += d * d; }
    const float var = bf16r(warp_sum(q) * (1.0f / DM));
    const float m = bf16r(mean);
    const float rden = 1.0f / bf16r(sqrtf(bf16r(var + 1e-5f)));
#pragma unroll
    for (int i = 0; i < 20; i++) v[i] = bf16r(bf16r(v[i] - m) * rden);
}

__device__ __forceinline__ float sel4(int j, float a, float b, float c, float d) {
    float lo, hi, r;
    asm("{\n.reg .pred p;\nsetp.ne.s32 p, %3, 0;\nselp.f32 %0, %2, %1, p;\n}" : "=f"(lo) : "f"(a), "f"(b), "r"(j & 1));
    asm("{\n.reg .pred p;\nsetp.ne.s32 p, %3, 0;\nselp.f32 %0, %2, %1, p;\n}" : "=f"(hi) : "f"(c), "f"(d), "r"(j & 1));
    asm("{\n.reg .pred p;\nsetp.ne.s32 p, %3, 0;\nselp.f32 %0, %2, %1, p;\n}" : "=f"(r) : "f"(lo), "f"(hi), "r"(j & 2));
    return r;
}
template <typename T> __device__ __forceinline__ void pin(T*& p) { asm volatile("" : "+l"(p)); }
__device__ __forceinline__ void pin(uint32_t& v) { asm volatile("" : "+r"(v)); }
__device__ __forceinline__ void pin(float& v) { asm volatile("" : "+f"(v)); }
__device__ __forceinline__ void hold(uint32_t& v) { v = __shfl_xor_sync(0xffffffffu, v, 0); }
template <typename T> __device__ __forceinline__ void hold(T*& p) {
    p = reinterpret_cast<T*>(__shfl_xor_sync(0xffffffffu, (unsigned long long)reinterpret_cast<uintptr_t>(p), 0));
}
__device__ __forceinline__ uint32_t after(uint32_t n, float v) {
    asm volatile("{\n.reg .pred p;\nsetp.eq.u32 p, %1, 0x7fc1a5a5;\n@p add.u32 %0, %0, 32;\n}" : "+r"(n) : "r"(__float_as_uint(v)));
    return n;
}
__device__ __forceinline__ float2 lds64f(uint32_t addr) {
    float2 v;
    asm volatile("ld.shared.v2.f32 {%0,%1}, [%2];" : "=f"(v.x), "=f"(v.y) : "r"(addr) : "memory");
    return v;
}
__device__ __forceinline__ float4 lds128f(uint32_t addr) {
    float4 v;
    asm volatile("ld.shared.v4.f32 {%0,%1,%2,%3}, [%4];" : "=f"(v.x), "=f"(v.y), "=f"(v.z), "=f"(v.w) : "r"(addr) : "memory");
    return v;
}
__device__ __forceinline__ void sts64f(uint32_t addr, float a, float b, bool pred) {
    asm volatile("{\n.reg .pred p;\nsetp.ne.u32 p, %3, 0;\n@p st.shared.v2.f32 [%0], {%1,%2};\n}" :: "r"(addr), "f"(a), "f"(b), "r"((uint32_t)pred) : "memory");
}
__device__ __forceinline__ void sts128f(uint32_t addr, float a, float b, float c, float d, bool pred) {
    asm volatile("{\n.reg .pred p;\nsetp.ne.u32 p, %5, 0;\n@p st.shared.v4.f32 [%0], {%1,%2,%3,%4};\n}"
                 :: "r"(addr), "f"(a), "f"(b), "f"(c), "f"(d), "r"((uint32_t)pred) : "memory");
}
__device__ __forceinline__ void lds128_if(uint4& v, uint32_t addr, bool pred) {
    asm volatile("{\n.reg .pred p;\nsetp.ne.u32 p, %5, 0;\n@p ld.shared.v4.u32 {%0,%1,%2,%3}, [%4];\n}"
                 : "+r"(v.x), "+r"(v.y), "+r"(v.z), "+r"(v.w) : "r"(addr), "r"((uint32_t)pred) : "memory");
}
__device__ __forceinline__ void sts32f(uint32_t addr, float v) { asm volatile("st.shared.f32 [%0], %1;" :: "r"(addr), "f"(v) : "memory"); }
template <int ID> __device__ __forceinline__ void fin_arrive() { asm volatile("bar.arrive %0, 288;" :: "n"(ID) : "memory"); }
template <int ID> __device__ __forceinline__ void fin_sync() { asm volatile("bar.sync %0, 288;" :: "n"(ID) : "memory"); }
template <int ID> __device__ __forceinline__ void fin_sync(uint32_t n) { asm volatile("bar.sync %0, %1;" :: "n"(ID), "r"(n) : "memory"); }
__device__ __forceinline__ float2 sum8(uint32_t addr) {
    float2 t[8];
#pragma unroll
    for (int w = 0; w < 8; w++) t[w] = lds64f(addr + w * 128);
    return make_float2(((t[0].x + t[1].x) + (t[2].x + t[3].x)) + ((t[4].x + t[5].x) + (t[6].x + t[7].x)),
                       ((t[0].y + t[1].y) + (t[2].y + t[3].y)) + ((t[4].y + t[5].y) + (t[6].y + t[7].y)));
}
__device__ __forceinline__ float4 sum4x4(uint32_t addr) {
    float4 t[4];
#pragma unroll
    for (int w = 0; w < 4; w++) t[w] = lds128f(addr + w * 256);
    return make_float4((t[0].x + t[1].x) + (t[2].x + t[3].x), (t[0].y + t[1].y) + (t[2].y + t[3].y),
                       (t[0].z + t[1].z) + (t[2].z + t[3].z), (t[0].w + t[1].w) + (t[2].w + t[3].w));
}
template <int NJ>
__device__ __forceinline__ void load_o(const Params& p, uint32_t (&ob)[3 * NJ][2], int bh, int J0, int j) {
    float4 v[NJ][4];
    float2 l;
#pragma unroll 1
    for (int it = 0; it < SPIN_MAX; it++) {
#pragma unroll
        for (int J = 0; J < NJ; J++) {
#pragma unroll
            for (int e = 0; e < 4; e++) v[J][e] = ld_relaxed_f4(&g_st.oacc[bh][(J0 + J) * 16 + e * 4 + j]);
        }
        l = ld_relaxed_f2(g_st.lsum[bh]);
        bool ok = l.y == UPB;
#pragma unroll
        for (int J = 0; J < NJ; J++) {
#pragma unroll
            for (int e = 0; e < 4; e++) ok &= v[J][e].w == UPB;
        }
        if (__all_sync(0xffffffffu, ok)) break;
    }
    const float rl = __fdividef(1.0f, l.x);
#pragma unroll
    for (int J = 0; J < NJ; J++) {
        ob[3 * J][0] = pack_bf16(v[J][0].x * rl, v[J][1].x * rl);     ob[3 * J][1] = pack_bf16(v[J][2].x * rl, v[J][3].x * rl);
        ob[3 * J + 1][0] = pack_bf16(v[J][0].y * rl, v[J][1].y * rl); ob[3 * J + 1][1] = pack_bf16(v[J][2].y * rl, v[J][3].y * rl);
        ob[3 * J + 2][0] = pack_bf16(v[J][0].z * rl, v[J][1].z * rl); ob[3 * J + 2][1] = pack_bf16(v[J][2].z * rl, v[J][3].z * rl);
    }
}
__device__ __forceinline__ void aux_sync() { asm volatile("bar.sync 1, 256;" ::: "memory"); }

__global__ void __launch_bounds__(NTHREADS, 1)
fused_decode_kernel(const __grid_constant__ Params p) {
    extern __shared__ __align__(1024) unsigned char smem[];
    if (threadIdx.x < 128) asm volatile("prefetch.global.L2 [%0];" :: "l"(p.wq_raw + (blockIdx.x * 128 + threadIdx.x) * 128));
    const uint32_t sb = s2u(smem);
    const int tid = threadIdx.x, warp = __shfl_sync(0xffffffffu, tid >> 5, 0), lane = tid & 31;
    const int cta = blockIdx.x;
    constexpr int grid = NCTAS;
    const int g = lane >> 2, j = lane & 3;
    const bool is_l = cta >= NE_CTAS, is_f = cta < 96 && !(cta & 1), is_g = cta < 80 && (cta & 1);
    const int fidx = cta >> 1;

    TS(0);
    if (warp == 4 && cta < NQ_CTAS) {
        asm volatile("{\n.reg .pred p;\nelect.sync _|p, 0xffffffff;\n"
                     "@p mbarrier.init.shared::cta.b64 [%0], 1;\n"
                     "@p fence.mbarrier_init.release.cluster;\n"
                     "@p mbarrier.arrive.expect_tx.shared::cta.b64 _, [%0], 61440;\n}" :: "r"(sb + BAR_WQ) : "memory");
#pragma unroll
        for (int i = 0; i < 4; i++) request_box(sb + SM_WQ + i * 15360, &p.wq, cta * 48, i * 160, sb + BAR_WQ);
    }
    if (tid == 160) {
#pragma unroll
        for (int w = 0; w < NWORK; w++) mbar_init(sb + BAR_KV + w * 8, 1);
        mbar_init(sb + BAR_W, 1);
#pragma unroll
        for (int w = 0; w < 8; w++) mbar_init(sb + BAR_G + w * 8, 1);
        asm volatile("fence.mbarrier_init.release.cluster;" ::: "memory");
    }
    __syncthreads();
    if (warp == NAUX + NWORK + 1) {
        uint32_t t = now_clk() + 2 * WO_AT_NS;
        const uint64_t pol = evict_first();
        if (lane == 0) mbar_expect_tx(sb + BAR_W, is_l ? 49152 : 61440);
#pragma unroll 1
        for (int r = 0; r < DH; r += 48, t += 2 * WO_GAP_NS) {
            wait_clk(t);
#pragma unroll 1
            for (int i = 0; i < (is_l ? 4 : 5); i++)
                request_box(sb + SM_A + i * 12288 + r * 64, &p.wo, is_l ? (cta - NE_CTAS) * 32 : (cta & 3) * 160 + i * 32,
                            (is_l ? 28 + i : cta >> 2) * DH + r, sb + BAR_W, pol);
        }
        if (!is_f && !is_g) return;
        if (lane < 8) mbar_expect_tx(sb + BAR_G + lane * 8, is_f ? 10240 : 6144);
        asm volatile("bar.sync 9, 288;" ::: "memory");
        asm volatile("fence.proxy.async.shared::cta;" ::: "memory");
#pragma unroll 1
        for (int it = 0; it < SPIN_MAX; it++) {
            t = ld_relaxed_u32(g_st.tstart);
            if (__all_sync(0xffffffffu, t != 0)) break;
            __nanosleep(400);
        }
#pragma unroll 1
        for (int it = 0; it < SPIN_MAX; it++) if (__all_sync(0xffffffffu, t - now_ns() > 2 * TRIG_NS)) break;
        TSW(11);
        t = now_clk() + (is_f ? 0 : DOFF);
#pragma unroll 1
        for (int i = 0; i < 8; i++, t += is_f ? GCLK : DCLK) {
            wait_clk(t);
            if (is_f) {
                request_box(sb + SM_G + i * 5120, &p.wg, fidx * 32, i * 80, sb + BAR_G + i * 8);
                request_box(sb + SM_G + 40960 + i * 5120, &p.wu, fidx * 32, i * 80, sb + BAR_G + i * 8);
            } else {
                request_box(sb + SM_G + i * 6144, &p.wd, fidx * 16, i * 192, sb + BAR_G + i * 8);
            }
        }
        return;
    }
    if (warp == NAUX + NWORK) {
        if (cta < NQ_CTAS) {
            wait_clk(now_clk() + 4000);
#pragma unroll
            for (int i = lane; i < STATE_V4; i += 32)
                if (cta * STATE_V4 + i < (int)(sizeof(State) / 16)) reinterpret_cast<uint4*>(&g_st)[cta * STATE_V4 + i] = make_uint4(0u, 0u, 0u, 0u);
            if (cta * 512 < X_END) {
                uint4* z = sided<uint4>(p, 0, cta * 512 + lane * 16);
                *z = make_uint4(0u, 0u, 0u, 0u);
                *other_side(z) = make_uint4(0u, 0u, 0u, 0u);
            }
            __syncwarp();
            if (lane == 0) red_release(g_cnt_z);
        }
        if (lane == 0) { TS2(2); wait_count(g_cnt_z, NQ_CTAS); TS2(29); }
        __syncwarp();
        asm volatile("bar.arrive 2, %0;" :: "n"((NWORK + 1) * 32) : "memory");
        uint32_t rtt[2] = {0xffffffffu, 0xffffffffu};
        if (lane == 0) {
#pragma unroll 1
            for (int r = 0; r < 12; r++) {
                int v = 0;
                uint32_t t1 = 0;
                unsigned* ctr = sided<unsigned>(p, r & 1, X_P + ((cta * 32 + (r >> 1) * 768) & 4095));
                pin(ctr);
                const uint32_t t0 = now_clk();
                draw(v, ctr, true);
                asm volatile("{\n.reg .pred q;\nsetp.ge.s32 q, %1, 0;\n@q mov.u32 %0, %%clock;\n}" : "+r"(t1) : "r"(v) : "memory");
                if (r & 1) rtt[1] = min(rtt[1], t1 - t0); else rtt[0] = min(rtt[0], t1 - t0);
            }
            sts32f(sb + SM_SIDE, __int_as_float(rtt[1] < rtt[0]));
        }
        const int side = __shfl_sync(0xffffffffu, rtt[1] < rtt[0], 0);
        fin_arrive<3>();
        int job = cta;
        auto sum_rows = [&](int row_end) {
#pragma unroll 1
            for (; job < 8 * min(row_end, RED0); job += NCTAS) {
                const int row = job >> 3, grp = (job & 7) * 8 + (lane & 7);
                if (lane == 0) wait_row(p, side, row, UPB);
                __syncwarp();
                const float4* src = &g_ring[row % RING][lane >> 3][grp];
                float sx = 0.f, sy = 0.f, sz = 0.f;
#pragma unroll 1
                for (int i = 0; i < 2; i++, src += 64 * 64) {
                    float4 v[16];
#pragma unroll 1
                    for (int it = 0; it < SPIN_MAX; it++) {
                        bool ok = true;
#pragma unroll
                        for (int k = 0; k < 16; k++) v[k] = ld_relaxed_b128(src + k * 4 * 64);
#pragma unroll
                        for (int k = 0; k < 16; k++) ok &= v[k].w == (float)(row + 1);
                        if (__all_sync(0xffffffffu, ok)) break;
                    }
#pragma unroll
                    for (int k = 0; k < 16; k++) { sx += v[k].x; sy += v[k].y; sz += v[k].z; }
                }
#pragma unroll
                for (int o = 8; o < 32; o <<= 1) {
                    sx += __shfl_xor_sync(0xffffffffu, sx, o); sy += __shfl_xor_sync(0xffffffffu, sy, o); sz += __shfl_xor_sync(0xffffffffu, sz, o);
                }
                if (lane < 8) st_relaxed_b128(&g_st.oacc[row][grp], sx, sy, sz, UPB);
            }
        };
        {
            uint32_t wr[10];
            float wsum = 0.f;
#pragma unroll
            for (int i = 0; i < 10; i++) {
                const int w = 4 * lane + 128 * (i >> 2) + (i & 3) - (i >= 8 ? 2 * lane : 0);
                wr[i] = *reinterpret_cast<const uint32_t*>(p.wr + (w >> 4) * 32 + (w & 3) * 8 + ((w >> 1) & 6));
                wsum += lo_f(wr[i]) + hi_f(wr[i]);
            }
            wsum = warp_sum(wsum);
            const int lb = lane >> 3, lc = lane & 7;
            uint32_t ypart = sb + SM_RED2 + (lb >> 1) * 160 + lc * 16 + (lb & 1) * 8;
            __nv_bfloat16* out = p.out + lb * DM + fidx * 16 + lc;
            float nmean_l = 0.f, rden_l = 0.f, sig_l = 0.f;
#pragma unroll 1
            for (int b = 0; b < NB; b++) {
                const uint32_t hx = X_H + b * (DM * 2), hrow = sb + SM_X + b * HPITCH;
                const uint4 *src0 = sided<uint4>(p, side, hx + 16 * lane), *src1 = sided<uint4>(p, side, hx + 512 + 16 * lane);
                const uint2* src2 = sided<uint2>(p, side, hx + 1024 + 8 * lane);
                sum_rows((b + 1) * NH);
                if (!is_l && !is_f && !is_g) continue;
                pin(src0); pin(src1); pin(src2); pin(ypart); pin(out);
                if (lane == 0) wait_row(p, side, b * NH + (is_l ? 28 : NH - 1), is_l ? 1 : 100);
                __syncwarp();
                if (is_l) {
                    const int col = (cta - NE_CTAS) * 32 + 2 * (lane & 15);
                    uint32_t lpart = sb + SM_RED + (lane & 15) * 8;
                    const uint32_t xv = *reinterpret_cast<const uint32_t*>(p.x + b * DM + col);
                    uint32_t* hdst = sided<uint32_t>(p, lane >> 4, hx + 4 * ((col >> 5) * 16 + (col & 6) * 2 + ((col >> 3) & 3)));
                    float4 early;
#pragma unroll 1
                    for (int it = 0; it < SPIN_MAX; it++) {
                        early = ld_relaxed_f4(&g_st.attn[b][col]);
                        if (__all_sync(0xffffffffu, early.y == NE_CTAS / 4 && early.w == NE_CTAS / 4)) break;
                    }
                    if (lane == 0) TS2(23);
                    float x0 = lo_f(xv), x1 = hi_f(xv);
                    pin(hdst); pin(lpart); pin(x0); pin(x1);
                    fin_sync<4>();
                    CK(2, lds32(sb + SM_RED));
                    const float2 late = sum8(lpart);
                    const uint32_t nh = pack_bf16(-x0 - bf16r(early.x + late.x), -x1 - bf16r(early.z + late.y));
                    st_relaxed(hdst, nh ? nh : 0x80008000u);
                    CK(3, 0);
                    if (lane == 0) TS2(15);
                    fin_sync<5>();
                    continue;
                }
                uint4 h0, h1;
                uint2 h2;
                float mm[5][4];
#pragma unroll 1
                for (int it = 0; it < SPIN_MAX; it++) {
                    h0 = ld_relaxed_v4(src0);
                    h1 = ld_relaxed_v4(src1);
                    h2 = ld_relaxed_v2(src2);
                    asm volatile("st.shared.v4.u32 [%0], {%1,%2,%3,%4};" :: "r"(hrow + lane * 16), "r"(h0.x), "r"(h0.y), "r"(h0.z), "r"(h0.w) : "memory");
                    asm volatile("st.shared.v4.u32 [%0], {%1,%2,%3,%4};" :: "r"(hrow + 512 + lane * 16), "r"(h1.x), "r"(h1.y), "r"(h1.z), "r"(h1.w) : "memory");
                    asm volatile("st.shared.v2.u32 [%0], {%1,%2};" :: "r"(hrow + 1024 + lane * 8), "r"(h2.x), "r"(h2.y) : "memory");
                    const uint32_t w[10] = {h0.x, h0.y, h0.z, h0.w, h1.x, h1.y, h1.z, h1.w, h2.x, h2.y};
#pragma unroll
                    for (int i = 0; i < 5; i++) {
                        const uint32_t a[4] = {w[2 * i], 0x3f803f80u, w[2 * i + 1], 0x3f803f80u};
                        mm[i][0] = mm[i][1] = mm[i][2] = mm[i][3] = 0.f;
                        mma16816(mm[i], a, w[2 * i], w[2 * i + 1]);
                    }
                    const uint32_t lo = min(min(min(h0.x, h0.y), min(h0.z, h0.w)), min(min(min(h1.x, h1.y), min(h1.z, h1.w)), min(h2.x, h2.y)));
                    const bool ok = __all_sync(0xffffffffu, lo != 0 || it == SPIN_MAX - 1);
                    asm volatile("{\n.reg .pred p;\nsetp.ne.u32 p, %0, 0;\n@p bar.arrive 7, 288;\n}" :: "r"((uint32_t)ok) : "memory");
                    if (ok) break;
                    if (!is_f) __nanosleep(100);
                }
                CK(4, h0.x);
                if (lane == 0 && is_f) TS2(12);
                const uint32_t hw[10] = {h0.x, h0.y, h0.z, h0.w, h1.x, h1.y, h1.z, h1.w, h2.x, h2.y};
                float m1 = ((mm[0][2] + mm[1][2]) + (mm[2][2] + mm[3][2])) + ((mm[0][3] + mm[1][3]) + (mm[2][3] + mm[3][3])) + (mm[4][2] + mm[4][3]);
                float m2 = (g & 1) ? ((mm[0][1] + mm[1][1]) + (mm[2][1] + mm[3][1])) + mm[4][1] : ((mm[0][0] + mm[1][0]) + (mm[2][0] + mm[3][0])) + mm[4][0];
                m2 += __shfl_xor_sync(0xffffffffu, m2, 4);
                m1 = (m1 + __shfl_xor_sync(0xffffffffu, m1, 1)) + (__shfl_xor_sync(0xffffffffu, m1, 2) + __shfl_xor_sync(0xffffffffu, m1, 3));
                m2 = (__shfl_sync(0xffffffffu, m2, 0) + __shfl_sync(0xffffffffu, m2, 9)) + (__shfl_sync(0xffffffffu, m2, 18) + __shfl_sync(0xffffffffu, m2, 27));
                m1 *= 1.0f / DM;
                const float nmean = bf16r(m1);
                const float var = bf16r(fmaxf(fmaf(-m1, m1, m2 * (1.0f / DM)), 0.f));
                const float den = bf16r(sqrt_approx(bf16r(var + 1e-5f)));
                if (is_f) {
                    sts64f(sb + SM_MOM + b * 8, nmean, den, lane == 0);
                    CK(5, 0);
                    fin_arrive<4>();
                } else {
                    const float rden = rcp_approx(den);
                    if (lb == b) { nmean_l = nmean; rden_l = rden; }
                    __syncwarp();
                    const float2 hw2 = lds64f(sb + SM_X + lb * HPITCH + ((fidx >> 1) * 16 + (lc & 6) * 2 + (fidx & 1) * 2) * 4);
                    const float nh0 = (lc & 1) ? hi_f(__float_as_uint(hw2.x)) : lo_f(__float_as_uint(hw2.x));
                    const float nh1 = (lc & 1) ? hi_f(__float_as_uint(hw2.y)) : lo_f(__float_as_uint(hw2.y));
                    float rr = 0.f;
#pragma unroll
                    for (int i = 0; i < 10; i++) rr = fmaf(lo_f(hw[i]), lo_f(wr[i]), fmaf(hi_f(hw[i]), hi_f(wr[i]), rr));
                    const float sig = bf16r(sigmoid_approx(bf16r((nmean * wsum - warp_sum(rr)) * rden)));
                    if (lb == b) sig_l = sig;
                    const float ln0 = bf16r(bf16r(nmean_l - nh0) * rden_l), ln1 = bf16r(bf16r(nmean_l - nh1) * rden_l);
                    fin_sync<6>(after(after(after(288, sig_l), ln0), ln1));
                    CK(10, lds32(ypart));
                    float2 t[16];
#pragma unroll
                    for (int i = 0; i < 16; i++) t[i] = lds64f(ypart + i * YPITCH);
#pragma unroll
                    for (int o = 1; o < 16; o <<= 1) {
#pragma unroll
                        for (int i = 0; i < 16; i += 2 * o) { t[i].x += t[i + o].x; t[i].y += t[i + o].y; }
                    }
                    const uint32_t o0 = pack_bf16(bf16r(ln0 - bf16r(bf16r(t[0].x) * sig_l)) - nh0, 0.f);
                    const uint32_t o1 = pack_bf16(bf16r(ln1 - bf16r(bf16r(t[0].y) * sig_l)) - nh1, 0.f);
                    asm volatile("{\n.reg .pred p;\nsetp.eq.u32 p, %3, 3;\n@p st.global.u16 [%0], %1;\n@p st.global.u16 [%0 + 16], %2;\n}"
                                 :: "l"(out), "h"((unsigned short)o0), "h"((unsigned short)o1), "r"(b) : "memory");
                    if (b == NB - 1) return;
                    CK(11, 0);
                    if (lane == 0) TS2(13);
                }
                if (b < NB - 1) fin_sync<5>();
            }
            if (cta == 0 && lane == 0) { g_work[0] = 0; g_cnt_z[0] = 0; }
        }
        return;
    }
    if (warp >= NAUX) {
        const int wk = warp - NAUX;
        const uint32_t bar = sb + BAR_KV + wk * 8;
        const uint32_t buf = sb + SM_KV + wk * TILE_BYTES;
        const uint64_t pol = evict_first();
        const int nstatic = NWORK * grid;
        constexpr int POOL0 = NUNITS - NPOOL;
        int uk = wk * grid + cta;
        wait_clk(now_clk() + 2 * (K0_DELAY_NS + wk * K0_STEP_NS));
        request_tile(buf, &p.k, uk, bar, pol);
        uint32_t koff[3], voff[3];
        {
            const int r = lane & 7, hf = (lane >> 3) & 1;
            const int kkey = hf ? 8 + (r ^ 1) : r;
            const int vh = lane >> 4;
            const int vkey = ((r & 1) ? 8 : 0) + (vh ? (r ^ 1) : r);
#pragma unroll
            for (int b = 0; b < 3; b++) {
                const int rk = 3 * kkey + b, rv = 3 * vkey + b;
                koff[b] = buf + rk * 128 + (((lane >> 4) ^ (rk & 7)) << 4);
                voff[b] = buf + rv * 128 + ((hf ^ (rv & 7)) << 4);
            }
        }
        uint32_t phase = 0;
        uint4 qf[6];
        auto load_q = [&](int u) {
            const uint32_t* q = &g_early[row_of(u)].q[j * 4];
#pragma unroll
            for (int i = 0; i < 6; i++) qf[i] = ld_relaxed_v4(q + i * 16);
        };
        load_q(uk);
        int uq[LAG];
        uint32_t sq[LAG];
#pragma unroll
        for (int i = 0; i < LAG; i++) { uq[i] = -1; sq[i] = 0; }
        uint4 mv = make_uint4(0u, 0u, 0u, 0u);
        uint32_t svp = 0;
        float freed = UPB;
        while (true) {
            const int uv = uq[0];
            uint32_t sv = sq[0];
#pragma unroll
            for (int i = 0; i + 1 < LAG; i++) { uq[i] = uq[i + 1]; sq[i] = sq[i + 1]; }
            uq[LAG - 1] = uk;
            if (uk < NUNITS) {
                PH(7);
#pragma unroll 1
                for (int it = 0; it < SPIN_MAX; it++) {
                    uint32_t lo = 0xffffffffu;
#pragma unroll
                    for (int i = 0; i < 6; i++) lo = min(min(lo, min(qf[i].x, qf[i].y)), min(qf[i].z, qf[i].w));
                    if (__all_sync(0xffffffffu, lo != 0)) break;
                    __nanosleep(250);
                    load_q(uk);
                }
                mbar_wait(bar, phase); phase ^= 1;
                PH(0); ARR();
                TSI(0, 16); TSI(1, 18);
                float acc[2][4][4] = {};
#pragma unroll
                for (int ks = 0; ks < 12; ks++) {
                    const uint4 qq = qf[ks >> 1];
                    const uint32_t b0 = (ks & 1) ? qq.z : qq.x, b1 = (ks & 1) ? qq.w : qq.y;
#pragma unroll
                    for (int mt = 0; mt < 4; mt++) {
                        uint32_t a[4];
                        ldsm4(a, (koff[ks >> 2] ^ ((ks & 3) << 5)) + mt * 6144);
                        mma16816(acc[ks & 1][mt], a, b0, b1);
                    }
                }
                PH(1);
                TSI(0, 17); TSI(1, 19);
                if (uv < NUNITS) request_tile(buf, uv >= 0 ? &p.v : &p.k, uv >= 0 ? uv : uk + nstatic, bar, pol);
                const float sa = sel4(j, acc[0][0][0], acc[0][1][0], acc[0][2][0], acc[0][3][0]) + sel4(j, acc[1][0][0], acc[1][1][0], acc[1][2][0], acc[1][3][0]);
                const float sc = sel4(j, acc[0][0][2], acc[0][1][2], acc[0][2][2], acc[0][3][2]) + sel4(j, acc[1][0][2], acc[1][1][2], acc[1][2][2], acc[1][3][2]);
                const uint32_t raw = pack_bf16(sa, sc);
                const float scale = -0.07216878364870322f;
                const uint32_t sk = pack_bf16(lo_f(raw) * scale, hi_f(raw) * scale);
                sq[LAG - 1] = sk;
                if (uk >= POOL0) st_relaxed(&g_st.score[uk - POOL0][lane], sk ? sk : 0x80008000u);
                int a = (int)(sk << 16), b = (int)(sk & 0xffff0000u);
                a ^= (a >> 31) & 0x7fff0000; b ^= (b >> 31) & 0x7fff0000;
                const int mx = __reduce_max_sync(0xffffffffu, max(a, b));
                if (lane == 0) st_relaxed(&g_early[row_of(uk)].umax[pos_of(uk)], (uint32_t)mx | 1u);
            }
            if (uv < 0) {
                uk += nstatic;
                load_q(uk);
                continue;
            }
            if (uv >= NUNITS) break;
            const int bh = row_of(uv);
#pragma unroll 1
            for (int it = 0; it < SPIN_MAX; it++) {
                if (__all_sync(0xffffffffu, (mv.x & mv.y & mv.z & mv.w & 1u) && (uv < POOL0 || svp != 0) && freed == UPB)) break;
                mv = ld_relaxed_v4(&g_early[bh].umax[lane * 4]);
                if (bh >= RING && bh < RED0) freed = __uint_as_float(ld_relaxed_u32(&g_st.oacc[bh - RING][(lane & 7) * 8].w));
                if (uv >= POOL0) svp = ld_relaxed_u32(&g_st.score[uv - POOL0][lane]);
            }
            if (uv >= POOL0) sv = svp;
            PH(2);
            int un = NUNITS, vn = 0;
            draw(un, g_work, uk < NUNITS && lane == 0);
            int mx = __reduce_max_sync(0xffffffffu, max(max((int)mv.x, (int)mv.y), max((int)mv.z, (int)mv.w))) & 0xffff0000;
            mx ^= (mx >> 31) & 0x7fff0000;
            const float m = __int_as_float(mx);
            const float l2e = 1.4426950408889634f;
            const uint32_t pp = pack_bf16(exp2f((lo_f(sv) - m) * l2e), exp2f((hi_f(sv) - m) * l2e));
            uint32_t pb[8];
#pragma unroll
            for (int t = 0; t < 4; t++) {
                pb[2 * t] = __shfl_sync(0xffffffffu, pp, 8 * j + t);
                pb[2 * t + 1] = __shfl_sync(0xffffffffu, pp, 8 * j + 4 + t);
            }
            float lacc[4] = {};
            const uint32_t ones[4] = {0x3f803f80u, 0x3f803f80u, 0x3f803f80u, 0x3f803f80u};
#pragma unroll
            for (int t = 0; t < 4; t++) mma16816(lacc, ones, pb[2 * t], pb[2 * t + 1]);
            if (uv < nstatic) {
                asm volatile("bar.sync 2, %0;" :: "n"((NWORK + 1) * 32) : "memory");
                TSW(3);
            }
            const int grp = 16 * j + 4 * (g & 1) + (g >> 1);
            float4* dst = bh < RED0 ? &g_ring[bh % RING][pos_of(uv)][grp] : oacc_at(p, lds32(sb + SM_SIDE) ^ 1, bh, grp);
            float4* dst2 = other_side(dst);
            float2* ldst = lsum_at(p, lane & 1, bh);
            if (bh >= SROW0 && lane < 2) red_f2(&ldst->x, lacc[0], 1.f);
            float tag = bh < RED0 ? (float)(bh + 1) : 1.f;
            un = __shfl_sync(0xffffffffu, un, 0) + (LAG + 1) * nstatic;
            uint32_t pooled = uq[0] >= POOL0 && lane == 0;
            pin(dst); pin(dst2); pin(ldst); pin(tag); pin(voff[0]); pin(voff[1]); pin(voff[2]); pin(pooled);
            PH(3);
            LT(1);
            mbar_wait(bar, phase); phase ^= 1;
            PH(4); ARR();
            LT(2);
            draw(vn, g_st.pool, pooled);
            float acc[12][4] = {};
#pragma unroll
            for (int t = 0; t < 4; t++) {
#pragma unroll
                for (int mt = 0; mt < 12; mt++) {
                    uint32_t a[4];
                    ldsm4t(a, (voff[mt >> 2] ^ ((mt & 3) << 5)) + t * 6144);
                    mma16816(acc[mt], a, pb[2 * t], pb[2 * t + 1]);
                }
            }
            PH(5);
            if (lane == 0) PROG(un);
            if (un < NUNITS) request_tile(buf, &p.k, un, bar, pol);
            float o[6];
#pragma unroll
            for (int e = 0; e < 6; e++) {
                const int q = e % 3, c = (e / 3) * 2;
                o[e] = sel4(j, acc[q][c], acc[3 + q][c], acc[6 + q][c], acc[9 + q][c]);
            }
            if (bh >= SROW0) {
                red_f4(&dst->x, o[0], o[1], o[2], tag);
                red_f4(&dst[16].x, o[3], o[4], o[5], tag);
                red_f4(&dst2->x, o[0], o[1], o[2], tag);
                red_f4(&dst2[16].x, o[3], o[4], o[5], tag);
            } else {
                if (bh >= RED0) {
                    red_f4(&dst->x, o[0], o[1], o[2], tag);
                    red_f4(&dst[8].x, o[3], o[4], o[5], tag);
                } else {
                    st_relaxed_b128(dst, o[0], o[1], o[2], tag);
                    st_relaxed_b128(dst + 8, o[3], o[4], o[5], tag);
                }
                if (lane == 0) red_f2(&ldst->x, lacc[0], 1.f);
            }
            if (uq[0] >= POOL0) {
                vn = __shfl_sync(0xffffffffu, vn, 0);
                uq[0] = POOL0 + vn;
                if (vn == VTRIG && lane == 0) st_relaxed(g_st.tstart, (now_ns() + TRIG_NS) | 1u);
            }
            if (un < NUNITS) load_q(un);
            PH(6);
            if (uq[0] >= NUNITS && un >= NUNITS) break;
            uk = un;
            if (uq[0] < NUNITS) {
                const int nb = row_of(uq[0]);
                mv = ld_relaxed_v4(&g_early[nb].umax[lane * 4]);
                freed = nb >= RING && nb < RED0 ? __uint_as_float(ld_relaxed_u32(&g_st.oacc[nb - RING][(lane & 7) * 8].w)) : UPB;
                if (uq[0] >= POOL0) svp = ld_relaxed_u32(&g_st.score[uq[0] - POOL0][lane]);
                if (un >= NUNITS) {
                    request_tile(buf, &p.v, uq[0], bar, pol);
                    LT(0);
                }
            }
        }
        if (is_f) asm volatile("bar.arrive 10, %0;" :: "n"((NAUX + NWORK) * 32) : "memory");
        return;
    }

    __nv_bfloat16* xs = reinterpret_cast<__nv_bfloat16*>(smem + SM_X);
    float* red = reinterpret_cast<float*>(smem + SM_RED);
    const int frow = (lane & 7) + ((lane >> 4) << 3), fcol = (lane >> 3) & 1;
    if (cta < NQ_CTAS) {
        uint2 xr[5];
        if (warp < NB) {
#pragma unroll
            for (int i = 0; i < 5; i++) xr[i] = *reinterpret_cast<const uint2*>(p.x + warp * DM + i * 128 + lane * 4);
        }
        TS(26);
        if (warp < NB) {
            float v[20];
#pragma unroll
            for (int i = 0; i < 5; i++) {
                v[4 * i] = lo_f(xr[i].x); v[4 * i + 1] = hi_f(xr[i].x); v[4 * i + 2] = lo_f(xr[i].y); v[4 * i + 3] = hi_f(xr[i].y);
            }
            layernorm20(v);
#pragma unroll
            for (int i = 0; i < 5; i++)
                *reinterpret_cast<uint2*>(xs + warp * XPITCH + i * 128 + lane * 4) =
                    make_uint2(pack_bf16(v[4 * i], v[4 * i + 1]), pack_bf16(v[4 * i + 2], v[4 * i + 3]));
        }
        TS(27);
        aux_sync();
        mbar_wait(sb + BAR_WQ, 0);
        TS(1);
        const uint32_t xfrag = sb + SM_X + ((g & 3) * XPITCH + 2 * j) * 2;
        float acc[3][4] = {};
#pragma unroll
        for (int s = 0; s < 5; s++) {
            const int ks = warp * 5 + s;
            const uint32_t b0 = lds32(xfrag + ks * 32), b1 = lds32(xfrag + ks * 32 + 16);
            const int row = ks * 16 + frow;
#pragma unroll
            for (int mt = 0; mt < 3; mt++) {
                uint32_t a[4];
                ldsm4t(a, sb + SM_WQ + (row * 6 + 2 * mt + fcol) * 16);
                mma16816(acc[mt], a, b0, b1);
            }
        }
        if (j < 2) {
#pragma unroll
            for (int mt = 0; mt < 3; mt++) {
                *reinterpret_cast<float2*>(red + (warp * 48 + mt * 16 + g) * 4 + 2 * j) = make_float2(acc[mt][0], acc[mt][1]);
                *reinterpret_cast<float2*>(red + (warp * 48 + mt * 16 + 8 + g) * 4 + 2 * j) = make_float2(acc[mt][2], acc[mt][3]);
            }
        }
        aux_sync();
        if (tid < 96) {
            const int b = tid & 3, cp = tid >> 2;
            float s0 = 0.f, s1 = 0.f;
#pragma unroll
            for (int w = 0; w < 8; w++) { s0 += red[(w * 48 + 2 * cp) * 4 + b]; s1 += red[(w * 48 + 2 * cp + 1) * 4 + b]; }
            const int h = cta >> 2, d = (cta & 3) * 48 + 2 * cp;
            const int ch = d >> 3, jj = (d & 7) >> 1;
            st_relaxed(&g_early[b * NH + h].q[(ch >> 2) * 16 + jj * 4 + (ch & 3)], pack_neg(s0, s1));
        }
        TS(28);
    }
    if (tid < 160) *reinterpret_cast<uint2*>(smem + SM_X + 4 * HPITCH + tid * 8) = make_uint2(0x3f803f80u, 0x3f803f80u);
    fin_sync<3>();
    const int side = lds32(sb + SM_SIDE);
    mbar_wait(sb + BAR_W, 0);
    TS(7);
    uint32_t part = sb + SM_RED + (warp * 32 + 8 * j + g) * 4;

#pragma unroll 1
    for (int b = 0; b < NB; b++) {
        if (b == NB - 1 && (is_f || is_g)) asm volatile("bar.arrive 9, 288;" ::: "memory");
        if (is_l) {
            uint32_t a[6][2][4];
#pragma unroll
            for (int s = 0; s < 6; s++) {
                const int row = (warp * 6 + s) * 16 + frow;
#pragma unroll
                for (int mt = 0; mt < 2; mt++) ldsm4t(a[s][mt], sb + SM_A + (row * 4 + ((2 * mt + fcol) ^ ((row >> 1) & 3))) * 16);
            }
            const int bh = b * NH + 28 + (warp >> 1);
            const float4* osrc = oacc_at(p, side, bh, (warp & 1) * 32 + lane);
            const float2* lsrc = lsum_at(p, side, bh);
            if (lane == 0) wait_row_o(p, side, bh, 1);
            __syncwarp();
            float2 lv;
#pragma unroll 1
            for (int it = 0; it < SPIN_MAX; it++) {
                lv = ld_relaxed_f2(lsrc);
                if (__all_sync(0xffffffffu, lv.y == UPB)) break;
            }
            if (warp == 7) TSW(25);
            if (cta == NE_CTAS && lane < 28)
                reinterpret_cast<uint4*>(&g_early[bh])[(warp & 1) * 28 + lane] = make_uint4(0u, 0u, 0u, 0u);
            float rl = rcp_approx(lv.x);
            float4 ov;
            pin(osrc); pin(rl); hold(part);
#pragma unroll 1
            for (int it = 0;; it++) {
                ov = ld_relaxed_f4(osrc);
                if (__all_sync(0xffffffffu, ov.w == UPB || it == SPIN_MAX)) break;
            }
            CK(0, __float_as_uint(ov.x));
            const float px = __shfl_xor_sync(0xffffffffu, ov.x, 4), py = __shfl_xor_sync(0xffffffffu, ov.y, 4),
                        pz = __shfl_xor_sync(0xffffffffu, ov.z, 4);
            const uint32_t w[3] = {pack_bf16(ov.x * rl, px * rl), pack_bf16(ov.y * rl, py * rl), pack_bf16(ov.z * rl, pz * rl)};
            float acc[2][2][4] = {};
#pragma unroll
            for (int s = 0; s < 6; s++) {
                const uint32_t b0 = __shfl_sync(0xffffffffu, w[s % 3], (s / 3) * 16 + j);
                const uint32_t b1 = __shfl_sync(0xffffffffu, w[s % 3], (s / 3) * 16 + 8 + j);
#pragma unroll
                for (int mt = 0; mt < 2; mt++) mma16816(acc[mt][s & 1], a[s][mt], b0, b1);
            }
            sts32f(part, sel4(j, acc[0][0][0] + acc[0][1][0], acc[0][0][2] + acc[0][1][2], acc[1][0][0] + acc[1][1][0], acc[1][0][2] + acc[1][1][2]));
            CK(1, 0);
            fin_arrive<4>();
            if (warp == 7) TSW(30);
            if (warp == 5) TSW(31);
            fin_sync<5>();
            continue;
        }
        {
            const int bh = b * NH + (cta >> 2);
            if (tid == 0) wait_row_o(p, side, bh, UPB);
            aux_sync();
            if (warp < 5) {
                uint32_t ob[12][2];
                load_o<4>(p, ob, bh, 0, j);
                float acc[2][2][4] = {};
#pragma unroll
                for (int ks = 0; ks < 12; ks++) {
                    const int row = ks * 16 + frow;
#pragma unroll
                    for (int mt = 0; mt < 2; mt++) {
                        uint32_t a[4];
                        ldsm4t(a, sb + SM_A + warp * 12288 + (row * 4 + ((2 * mt + fcol) ^ ((row >> 1) & 3))) * 16);
                        mma16816(acc[mt][ks & 1], a, ob[ks][0], ob[ks][1]);
                    }
                }
                red_f2(&g_st.attn[b][(cta & 3) * 160 + warp * 32 + 8 * j + g].x,
                       sel4(j, acc[0][0][0] + acc[0][1][0], acc[0][0][2] + acc[0][1][2], acc[1][0][0] + acc[1][1][0], acc[1][0][2] + acc[1][1][2]), 1.f);
                TS(8);
            } else if (warp > 5 && (cta & 3) == 0 && tid - 192 < 56) {
                reinterpret_cast<uint4*>(&g_early[bh])[tid - 192] = make_uint4(0u, 0u, 0u, 0u);
            }
        }
        if (is_f) {
            const int kq = warp >> 1, tp = warp & 1;
            uint32_t hfrag = sb + SM_X + min(g, 4) * HPITCH + (kq * 80 + 4 * j) * 4;
            uint32_t fpart = sb + SM_RED + 2 * j * FPITCH + warp * 128 + g * 16;
            uint32_t dsum = sb + SM_RED + (lane >> 3) * FPITCH + tp * 128 + (lane & 7) * 16, csum = sb + SM_RED + 4 * FPITCH + tp * 128 + (lane & 7) * 16;
            uint32_t mom = sb + SM_MOM + (lane >> 3) * 8;
            uint32_t* dst = sided<uint32_t>(p, side ^ 1, X_A + (2 * fidx + tp) * 128 + (lane ^ 2 * tp) * 4);
            uint32_t* dst2 = other_side(dst);
            hold(fpart); hold(hfrag); hold(dsum); hold(csum); hold(mom); hold(dst); hold(dst2);
            uint4 hv[5] = {};
#pragma unroll
            for (int s = 0; s < 5; s++) lds128_if(hv[s], hfrag + s * 64, true);
            if (b == NB - 1) asm volatile("bar.sync 10, %0;" :: "n"((NAUX + NWORK) * 32) : "memory");
            uint32_t ga[10][2][4];
#pragma unroll
            for (int s = 0; s < 10; s++) {
                if (s % 5 == 0 && b == NB - 1) mbar_wait(sb + BAR_G + (kq * 2 + s / 5) * 8, 0);
                const int row = (kq * 10 + s) * 16 + frow;
#pragma unroll
                for (int t = 0; t < 2; t++) ldsm4t(ga[s][t], sb + SM_G + fcol * 40960 + (row * 4 + ((2 * tp + t) ^ ((row >> 1) & 3))) * 16);
            }
            if (warp == NAUX - 1) TSW(9);
            uint32_t dep = 0;
#pragma unroll
            for (int s = 0; s < 5; s++) dep ^= ga[s][0][0] ^ ga[s][1][0];
            fin_sync<7>(288 + (dep & (side >> 1)));
#pragma unroll
            for (int s = 0; s < 5; s++) lds128_if(hv[s], hfrag + s * 64, g == b);
            float acc[2][2][4] = {};
#pragma unroll
            for (int s = 0; s < 5; s++) {
#pragma unroll
                for (int t = 0; t < 2; t++) mma16816(acc[t][0], ga[2 * s][t], hv[s].x, hv[s].y);
#pragma unroll
                for (int t = 0; t < 2; t++) mma16816(acc[t][1], ga[2 * s + 1][t], hv[s].z, hv[s].w);
            }
#pragma unroll
            for (int e = 0; e < 2; e++)
                sts128f(fpart + e * FPITCH, acc[0][0][e] + acc[0][1][e], acc[0][0][2 + e] + acc[0][1][2 + e],
                        acc[1][0][e] + acc[1][1][e], acc[1][0][2 + e] + acc[1][1][2 + e], 2 * j + e < 5);
            CK(5, 0);
            if (warp < 2) {
                fin_sync<4>();
                CK(6, lds32(dsum));
                float2 m = lds64f(mom);
                m.y = rcp_approx(m.y);
                const float4 d = sum4x4(dsum), cs = sum4x4(csum);
                const float g0 = bf16r(fmaf(m.x, cs.x, -d.x) * m.y), g1 = bf16r(fmaf(m.x, cs.z, -d.z) * m.y);
                const float u0 = bf16r(fmaf(m.x, cs.y, -d.y) * m.y), u1 = bf16r(fmaf(m.x, cs.w, -d.w) * m.y);
                const uint32_t av = pack_neg(bf16r(g0 * sigmoid_approx(g0)) * u0, bf16r(g1 * sigmoid_approx(g1)) * u1);
                asm volatile("{\n.reg .pred p;\nsetp.eq.u32 p, %3, 3;\n@p st.relaxed.gpu.global.u32 [%0], %2;\n@p st.relaxed.gpu.global.u32 [%1], %2;\n}"
                             :: "l"(dst), "l"(dst2), "r"(av), "r"(b) : "memory");
                CK(7, 0);
                TS(14);
            } else {
                fin_arrive<4>();
            }
        } else if (is_g) {
            if (b == NB - 1) {
                mbar_wait(sb + BAR_G + warp * 8, 0);
                if (warp == NAUX - 1) TSW(10);
            }
            uint32_t wb[3][2][2][4];
#pragma unroll
            for (int s = 0; s < 12; s++) {
                const int odd = (lane >> 2) & 1, c = ((lane & 2) * 2 + (s & 1) * 2 + (lane >> 4)) ^ (2 * odd);
                const int row = (warp * 12 + (s >> 1) * 2 + odd) * 16 + (lane & 1) * 8 + c;
                ldsm4t(wb[s >> 2][(s >> 1) & 1][s & 1], sb + SM_G + (row * 2 + (fcol ^ ((row >> 2) & 1))) * 16);
            }
            const uint4* asrc[3];
#pragma unroll
            for (int q = 0; q < 3; q++) {
                asrc[q] = sided<uint4>(p, side, X_A + (warp * 12 + 4 * q + 2 * (g >> 2) + (j >> 1)) * 128 + (g & 3) * 32 + (j & 1) * 16);
                pin(asrc[q]);
            }
            uint32_t ypart = sb + SM_RED2 + (warp * 2 + (j >> 1)) * YPITCH + (j & 1) * 160 + g * 16;
            pin(ypart);
            fin_sync<7>();
            uint4 v[3] = {};
            uint32_t mq[3] = {};
#pragma unroll 1
            for (int it = b < NB - 1 ? SPIN_MAX : 0;; it++) {
                asm volatile("{\n.reg .pred p0, p1, p2;\nsetp.eq.u32 p0, %15, 0;\nsetp.eq.u32 p1, %16, 0;\nsetp.eq.u32 p2, %17, 0;\n"
                             "@p0 ld.relaxed.gpu.global.v4.u32 {%0,%1,%2,%3}, [%12];\n"
                             "@p1 ld.relaxed.gpu.global.v4.u32 {%4,%5,%6,%7}, [%13];\n"
                             "@p2 ld.relaxed.gpu.global.v4.u32 {%8,%9,%10,%11}, [%14];\n}"
                             : "+r"(v[0].x), "+r"(v[0].y), "+r"(v[0].z), "+r"(v[0].w), "+r"(v[1].x), "+r"(v[1].y), "+r"(v[1].z), "+r"(v[1].w),
                               "+r"(v[2].x), "+r"(v[2].y), "+r"(v[2].z), "+r"(v[2].w)
                             : "l"(asrc[0]), "l"(asrc[1]), "l"(asrc[2]), "r"(mq[0]), "r"(mq[1]), "r"(mq[2]) : "memory");
#pragma unroll
                for (int q = 0; q < 3; q++) mq[q] = min(min(v[q].x, v[q].y), min(v[q].z, v[q].w));
                const uint32_t lo = min(min(mq[0], mq[1]), mq[2]);
                if (__all_sync(0xffffffffu, lo != 0 || it == SPIN_MAX)) break;
            }
            CK(8, v[0].x);
            float acc[2][2][4] = {};
#pragma unroll
            for (int q = 0; q < 3; q++) {
#pragma unroll
                for (int pr = 0; pr < 2; pr++) {
                    mma16816(acc[pr][0], wb[q][pr][0], v[q].x, v[q].y);
                    mma16816(acc[pr][1], wb[q][pr][1], v[q].z, v[q].w);
                }
            }
            float y[4];
#pragma unroll
            for (int e = 0; e < 4; e++) y[e] = j < 2 ? acc[0][0][e] + acc[0][1][e] : acc[1][0][e] + acc[1][1][e];
            asm volatile("st.shared.v4.f32 [%0], {%1,%2,%3,%4};" :: "r"(ypart), "f"(y[0]), "f"(y[2]), "f"(y[1]), "f"(y[3]) : "memory");
            CK(9, 0);
            fin_arrive<6>();
        } else {
            continue;
        }
        if (b < NB - 1) fin_sync<5>();
    }
}

typedef CUresult (*EncodeFn)(CUtensorMap*, CUtensorMapDataType, cuuint32_t, void*, const cuuint64_t*, const cuuint64_t*,
                             const cuuint32_t*, const cuuint32_t*, CUtensorMapInterleave, CUtensorMapSwizzle,
                             CUtensorMapL2promotion, CUtensorMapFloatOOBfill);

CUtensorMap make_map(EncodeFn enc, void* ptr, uint64_t cols, uint64_t rows, uint32_t bcols, uint32_t brows,
                     CUtensorMapSwizzle sw, CUtensorMapL2promotion promo) {
    CUtensorMap m;
    const cuuint64_t dims[2] = {cols, rows};
    const cuuint64_t strides[1] = {cols * 2};
    const cuuint32_t box[2] = {bcols, brows};
    const cuuint32_t es[2] = {1, 1};
    enc(&m, CU_TENSOR_MAP_DATA_TYPE_BFLOAT16, 2, ptr, dims, strides, box, es, CU_TENSOR_MAP_INTERLEAVE_NONE, sw, promo,
        CU_TENSOR_MAP_FLOAT_OOB_FILL_NONE);
    return m;
}

}

extern "C" void kernel_launch(void* const* d_in, const int* in_sizes, int n_in, void* d_out, int out_size) {
    (void)in_sizes; (void)n_in; (void)out_size;
    static EncodeFn enc = nullptr;
    static int sms = 0;
    static void* raw = nullptr;
    if (!enc) {
        cudaDriverEntryPointQueryResult qr;
        cudaGetDriverEntryPoint("cuTensorMapEncodeTiled", (void**)&enc, cudaEnableDefault, &qr);
        int dev = 0;
        cudaGetDevice(&dev);
        cudaDeviceGetAttribute(&sms, cudaDevAttrMultiProcessorCount, dev);
        cudaGetSymbolAddress(&raw, g_raw);
        cudaFuncSetAttribute(fused_decode_kernel, cudaFuncAttributeMaxDynamicSharedMemorySize, SM_TOTAL);
    }
    if (sms < NCTAS) return;
    const CUtensorMapL2promotion WPROMO = CU_TENSOR_MAP_L2_PROMOTION_L2_128B;
    Params p;
    p.k = make_map(enc, d_in[1], 64, (uint64_t)NBH * SK * 3, 64, TILE_ROWS, CU_TENSOR_MAP_SWIZZLE_128B, CU_TENSOR_MAP_L2_PROMOTION_NONE);
    p.v = make_map(enc, d_in[2], 64, (uint64_t)NBH * SK * 3, 64, TILE_ROWS, CU_TENSOR_MAP_SWIZZLE_128B, CU_TENSOR_MAP_L2_PROMOTION_NONE);
    p.wq = make_map(enc, d_in[3], NH * DH, DM, 48, 160, CU_TENSOR_MAP_SWIZZLE_NONE, WPROMO);
    p.wo = make_map(enc, d_in[4], DM, NH * DH, 32, 48, CU_TENSOR_MAP_SWIZZLE_64B, WPROMO);
    p.wg = make_map(enc, d_in[7], FF, DM, 32, 80, CU_TENSOR_MAP_SWIZZLE_64B, WPROMO);
    p.wu = make_map(enc, d_in[8], FF, DM, 32, 80, CU_TENSOR_MAP_SWIZZLE_64B, WPROMO);
    p.wd = make_map(enc, d_in[9], DM, FF, 16, 192, CU_TENSOR_MAP_SWIZZLE_32B, WPROMO);
    p.scratch = reinterpret_cast<Scratch*>((reinterpret_cast<uintptr_t>(raw) + PAGE - 1) & ~(uintptr_t)(PAGE - 1));
    p.wq_raw = (const char*)d_in[3];
    p.x = (const __nv_bfloat16*)d_in[0];
    p.wr = (const __nv_bfloat16*)d_in[6];
    p.out = (__nv_bfloat16*)d_out;
    fused_decode_kernel<<<NCTAS, NTHREADS, SM_TOTAL, cudaStreamPerThread>>>(p);
}
```

```cpp
#include <cuda_runtime.h>
#include <cuda_bf16.h>
#include <cuda.h>
#include <stdint.h>

namespace {

constexpr int NB = 4, NH = 32, SK = 8192, DH = 192, DM = 640, FF = 1536;
constexpr int NBH = NB * NH;
constexpr int TILE = 64;
constexpr int UPB = SK / TILE;
constexpr int NUNITS = NBH * UPB;
constexpr int TILE_BYTES = TILE * DH * 2;
constexpr int TILE_ROWS = TILE * 3;
constexpr int NCTAS = 132;
constexpr int NQ_CTAS = 128;
constexpr int NE_CTAS = 112;

constexpr int SROW0 = NBH - 4;

#define PRES 48
#define NWORK 2
#define NWL 2
#define SKEW 16
#define LAG 3
#define NPOOL 896
#define RED0 120
#define RING 12
#define K0_DELAY_NS 1600
#define K0_STEP_NS 900
#define WO_AT_NS 3600
#define WO_GAP_NS 550
#define VTRIG (NPOOL - 240)
#define TRIG_NS 2200
#define GCLK 250
#define DOFF 2100
#define DCLK 150
constexpr int NAUX = 8;
constexpr int NTHREADS = (NAUX + NWORK + 2) * 32;
constexpr int SPIN_MAX = 1 << 22;

constexpr int SM_KV = 0;
constexpr int SM_A = SM_KV + NWORK * TILE_BYTES;
constexpr int SM_WQ = SM_A + 61440;
constexpr int SM_G = SM_WQ;
constexpr int SM_X = SM_G + 81920;
constexpr int XPITCH = 648;
constexpr int HPITCH = 1344;
constexpr int SM_RED = SM_X + 5 * HPITCH;
constexpr int FPITCH = 1040;
constexpr int SM_RED2 = SM_RED;
constexpr int YPITCH = 320;
constexpr int SM_MISC = SM_RED + 6144;
constexpr int BAR_KV = SM_MISC, BAR_WQ = SM_MISC + 32, BAR_W = SM_MISC + 40, SM_SIDE = SM_MISC + 48, BAR_G = SM_MISC + 64, SM_MOM = SM_MISC + 128;
constexpr int SM_TOTAL = SM_MISC + 160;

struct Scratch;
struct Params {
    CUtensorMap k, v;
    CUtensorMap wq;
    CUtensorMap wo;
    CUtensorMap wg, wu;
    CUtensorMap wd;
    Scratch* scratch;
    const char* wq_raw;
    const __nv_bfloat16 *x, *wr;
    __nv_bfloat16* out;
};

struct Early {
    uint32_t q[96];
    uint32_t umax[UPB];
};
struct State {
    float4 oacc[SROW0][64];
    float2 attn[NB][DM];
    float2 lsum[SROW0][16];
    unsigned pool[64];
    uint32_t tstart[32];
    uint32_t score[NPOOL][32];
};
constexpr int STATE_V4 = ((sizeof(State) / 32 + NQ_CTAS - 1) / NQ_CTAS) * 2;
static_assert(sizeof(State) % 32 == 0, "State is cleared in whole sectors");
static_assert(sizeof(Early) == 56 * 16, "an Early entry is cleared by 56 threads");
constexpr uint32_t X_O = 0;
constexpr uint32_t X_L = X_O + 4 * 1024;
constexpr uint32_t X_H = X_L + 4 * 128;
constexpr uint32_t X_A = X_H + NB * DM * 2;
constexpr uint32_t X_P = X_A + NB * FF * 2;
constexpr uint32_t X_END = X_P + 4096;
static_assert(X_END <= 8 * 4096 && RED0 <= SROW0, "");
struct Scratch {
    unsigned char sided[8][2][4096];
    unsigned work[64];
    unsigned cnt_z[32];
    unsigned char pad0[1024];
    Early early[NBH];
    unsigned char pad1[1024];
    State st;
    unsigned char pad2[1792];
    float4 ring[RING][UPB][64];
};
constexpr size_t PAGE = 2u << 20;
static_assert(sizeof(Scratch) <= PAGE, "scratch must fit one page");
__device__ __align__(128) unsigned char g_raw[2 * PAGE];
template <typename T> __device__ __forceinline__ T* sided(const Params& p, int side, uint32_t x) {
    const uint32_t pair = (x >> 10) & 7;
    return reinterpret_cast<T*>(&p.scratch->sided[pair][(side ^ pair) & 1]
                                    [(x & 127) + ((x & 128) << 1) + ((x & 768) << 2) + ((x >> 6) & 128) + ((x >> 5) & 512)]);
}
template <typename T> __device__ __forceinline__ T* other_side(T* p) { return reinterpret_cast<T*>(reinterpret_cast<uintptr_t>(p) ^ 4096); }
#define g_early p.scratch->early
#define g_st p.scratch->st
#define g_ring p.scratch->ring
#define g_cnt_z p.scratch->cnt_z
#define g_work p.scratch->work
#define TS(i)
#define TSW(i)
#define TS2(i)
#define TSI(n, i)
#define PH(i)
#define CK(i, dep)
#define ARR()
#define PROG(u)
#define LT(i)

__device__ __forceinline__ int row_of(int u) { return (((unsigned)u >> (7 + NWL)) << NWL) | (u & ((1 << NWL) - 1)); }
__device__ __forceinline__ int pos_of(int u) { return ((unsigned)u >> NWL) & (UPB - 1); }
__device__ __forceinline__ int tile_of(int u) { return (row_of(u) * UPB + ((pos_of(u) + (u & ((1 << NWL) - 1)) * SKEW) & (UPB - 1))) * TILE_ROWS; }

__device__ __forceinline__ uint32_t s2u(const void* p) { return (uint32_t)__cvta_generic_to_shared(p); }
__device__ __forceinline__ void mbar_init(uint32_t bar, int cnt) {
    asm volatile("mbarrier.init.shared::cta.b64 [%0], %1;" :: "r"(bar), "r"(cnt) : "memory");
}
__device__ __forceinline__ void mbar_expect_tx(uint32_t bar, uint32_t bytes) {
    asm volatile("mbarrier.arrive.expect_tx.shared::cta.b64 _, [%0], %1;" :: "r"(bar), "r"(bytes) : "memory");
}
__device__ __forceinline__ void mbar_wait(uint32_t bar, uint32_t parity) {
    asm volatile("{\n.reg .pred p;\n.reg .u32 n;\nmov.u32 n, 0;\nWAIT_LOOP:\n"
                 "mbarrier.try_wait.parity.shared::cta.b64 p, [%0], %1;\n"
                 "@p bra WAIT_DONE;\nadd.u32 n, n, 1;\nsetp.lt.u32 p, n, %2;\n@p bra WAIT_LOOP;\nWAIT_DONE:\n}"
                 :: "r"(bar), "r"(parity), "n"(SPIN_MAX) : "memory");
}
__device__ __forceinline__ void request_tile(uint32_t dst, const CUtensorMap* tm, int unit, uint32_t bar, uint64_t pol) {
    asm volatile("{\n.reg .pred p;\nelect.sync _|p, 0xffffffff;\n"
                 "@p mbarrier.arrive.expect_tx.shared::cta.b64 _, [%2], %6;\n"
                 "@p cp.async.bulk.tensor.2d.shared::cluster.global.mbarrier::complete_tx::bytes.L2::cache_hint "
                 "[%0], [%1, {%3, %4}], [%2], %5;\n}"
                 :: "r"(dst), "l"(tm), "r"(bar), "r"(0), "r"(tile_of(unit)), "l"(pol), "n"(TILE_BYTES) : "memory");
}
__device__ __forceinline__ uint32_t now_ns() { uint32_t t; asm volatile("mov.u32 %0, %%globaltimer_lo;" : "=r"(t)); return t; }
__device__ __forceinline__ uint32_t now_clk() { uint32_t t; asm volatile("mov.u32 %0, %%clock;" : "=r"(t)); return t; }
__device__ __forceinline__ void wait_clk(uint32_t t) { while (__any_sync(0xffffffffu, (int)(now_clk() - t) < 0)) {} }
__device__ __forceinline__ uint64_t evict_first() {
    uint64_t pol;
    asm volatile("createpolicy.fractional.L2::evict_first.b64 %0, 1.0;" : "=l"(pol));
    return pol;
}
__device__ __forceinline__ void request_box(uint32_t dst, const CUtensorMap* tm, int col, int row, uint32_t bar) {
    asm volatile("{\n.reg .pred p;\nelect.sync _|p, 0xffffffff;\n"
                 "@p cp.async.bulk.tensor.2d.shared::cluster.global.mbarrier::complete_tx::bytes [%0], [%1, {%3, %4}], [%2];\n}"
                 :: "r"(dst), "l"(tm), "r"(bar), "r"(col), "r"(row) : "memory");
}
__device__ __forceinline__ void request_box(uint32_t dst, const CUtensorMap* tm, int col, int row, uint32_t bar, uint64_t pol) {
    asm volatile("{\n.reg .pred p;\nelect.sync _|p, 0xffffffff;\n"
                 "@p cp.async.bulk.tensor.2d.shared::cluster.global.mbarrier::complete_tx::bytes.L2::cache_hint [%0], [%1, {%3, %4}], [%2], %5;\n}"
                 :: "r"(dst), "l"(tm), "r"(bar), "r"(col), "r"(row), "l"(pol) : "memory");
}
__device__ __forceinline__ uint32_t lds32(uint32_t addr) {
    uint32_t v;
    asm volatile("ld.shared.u32 %0, [%1];" : "=r"(v) : "r"(addr) : "memory");
    return v;
}
__device__ __forceinline__ void ldsm4(uint32_t (&r)[4], uint32_t addr) {
    asm volatile("ldmatrix.sync.aligned.m8n8.x4.shared.b16 {%0,%1,%2,%3}, [%4];"
                 : "=r"(r[0]), "=r"(r[1]), "=r"(r[2]), "=r"(r[3]) : "r"(addr) : "memory");
}
__device__ __forceinline__ void ldsm4t(uint32_t (&r)[4], uint32_t addr) {
    asm volatile("ldmatrix.sync.aligned.m8n8.x4.trans.shared.b16 {%0,%1,%2,%3}, [%4];"
                 : "=r"(r[0]), "=r"(r[1]), "=r"(r[2]), "=r"(r[3]) : "r"(addr) : "memory");
}
__device__ __forceinline__ void mma16816(float (&c)[4], const uint32_t (&a)[4], uint32_t b0, uint32_t b1) {
    asm volatile("mma.sync.aligned.m16n8k16.row.col.f32.bf16.bf16.f32 {%0,%1,%2,%3}, {%4,%5,%6,%7}, {%8,%9}, {%0,%1,%2,%3};"
                 : "+f"(c[0]), "+f"(c[1]), "+f"(c[2]), "+f"(c[3])
                 : "r"(a[0]), "r"(a[1]), "r"(a[2]), "r"(a[3]), "r"(b0), "r"(b1));
}
__device__ __forceinline__ uint4 ld_relaxed_v4(const void* p) {
    uint4 v;
    asm volatile("ld.relaxed.gpu.global.v4.u32 {%0,%1,%2,%3}, [%4];" : "=r"(v.x), "=r"(v.y), "=r"(v.z), "=r"(v.w) : "l"(p) : "memory");
    return v;
}
__device__ __forceinline__ float4 ld_relaxed_f4(const void* p) {
    float4 v;
    asm volatile("ld.relaxed.gpu.global.v4.f32 {%0,%1,%2,%3}, [%4];" : "=f"(v.x), "=f"(v.y), "=f"(v.z), "=f"(v.w) : "l"(p) : "memory");
    return v;
}
__device__ __forceinline__ float2 ld_relaxed_f2(const void* p) {
    float2 v;
    asm volatile("ld.relaxed.gpu.global.v2.f32 {%0,%1}, [%2];" : "=f"(v.x), "=f"(v.y) : "l"(p) : "memory");
    return v;
}
__device__ __forceinline__ float4 ld_relaxed_b128(const void* p) {
    float4 v;
    asm volatile("{\n.reg .b128 t;\n.reg .b64 a, b;\nld.relaxed.gpu.global.b128 t, [%4];\nmov.b128 {a, b}, t;\n"
                 "mov.b64 {%0, %1}, a;\nmov.b64 {%2, %3}, b;\n}" : "=f"(v.x), "=f"(v.y), "=f"(v.z), "=f"(v.w) : "l"(p) : "memory");
    return v;
}
__device__ __forceinline__ void st_relaxed_b128(void* p, float x, float y, float z, float w) {
    asm volatile("{\n.reg .b128 t;\n.reg .b64 a, b;\nmov.b64 a, {%1, %2};\nmov.b64 b, {%3, %4};\nmov.b128 t, {a, b};\n"
                 "st.relaxed.gpu.global.b128 [%0], t;\n}" :: "l"(p), "f"(x), "f"(y), "f"(z), "f"(w) : "memory");
}
__device__ __forceinline__ unsigned ld_acquire(const unsigned* p) {
    unsigned v;
    asm volatile("ld.acquire.gpu.global.u32 %0, [%1];" : "=r"(v) : "l"(p) : "memory");
    return v;
}
__device__ __forceinline__ void st_relaxed(void* p, uint32_t v) {
    asm volatile("st.relaxed.gpu.global.u32 [%0], %1;" :: "l"(p), "r"(v) : "memory");
}
__device__ __forceinline__ void red_f2(float* p, float a, float b) {
    asm volatile("red.relaxed.gpu.global.add.v2.f32 [%0], {%1,%2};" :: "l"(p), "f"(a), "f"(b) : "memory");
}
__device__ __forceinline__ void red_f4(float* p, float a, float b, float c, float d) {
    asm volatile("red.relaxed.gpu.global.add.v4.f32 [%0], {%1,%2,%3,%4};" :: "l"(p), "f"(a), "f"(b), "f"(c), "f"(d) : "memory");
}
__device__ __forceinline__ void draw(int& ticket, unsigned* ctr, bool pred) {
    asm volatile("{\n.reg .pred p;\nsetp.ne.u32 p, %2, 0;\n@p atom.relaxed.gpu.global.inc.u32 %0, [%1], 0x7fffffff;\n}"
                 : "+r"(ticket) : "l"(ctr), "r"((uint32_t)pred) : "memory");
}
__device__ __forceinline__ void red_release(unsigned* p) {
    asm volatile("red.release.gpu.global.add.u32 [%0], 1;" :: "l"(p) : "memory");
}
__device__ __forceinline__ uint32_t ld_relaxed_u32(const void* p) {
    uint32_t v;
    asm volatile("ld.relaxed.gpu.global.u32 %0, [%1];" : "=r"(v) : "l"(p) : "memory");
    return v;
}
__device__ __forceinline__ float rcp_approx(float v) {
    float r;
    asm("rcp.approx.ftz.f32 %0, %1;" : "=f"(r) : "f"(v));
    return r;
}
__device__ __forceinline__ float sigmoid_approx(float v) {
    float e;
    asm("ex2.approx.ftz.f32 %0, %1;" : "=f"(e) : "f"(v * -1.4426950408889634f));
    return rcp_approx(1.0f + e);
}
__device__ __forceinline__ float sqrt_approx(float v) {
    float r;
    asm("sqrt.approx.ftz.f32 %0, %1;" : "=f"(r) : "f"(v));
    return r;
}
__device__ __forceinline__ uint2 ld_relaxed_v2(const void* p) {
    uint2 v;
    asm volatile("ld.relaxed.gpu.global.v2.u32 {%0,%1}, [%2];" : "=r"(v.x), "=r"(v.y) : "l"(p) : "memory");
    return v;
}
__device__ __forceinline__ void wait_count(const unsigned* p, unsigned target) {
#pragma unroll 1
    for (int it = 0; it < SPIN_MAX; it++) {
        if (ld_acquire(p) >= target) break;
        __nanosleep(400);
    }
}
__device__ __forceinline__ float4* oacc_at(const Params& p, int side, int row, int grp) {
    return row >= SROW0 ? sided<float4>(p, side, X_O + (row - SROW0) * 1024 + grp * 16) : &g_st.oacc[row][grp];
}
__device__ __forceinline__ float2* lsum_at(const Params& p, int side, int row) {
    return row >= SROW0 ? sided<float2>(p, side, X_L + (row - SROW0) * 128) : g_st.lsum[row];
}
__device__ __forceinline__ void wait_row(const Params& p, int side, int bh, float n) {
    const float2* l = lsum_at(p, side, bh);
#pragma unroll 1
    for (int it = 0; it < SPIN_MAX; it++) {
        const float c = ld_relaxed_f2(l).y;
        if (c >= n) break;
        if (c == 0.f) __nanosleep(600);
    }
}
__device__ __forceinline__ void wait_row_o(const Params& p, int side, int bh, float n) {
    wait_row(p, side, bh, n);
    if (bh >= RED0) return;
#pragma unroll 1
    for (int it = 0; it < SPIN_MAX; it++) {
        if (__uint_as_float(ld_relaxed_u32(&g_st.oacc[bh][0].w)) == UPB) break;
        __nanosleep(300);
    }
}
__device__ __forceinline__ uint32_t pack_bf16(float lo, float hi) {
    uint32_t r;
    asm("cvt.rn.bf16x2.f32 %0, %1, %2;" : "=r"(r) : "f"(hi), "f"(lo));
    return r;
}
__device__ __forceinline__ float bf16r(float v) { return __uint_as_float(pack_bf16(0.f, v)); }
__device__ __forceinline__ uint32_t pack_neg(float lo, float hi) {
    const uint32_t w = pack_bf16(-lo, -hi);
    return w ? w : 0x80008000u;
}
__device__ __forceinline__ float lo_f(uint32_t v) { return __uint_as_float(v << 16); }
__device__ __forceinline__ float hi_f(uint32_t v) { return __uint_as_float(v & 0xffff0000u); }
__device__ __forceinline__ float warp_sum(float v) {
#pragma unroll
    for (int o = 16; o; o >>= 1) v += __shfl_xor_sync(0xffffffffu, v, o);
    return v;
}
__device__ __forceinline__ void layernorm20(float (&v)[20]) {
    float s = 0.f;
#pragma unroll
    for (int i = 0; i < 20; i++) s += v[i];
    const float mean = warp_sum(s) * (1.0f / DM);
    float q = 0.f;
#pragma unroll
    for (int i = 0; i < 20; i++) { const float d = v[i] - mean; q += d * d; }
    const float var = bf16r(warp_sum(q) * (1.0f / DM));
    const float m = bf16r(mean);
    const float rden = 1.0f / bf16r(sqrtf(bf16r(var + 1e-5f)));
#pragma unroll
    for (int i = 0; i < 20; i++) v[i] = bf16r(bf16r(v[i] - m) * rden);
}

__device__ __forceinline__ float sel4(int j, float a, float b, float c, float d) {
    float lo, hi, r;
    asm("{\n.reg .pred p;\nsetp.ne.s32 p, %3, 0;\nselp.f32 %0, %2, %1, p;\n}" : "=f"(lo) : "f"(a), "f"(b), "r"(j & 1));
    asm("{\n.reg .pred p;\nsetp.ne.s32 p, %3, 0;\nselp.f32 %0, %2, %1, p;\n}" : "=f"(hi) : "f"(c), "f"(d), "r"(j & 1));
    asm("{\n.reg .pred p;\nsetp.ne.s32 p, %3, 0;\nselp.f32 %0, %2, %1, p;\n}" : "=f"(r) : "f"(lo), "f"(hi), "r"(j & 2));
    return r;
}
template <typename T> __device__ __forceinline__ void pin(T*& p) { asm volatile("" : "+l"(p)); }
__device__ __forceinline__ void pin(uint32_t& v) { asm volatile("" : "+r"(v)); }
__device__ __forceinline__ void pin(float& v) { asm volatile("" : "+f"(v)); }
__device__ __forceinline__ void hold(uint32_t& v) { v = __shfl_xor_sync(0xffffffffu, v, 0); }
template <typename T> __device__ __forceinline__ void hold(T*& p) {
    p = reinterpret_cast<T*>(__shfl_xor_sync(0xffffffffu, (unsigned long long)reinterpret_cast<uintptr_t>(p), 0));
}
__device__ __forceinline__ uint32_t after(uint32_t n, float v) {
    asm volatile("{\n.reg .pred p;\nsetp.eq.u32 p, %1, 0x7fc1a5a5;\n@p add.u32 %0, %0, 32;\n}" : "+r"(n) : "r"(__float_as_uint(v)));
    return n;
}
__device__ __forceinline__ float2 lds64f(uint32_t addr) {
    float2 v;
    asm volatile("ld.shared.v2.f32 {%0,%1}, [%2];" : "=f"(v.x), "=f"(v.y) : "r"(addr) : "memory");
    return v;
}
__device__ __forceinline__ float4 lds128f(uint32_t addr) {
    float4 v;
    asm volatile("ld.shared.v4.f32 {%0,%1,%2,%3}, [%4];" : "=f"(v.x), "=f"(v.y), "=f"(v.z), "=f"(v.w) : "r"(addr) : "memory");
    return v;
}
__device__ __forceinline__ void sts64f(uint32_t addr, float a, float b, bool pred) {
    asm volatile("{\n.reg .pred p;\nsetp.ne.u32 p, %3, 0;\n@p st.shared.v2.f32 [%0], {%1,%2};\n}" :: "r"(addr), "f"(a), "f"(b), "r"((uint32_t)pred) : "memory");
}
__device__ __forceinline__ void sts128f(uint32_t addr, float a, float b, float c, float d, bool pred) {
    asm volatile("{\n.reg .pred p;\nsetp.ne.u32 p, %5, 0;\n@p st.shared.v4.f32 [%0], {%1,%2,%3,%4};\n}"
                 :: "r"(addr), "f"(a), "f"(b), "f"(c), "f"(d), "r"((uint32_t)pred) : "memory");
}
__device__ __forceinline__ void lds128_if(uint4& v, uint32_t addr, bool pred) {
    asm volatile("{\n.reg .pred p;\nsetp.ne.u32 p, %5, 0;\n@p ld.shared.v4.u32 {%0,%1,%2,%3}, [%4];\n}"
                 : "+r"(v.x), "+r"(v.y), "+r"(v.z), "+r"(v.w) : "r"(addr), "r"((uint32_t)pred) : "memory");
}
__device__ __forceinline__ void sts32f(uint32_t addr, float v) { asm volatile("st.shared.f32 [%0], %1;" :: "r"(addr), "f"(v) : "memory"); }
template <int ID> __device__ __forceinline__ void fin_arrive() { asm volatile("bar.arrive %0, 288;" :: "n"(ID) : "memory"); }
template <int ID> __device__ __forceinline__ void fin_sync() { asm volatile("bar.sync %0, 288;" :: "n"(ID) : "memory"); }
template <int ID> __device__ __forceinline__ void fin_sync(uint32_t n) { asm volatile("bar.sync %0, %1;" :: "n"(ID), "r"(n) : "memory"); }
__device__ __forceinline__ float2 sum8(uint32_t addr) {
    float2 t[8];
#pragma unroll
    for (int w = 0; w < 8; w++) t[w] = lds64f(addr + w * 128);
    return make_float2(((t[0].x + t[1].x) + (t[2].x + t[3].x)) + ((t[4].x + t[5].x) + (t[6].x + t[7].x)),
                       ((t[0].y + t[1].y) + (t[2].y + t[3].y)) + ((t[4].y + t[5].y) + (t[6].y + t[7].y)));
}
__device__ __forceinline__ float4 sum4x4(uint32_t addr) {
    float4 t[4];
#pragma unroll
    for (int w = 0; w < 4; w++) t[w] = lds128f(addr + w * 256);
    return make_float4((t[0].x + t[1].x) + (t[2].x + t[3].x), (t[0].y + t[1].y) + (t[2].y + t[3].y),
                       (t[0].z + t[1].z) + (t[2].z + t[3].z), (t[0].w + t[1].w) + (t[2].w + t[3].w));
}
template <int NJ>
__device__ __forceinline__ void load_o(const Params& p, uint32_t (&ob)[3 * NJ][2], int bh, int J0, int j) {
    float4 v[NJ][4];
    float2 l;
#pragma unroll 1
    for (int it = 0; it < SPIN_MAX; it++) {
#pragma unroll
        for (int J = 0; J < NJ; J++) {
#pragma unroll
            for (int e = 0; e < 4; e++) v[J][e] = ld_relaxed_f4(&g_st.oacc[bh][(J0 + J) * 16 + e * 4 + j]);
        }
        l = ld_relaxed_f2(g_st.lsum[bh]);
        bool ok = l.y == UPB;
#pragma unroll
        for (int J = 0; J < NJ; J++) {
#pragma unroll
            for (int e = 0; e < 4; e++) ok &= v[J][e].w == UPB;
        }
        if (__all_sync(0xffffffffu, ok)) break;
    }
    const float rl = __fdividef(1.0f, l.x);
#pragma unroll
    for (int J = 0; J < NJ; J++) {
        ob[3 * J][0] = pack_bf16(v[J][0].x * rl, v[J][1].x * rl);     ob[3 * J][1] = pack_bf16(v[J][2].x * rl, v[J][3].x * rl);
        ob[3 * J + 1][0] = pack_bf16(v[J][0].y * rl, v[J][1].y * rl); ob[3 * J + 1][1] = pack_bf16(v[J][2].y * rl, v[J][3].y * rl);
        ob[3 * J + 2][0] = pack_bf16(v[J][0].z * rl, v[J][1].z * rl); ob[3 * J + 2][1] = pack_bf16(v[J][2].z * rl, v[J][3].z * rl);
    }
}
__device__ __forceinline__ void aux_sync() { asm volatile("bar.sync 1, 256;" ::: "memory"); }

__global__ void __launch_bounds__(NTHREADS, 1)
fused_decode_kernel(const __grid_constant__ Params p) {
    extern __shared__ __align__(1024) unsigned char smem[];
    asm volatile("prefetch.global.L2 [%0];" :: "l"(p.wq_raw + (blockIdx.x * NTHREADS + threadIdx.x) * PRES));
    const uint32_t sb = s2u(smem);
    const int tid = threadIdx.x, warp = __shfl_sync(0xffffffffu, tid >> 5, 0), lane = tid & 31;
    const int cta = blockIdx.x;
    constexpr int grid = NCTAS;
    const int g = lane >> 2, j = lane & 3;
    const bool is_l = cta >= NE_CTAS, is_f = cta < 96 && !(cta & 1), is_g = cta < 80 && (cta & 1);
    const int fidx = cta >> 1;

    TS(0);
    if (warp == 4 && cta < NQ_CTAS) {
        asm volatile("{\n.reg .pred p;\nelect.sync _|p, 0xffffffff;\n"
                     "@p mbarrier.init.shared::cta.b64 [%0], 1;\n"
                     "@p fence.mbarrier_init.release.cluster;\n"
                     "@p mbarrier.arrive.expect_tx.shared::cta.b64 _, [%0], 61440;\n}" :: "r"(sb + BAR_WQ) : "memory");
#pragma unroll
        for (int i = 0; i < 4; i++) request_box(sb + SM_WQ + i * 15360, &p.wq, cta * 48, i * 160, sb + BAR_WQ);
    }
    if (tid == 160) {
#pragma unroll
        for (int w = 0; w < NWORK; w++) mbar_init(sb + BAR_KV + w * 8, 1);
        mbar_init(sb + BAR_W, 1);
#pragma unroll
        for (int w = 0; w < 8; w++) mbar_init(sb + BAR_G + w * 8, 1);
        asm volatile("fence.mbarrier_init.release.cluster;" ::: "memory");
    }
    __syncthreads();
    if (warp == NAUX + NWORK + 1) {
        uint32_t t = now_clk() + 2 * WO_AT_NS;
        const uint64_t pol = evict_first();
        if (lane == 0) mbar_expect_tx(sb + BAR_W, is_l ? 49152 : 61440);
#pragma unroll 1
        for (int r = 0; r < DH; r += 48, t += 2 * WO_GAP_NS) {
            wait_clk(t);
#pragma unroll 1
            for (int i = 0; i < (is_l ? 4 : 5); i++)
                request_box(sb + SM_A + i * 12288 + r * 64, &p.wo, is_l ? (cta - NE_CTAS) * 32 : (cta & 3) * 160 + i * 32,
                            (is_l ? 28 + i : cta >> 2) * DH + r, sb + BAR_W, pol);
        }
        if (!is_f && !is_g) return;
        if (lane < 8) mbar_expect_tx(sb + BAR_G + lane * 8, is_f ? 10240 : 6144);
        asm volatile("bar.sync 9, 288;" ::: "memory");
        asm volatile("fence.proxy.async.shared::cta;" ::: "memory");
#pragma unroll 1
        for (int it = 0; it < SPIN_MAX; it++) {
            t = ld_relaxed_u32(g_st.tstart);
            if (__all_sync(0xffffffffu, t != 0)) break;
            __nanosleep(400);
        }
#pragma unroll 1
        for (int it = 0; it < SPIN_MAX; it++) if (__all_sync(0xffffffffu, t - now_ns() > 2 * TRIG_NS)) break;
        TSW(11);
        t = now_clk() + (is_f ? 0 : DOFF);
#pragma unroll 1
        for (int i = 0; i < 8; i++, t += is_f ? GCLK : DCLK) {
            wait_clk(t);
            if (is_f) {
                request_box(sb + SM_G + i * 5120, &p.wg, fidx * 32, i * 80, sb + BAR_G + i * 8);
                request_box(sb + SM_G + 40960 + i * 5120, &p.wu, fidx * 32, i * 80, sb + BAR_G + i * 8);
            } else {
                request_box(sb + SM_G + i * 6144, &p.wd, fidx * 16, i * 192, sb + BAR_G + i * 8);
            }
        }
        return;
    }
    if (warp == NAUX + NWORK) {
        if (cta < NQ_CTAS) {
            wait_clk(now_clk() + 4000);
#pragma unroll
            for (int i = lane; i < STATE_V4; i += 32)
                if (cta * STATE_V4 + i < (int)(sizeof(State) / 16)) reinterpret_cast<uint4*>(&g_st)[cta * STATE_V4 + i] = make_uint4(0u, 0u, 0u, 0u);
            if (cta * 512 < X_END) {
                uint4* z = sided<uint4>(p, 0, cta * 512 + lane * 16);
                *z = make_uint4(0u, 0u, 0u, 0u);
                *other_side(z) = make_uint4(0u, 0u, 0u, 0u);
            }
            __syncwarp();
            if (lane == 0) red_release(g_cnt_z);
        }
        if (lane == 0) { TS2(2); wait_count(g_cnt_z, NQ_CTAS); TS2(29); }
        __syncwarp();
        asm volatile("bar.arrive 2, %0;" :: "n"((NWORK + 1) * 32) : "memory");
        uint32_t rtt[2] = {0xffffffffu, 0xffffffffu};
        if (lane == 0) {
#pragma unroll 1
            for (int r = 0; r < 12; r++) {
                int v = 0;
                uint32_t t1 = 0;
                unsigned* ctr = sided<unsigned>(p, r & 1, X_P + ((cta * 32 + (r >> 1) * 768) & 4095));
                pin(ctr);
                const uint32_t t0 = now_clk();
                draw(v, ctr, true);
                asm volatile("{\n.reg .pred q;\nsetp.ge.s32 q, %1, 0;\n@q mov.u32 %0, %%clock;\n}" : "+r"(t1) : "r"(v) : "memory");
                if (r & 1) rtt[1] = min(rtt[1], t1 - t0); else rtt[0] = min(rtt[0], t1 - t0);
            }
            sts32f(sb + SM_SIDE, __int_as_float(rtt[1] < rtt[0]));
        }
        const int side = __shfl_sync(0xffffffffu, rtt[1] < rtt[0], 0);
        fin_arrive<3>();
        int job = cta;
        auto sum_rows = [&](int row_end) {
#pragma unroll 1
            for (; job < 8 * min(row_end, RED0); job += NCTAS) {
                const int row = job >> 3, grp = (job & 7) * 8 + (lane & 7);
                if (lane == 0) wait_row(p, side, row, UPB);
                __syncwarp();
                const float4* src = &g_ring[row % RING][lane >> 3][grp];
                float sx = 0.f, sy = 0.f, sz = 0.f;
#pragma unroll 1
                for (int i = 0; i < 2; i++, src += 64 * 64) {
                    float4 v[16];
#pragma unroll 1
                    for (int it = 0; it < SPIN_MAX; it++) {
                        bool ok = true;
#pragma unroll
                        for (int k = 0; k < 16; k++) v[k] = ld_relaxed_b128(src + k * 4 * 64);
#pragma unroll
                        for (int k = 0; k < 16; k++) ok &= v[k].w == (float)(row + 1);
                        if (__all_sync(0xffffffffu, ok)) break;
                    }
#pragma unroll
                    for (int k = 0; k < 16; k++) { sx += v[k].x; sy += v[k].y; sz += v[k].z; }
                }
#pragma unroll
                for (int o = 8; o < 32; o <<= 1) {
                    sx += __shfl_xor_sync(0xffffffffu, sx, o); sy += __shfl_xor_sync(0xffffffffu, sy, o); sz += __shfl_xor_sync(0xffffffffu, sz, o);
                }
                if (lane < 8) st_relaxed_b128(&g_st.oacc[row][grp], sx, sy, sz, UPB);
            }
        };
        {
            uint32_t wr[10];
            float wsum = 0.f;
#pragma unroll
            for (int i = 0; i < 10; i++) {
                const int w = 4 * lane + 128 * (i >> 2) + (i & 3) - (i >= 8 ? 2 * lane : 0);
                wr[i] = *reinterpret_cast<const uint32_t*>(p.wr + (w >> 4) * 32 + (w & 3) * 8 + ((w >> 1) & 6));
                wsum += lo_f(wr[i]) + hi_f(wr[i]);
            }
            wsum = warp_sum(wsum);
            const int lb = lane >> 3, lc = lane & 7;
            uint32_t ypart = sb + SM_RED2 + (lb >> 1) * 160 + lc * 16 + (lb & 1) * 8;
            __nv_bfloat16* out = p.out + lb * DM + fidx * 16 + lc;
            float nmean_l = 0.f, rden_l = 0.f, sig_l = 0.f;
#pragma unroll 1
            for (int b = 0; b < NB; b++) {
                const uint32_t hx = X_H + b * (DM * 2), hrow = sb + SM_X + b * HPITCH;
                const uint4 *src0 = sided<uint4>(p, side, hx + 16 * lane), *src1 = sided<uint4>(p, side, hx + 512 + 16 * lane);
                const uint2* src2 = sided<uint2>(p, side, hx + 1024 + 8 * lane);
                sum_rows((b + 1) * NH);
                if (!is_l && !is_f && !is_g) continue;
                pin(src0); pin(src1); pin(src2); pin(ypart); pin(out);
                if (lane == 0) wait_row(p, side, b * NH + (is_l ? 28 : NH - 1), is_l ? 1 : 100);
                __syncwarp();
                if (is_l) {
                    const int col = (cta - NE_CTAS) * 32 + 2 * (lane & 15);
                    uint32_t lpart = sb + SM_RED + (lane & 15) * 8;
                    const uint32_t xv = *reinterpret_cast<const uint32_t*>(p.x + b * DM + col);
                    uint32_t* hdst = sided<uint32_t>(p, lane >> 4, hx + 4 * ((col >> 5) * 16 + (col & 6) * 2 + ((col >> 3) & 3)));
                    float4 early;
#pragma unroll 1
                    for (int it = 0; it < SPIN_MAX; it++) {
                        early = ld_relaxed_f4(&g_st.attn[b][col]);
                        if (__all_sync(0xffffffffu, early.y == NE_CTAS / 4 && early.w == NE_CTAS / 4)) break;
                    }
                    if (lane == 0) TS2(23);
                    float x0 = lo_f(xv), x1 = hi_f(xv);
                    pin(hdst); pin(lpart); pin(x0); pin(x1);
                    fin_sync<4>();
                    CK(2, lds32(sb + SM_RED));
                    const float2 late = sum8(lpart);
                    const uint32_t nh = pack_bf16(-x0 - bf16r(early.x + late.x), -x1 - bf16r(early.z + late.y));
                    st_relaxed(hdst, nh ? nh : 0x80008000u);
                    CK(3, 0);
                    if (lane == 0) TS2(15);
                    fin_sync<5>();
                    continue;
                }
                uint4 h0, h1;
                uint2 h2;
                float mm[5][4];
#pragma unroll 1
                for (int it = 0;; it++) {
                    h0 = ld_relaxed_v4(src0);
                    h1 = ld_relaxed_v4(src1);
                    h2 = ld_relaxed_v2(src2);
                    asm volatile("st.shared.v4.u32 [%0], {%1,%2,%3,%4};" :: "r"(hrow + lane * 16), "r"(h0.x), "r"(h0.y), "r"(h0.z), "r"(h0.w) : "memory");
                    asm volatile("st.shared.v4.u32 [%0], {%1,%2,%3,%4};" :: "r"(hrow + 512 + lane * 16), "r"(h1.x), "r"(h1.y), "r"(h1.z), "r"(h1.w) : "memory");
                    asm volatile("st.shared.v2.u32 [%0], {%1,%2};" :: "r"(hrow + 1024 + lane * 8), "r"(h2.x), "r"(h2.y) : "memory");
                    const uint32_t w[10] = {h0.x, h0.y, h0.z, h0.w, h1.x, h1.y, h1.z, h1.w, h2.x, h2.y};
#pragma unroll
                    for (int i = 0; i < 5; i++) {
                        const uint32_t a[4] = {w[2 * i], 0x3f803f80u, w[2 * i + 1], 0x3f803f80u};
                        mm[i][0] = mm[i][1] = mm[i][2] = mm[i][3] = 0.f;
                        mma16816(mm[i], a, w[2 * i], w[2 * i + 1]);
                    }
                    const uint32_t lo = min(min(min(h0.x, h0.y), min(h0.z, h0.w)), min(min(min(h1.x, h1.y), min(h1.z, h1.w)), min(h2.x, h2.y)));
                    const bool ok = __all_sync(0xffffffffu, lo != 0 || it == SPIN_MAX);
                    asm volatile("{\n.reg .pred p;\nsetp.ne.u32 p, %0, 0;\n@p bar.arrive 7, 288;\n}" :: "r"((uint32_t)ok) : "memory");
                    if (ok) break;
                }
                CK(4, h0.x);
                if (lane == 0 && is_f) TS2(12);
                const uint32_t hw[10] = {h0.x, h0.y, h0.z, h0.w, h1.x, h1.y, h1.z, h1.w, h2.x, h2.y};
                float m1 = ((mm[0][2] + mm[1][2]) + (mm[2][2] + mm[3][2])) + ((mm[0][3] + mm[1][3]) + (mm[2][3] + mm[3][3])) + (mm[4][2] + mm[4][3]);
                float m2 = (g & 1) ? ((mm[0][1] + mm[1][1]) + (mm[2][1] + mm[3][1])) + mm[4][1] : ((mm[0][0] + mm[1][0]) + (mm[2][0] + mm[3][0])) + mm[4][0];
                m2 += __shfl_xor_sync(0xffffffffu, m2, 4);
                m1 = (m1 + __shfl_xor_sync(0xffffffffu, m1, 1)) + (__shfl_xor_sync(0xffffffffu, m1, 2) + __shfl_xor_sync(0xffffffffu, m1, 3));
                m2 = (__shfl_sync(0xffffffffu, m2, 0) + __shfl_sync(0xffffffffu, m2, 9)) + (__shfl_sync(0xffffffffu, m2, 18) + __shfl_sync(0xffffffffu, m2, 27));
                m1 *= 1.0f / DM;
                const float nmean = bf16r(m1);
                const float var = bf16r(fmaxf(fmaf(-m1, m1, m2 * (1.0f / DM)), 0.f));
                const float vare = bf16r(var + 1e-5f);
                if (is_f) {
                    sts64f(sb + SM_MOM + b * 8, nmean, vare, lane == 0);
                    CK(5, 0);
                    fin_arrive<4>();
                } else {
                    const float rden = rcp_approx(bf16r(sqrt_approx(vare)));
                    if (lb == b) { nmean_l = nmean; rden_l = rden; }
                    __syncwarp();
                    const float2 hw2 = lds64f(sb + SM_X + lb * HPITCH + ((fidx >> 1) * 16 + (lc & 6) * 2 + (fidx & 1) * 2) * 4);
                    const float nh0 = (lc & 1) ? hi_f(__float_as_uint(hw2.x)) : lo_f(__float_as_uint(hw2.x));
                    const float nh1 = (lc & 1) ? hi_f(__float_as_uint(hw2.y)) : lo_f(__float_as_uint(hw2.y));
                    float rr = 0.f;
#pragma unroll
                    for (int i = 0; i < 10; i++) rr = fmaf(lo_f(hw[i]), lo_f(wr[i]), fmaf(hi_f(hw[i]), hi_f(wr[i]), rr));
                    const float sig = bf16r(sigmoid_approx(bf16r((nmean * wsum - warp_sum(rr)) * rden)));
                    if (lb == b) sig_l = sig;
                    const float ln0 = bf16r(bf16r(nmean_l - nh0) * rden_l), ln1 = bf16r(bf16r(nmean_l - nh1) * rden_l);
                    fin_sync<6>(after(after(after(288, sig_l), ln0), ln1));
                    CK(10, lds32(ypart));
                    float2 t[16];
#pragma unroll
                    for (int i = 0; i < 16; i++) t[i] = lds64f(ypart + i * YPITCH);
#pragma unroll
                    for (int o = 1; o < 16; o <<= 1) {
#pragma unroll
                        for (int i = 0; i < 16; i += 2 * o) { t[i].x += t[i + o].x; t[i].y += t[i + o].y; }
                    }
                    const uint32_t o0 = pack_bf16(bf16r(ln0 - bf16r(bf16r(t[0].x) * sig_l)) - nh0, 0.f);
                    const uint32_t o1 = pack_bf16(bf16r(ln1 - bf16r(bf16r(t[0].y) * sig_l)) - nh1, 0.f);
                    asm volatile("{\n.reg .pred p;\nsetp.eq.u32 p, %3, 3;\n@p st.global.u16 [%0], %1;\n@p st.global.u16 [%0 + 16], %2;\n}"
                                 :: "l"(out), "h"((unsigned short)o0), "h"((unsigned short)o1), "r"(b) : "memory");
                    if (b == NB - 1) return;
                    CK(11, 0);
                    if (lane == 0) TS2(13);
                }
                if (b < NB - 1) fin_sync<5>();
            }
            if (cta == 0 && lane == 0) { g_work[0] = 0; g_cnt_z[0] = 0; }
        }
        return;
    }
    if (warp >= NAUX) {
        const int wk = warp - NAUX;
        const uint32_t bar = sb + BAR_KV + wk * 8;
        const uint32_t buf = sb + SM_KV + wk * TILE_BYTES;
        const uint64_t pol = evict_first();
        const int nstatic = NWORK * grid;
        constexpr int POOL0 = NUNITS - NPOOL;
        int uk = wk * grid + cta;
        wait_clk(now_clk() + 2 * (K0_DELAY_NS + wk * K0_STEP_NS));
        request_tile(buf, &p.k, uk, bar, pol);
        uint32_t koff[3], voff[3];
        {
            const int r = lane & 7, hf = (lane >> 3) & 1;
            const int kkey = hf ? 8 + (r ^ 1) : r;
            const int vh = lane >> 4;
            const int vkey = ((r & 1) ? 8 : 0) + (vh ? (r ^ 1) : r);
#pragma unroll
            for (int b = 0; b < 3; b++) {
                const int rk = 3 * kkey + b, rv = 3 * vkey + b;
                koff[b] = buf + rk * 128 + (((lane >> 4) ^ (rk & 7)) << 4);
                voff[b] = buf + rv * 128 + ((hf ^ (rv & 7)) << 4);
            }
        }
        uint32_t phase = 0;
        uint4 qf[6];
        auto load_q = [&](int u) {
            const uint32_t* q = &g_early[row_of(u)].q[j * 4];
#pragma unroll
            for (int i = 0; i < 6; i++) qf[i] = ld_relaxed_v4(q + i * 16);
        };
        load_q(uk);
        int uq[LAG];
        uint32_t sq[LAG];
#pragma unroll
        for (int i = 0; i < LAG; i++) { uq[i] = -1; sq[i] = 0; }
        uint4 mv = make_uint4(0u, 0u, 0u, 0u);
        uint32_t svp = 0;
        float freed = UPB;
        while (true) {
            const int uv = uq[0];
            uint32_t sv = sq[0];
#pragma unroll
            for (int i = 0; i + 1 < LAG; i++) { uq[i] = uq[i + 1]; sq[i] = sq[i + 1]; }
            uq[LAG - 1] = uk;
            if (uk < NUNITS) {
                PH(7);
#pragma unroll 1
                for (int it = 0; it < SPIN_MAX; it++) {
                    uint32_t lo = 0xffffffffu;
#pragma unroll
                    for (int i = 0; i < 6; i++) lo = min(min(lo, min(qf[i].x, qf[i].y)), min(qf[i].z, qf[i].w));
                    if (__all_sync(0xffffffffu, lo != 0)) break;
                    __nanosleep(250);
                    load_q(uk);
                }
                mbar_wait(bar, phase); phase ^= 1;
                PH(0); ARR();
                TSI(0, 16); TSI(1, 18);
                float acc[2][4][4] = {};
#pragma unroll
                for (int ks = 0; ks < 12; ks++) {
                    const uint4 qq = qf[ks >> 1];
                    const uint32_t b0 = (ks & 1) ? qq.z : qq.x, b1 = (ks & 1) ? qq.w : qq.y;
#pragma unroll
                    for (int mt = 0; mt < 4; mt++) {
                        uint32_t a[4];
                        ldsm4(a, (koff[ks >> 2] ^ ((ks & 3) << 5)) + mt * 6144);
                        mma16816(acc[ks & 1][mt], a, b0, b1);
                    }
                }
                PH(1);
                TSI(0, 17); TSI(1, 19);
                if (uv < NUNITS) request_tile(buf, uv >= 0 ? &p.v : &p.k, uv >= 0 ? uv : uk + nstatic, bar, pol);
                const float sa = sel4(j, acc[0][0][0], acc[0][1][0], acc[0][2][0], acc[0][3][0]) + sel4(j, acc[1][0][0], acc[1][1][0], acc[1][2][0], acc[1][3][0]);
                const float sc = sel4(j, acc[0][0][2], acc[0][1][2], acc[0][2][2], acc[0][3][2]) + sel4(j, acc[1][0][2], acc[1][1][2], acc[1][2][2], acc[1][3][2]);
                const uint32_t raw = pack_bf16(sa, sc);
                const float scale = -0.07216878364870322f;
                const uint32_t sk = pack_bf16(lo_f(raw) * scale, hi_f(raw) * scale);
                sq[LAG - 1] = sk;
                if (uk >= POOL0) st_relaxed(&g_st.score[uk - POOL0][lane], sk ? sk : 0x80008000u);
                int a = (int)(sk << 16), b = (int)(sk & 0xffff0000u);
                a ^= (a >> 31) & 0x7fff0000; b ^= (b >> 31) & 0x7fff0000;
                const int mx = __reduce_max_sync(0xffffffffu, max(a, b));
                if (lane == 0) st_relaxed(&g_early[row_of(uk)].umax[pos_of(uk)], (uint32_t)mx | 1u);
            }
            if (uv < 0) {
                uk += nstatic;
                load_q(uk);
                continue;
            }
            if (uv >= NUNITS) break;
            const int bh = row_of(uv);
#pragma unroll 1
            for (int it = 0; it < SPIN_MAX; it++) {
                if (__all_sync(0xffffffffu, (mv.x & mv.y & mv.z & mv.w & 1u) && (uv < POOL0 || svp != 0) && freed == UPB)) break;
                mv = ld_relaxed_v4(&g_early[bh].umax[lane * 4]);
                if (bh >= RING && bh < RED0) freed = __uint_as_float(ld_relaxed_u32(&g_st.oacc[bh - RING][(lane & 7) * 8].w));
                if (uv >= POOL0) svp = ld_relaxed_u32(&g_st.score[uv - POOL0][lane]);
            }
            if (uv >= POOL0) sv = svp;
            PH(2);
            int un = NUNITS, vn = 0;
            draw(un, g_work, uk < NUNITS && lane == 0);
            int mx = __reduce_max_sync(0xffffffffu, max(max((int)mv.x, (int)mv.y), max((int)mv.z, (int)mv.w))) & 0xffff0000;
            mx ^= (mx >> 31) & 0x7fff0000;
            const float m = __int_as_float(mx);
            const float l2e = 1.4426950408889634f;
            const uint32_t pp = pack_bf16(exp2f((lo_f(sv) - m) * l2e), exp2f((hi_f(sv) - m) * l2e));
            uint32_t pb[8];
#pragma unroll
            for (int t = 0; t < 4; t++) {
                pb[2 * t] = __shfl_sync(0xffffffffu, pp, 8 * j + t);
                pb[2 * t + 1] = __shfl_sync(0xffffffffu, pp, 8 * j + 4 + t);
            }
            float lacc[4] = {};
            const uint32_t ones[4] = {0x3f803f80u, 0x3f803f80u, 0x3f803f80u, 0x3f803f80u};
#pragma unroll
            for (int t = 0; t < 4; t++) mma16816(lacc, ones, pb[2 * t], pb[2 * t + 1]);
            if (uv < nstatic) {
                asm volatile("bar.sync 2, %0;" :: "n"((NWORK + 1) * 32) : "memory");
                TSW(3);
            }
            const int grp = 16 * j + 4 * (g & 1) + (g >> 1);
            float4* dst = bh < RED0 ? &g_ring[bh % RING][pos_of(uv)][grp] : oacc_at(p, lds32(sb + SM_SIDE) ^ 1, bh, grp);
            float4* dst2 = other_side(dst);
            float2* ldst = lsum_at(p, lane & 1, bh);
            if (bh >= SROW0 && lane < 2) red_f2(&ldst->x, lacc[0], 1.f);
            float tag = bh < RED0 ? (float)(bh + 1) : 1.f;
            un = __shfl_sync(0xffffffffu, un, 0) + (LAG + 1) * nstatic;
            uint32_t pooled = uq[0] >= POOL0 && lane == 0;
            pin(dst); pin(dst2); pin(ldst); pin(tag); pin(voff[0]); pin(voff[1]); pin(voff[2]); pin(pooled);
            PH(3);
            LT(1);
            mbar_wait(bar, phase); phase ^= 1;
            PH(4); ARR();
            LT(2);
            draw(vn, g_st.pool, pooled);
            float acc[12][4] = {};
#pragma unroll
            for (int t = 0; t < 4; t++) {
#pragma unroll
                for (int mt = 0; mt < 12; mt++) {
                    uint32_t a[4];
                    ldsm4t(a, (voff[mt >> 2] ^ ((mt & 3) << 5)) + t * 6144);
                    mma16816(acc[mt], a, pb[2 * t], pb[2 * t + 1]);
                }
            }
            PH(5);
            if (lane == 0) PROG(un);
            if (un < NUNITS) request_tile(buf, &p.k, un, bar, pol);
            float o[6];
#pragma unroll
            for (int e = 0; e < 6; e++) {
                const int q = e % 3, c = (e / 3) * 2;
                o[e] = sel4(j, acc[q][c], acc[3 + q][c], acc[6 + q][c], acc[9 + q][c]);
            }
            if (bh >= SROW0) {
                red_f4(&dst->x, o[0], o[1], o[2], tag);
                red_f4(&dst[16].x, o[3], o[4], o[5], tag);
                red_f4(&dst2->x, o[0], o[1], o[2], tag);
                red_f4(&dst2[16].x, o[3], o[4], o[5], tag);
            } else {
                if (bh >= RED0) {
                    red_f4(&dst->x, o[0], o[1], o[2], tag);
                    red_f4(&dst[8].x, o[3], o[4], o[5], tag);
                } else {
                    st_relaxed_b128(dst, o[0], o[1], o[2], tag);
                    st_relaxed_b128(dst + 8, o[3], o[4], o[5], tag);
                }
                if (lane == 0) red_f2(&ldst->x, lacc[0], 1.f);
            }
            if (uq[0] >= POOL0) {
                vn = __shfl_sync(0xffffffffu, vn, 0);
                uq[0] = POOL0 + vn;
                if (vn == VTRIG && lane == 0) st_relaxed(g_st.tstart, (now_ns() + TRIG_NS) | 1u);
            }
            if (un < NUNITS) load_q(un);
            PH(6);
            if (uq[0] >= NUNITS && un >= NUNITS) break;
            uk = un;
            if (uq[0] < NUNITS) {
                const int nb = row_of(uq[0]);
                mv = ld_relaxed_v4(&g_early[nb].umax[lane * 4]);
                freed = nb >= RING && nb < RED0 ? __uint_as_float(ld_relaxed_u32(&g_st.oacc[nb - RING][(lane & 7) * 8].w)) : UPB;
                if (uq[0] >= POOL0) svp = ld_relaxed_u32(&g_st.score[uq[0] - POOL0][lane]);
                if (un >= NUNITS) {
                    request_tile(buf, &p.v, uq[0], bar, pol);
                    LT(0);
                }
            }
        }
        if (is_f) asm volatile("bar.arrive 10, %0;" :: "n"((NAUX + NWORK) * 32) : "memory");
        return;
    }

    __nv_bfloat16* xs = reinterpret_cast<__nv_bfloat16*>(smem + SM_X);
    float* red = reinterpret_cast<float*>(smem + SM_RED);
    const int frow = (lane & 7) + ((lane >> 4) << 3), fcol = (lane >> 3) & 1;
    if (cta < NQ_CTAS) {
        uint2 xr[5];
        if (warp < NB) {
#pragma unroll
            for (int i = 0; i < 5; i++) xr[i] = *reinterpret_cast<const uint2*>(p.x + warp * DM + i * 128 + lane * 4);
        }
        TS(26);
        if (warp < NB) {
            float v[20];
#pragma unroll
            for (int i = 0; i < 5; i++) {
                v[4 * i] = lo_f(xr[i].x); v[4 * i + 1] = hi_f(xr[i].x); v[4 * i + 2] = lo_f(xr[i].y); v[4 * i + 3] = hi_f(xr[i].y);
            }
            layernorm20(v);
#pragma unroll
            for (int i = 0; i < 5; i++)
                *reinterpret_cast<uint2*>(xs + warp * XPITCH + i * 128 + lane * 4) =
                    make_uint2(pack_bf16(v[4 * i], v[4 * i + 1]), pack_bf16(v[4 * i + 2], v[4 * i + 3]));
        }
        TS(27);
        aux_sync();
        mbar_wait(sb + BAR_WQ, 0);
        TS(1);
        const uint32_t xfrag = sb + SM_X + ((g & 3) * XPITCH + 2 * j) * 2;
        float acc[3][4] = {};
#pragma unroll
        for (int s = 0; s < 5; s++) {
            const int ks = warp * 5 + s;
            const uint32_t b0 = lds32(xfrag + ks * 32), b1 = lds32(xfrag + ks * 32 + 16);
            const int row = ks * 16 + frow;
#pragma unroll
            for (int mt = 0; mt < 3; mt++) {
                uint32_t a[4];
                ldsm4t(a, sb + SM_WQ + (row * 6 + 2 * mt + fcol) * 16);
                mma16816(acc[mt], a, b0, b1);
            }
        }
        if (j < 2) {
#pragma unroll
            for (int mt = 0; mt < 3; mt++) {
                *reinterpret_cast<float2*>(red + (warp * 48 + mt * 16 + g) * 4 + 2 * j) = make_float2(acc[mt][0], acc[mt][1]);
                *reinterpret_cast<float2*>(red + (warp * 48 + mt * 16 + 8 + g) * 4 + 2 * j) = make_float2(acc[mt][2], acc[mt][3]);
            }
        }
        aux_sync();
        if (tid < 96) {
            const int b = tid & 3, cp = tid >> 2;
            float s0 = 0.f, s1 = 0.f;
#pragma unroll
            for (int w = 0; w < 8; w++) { s0 += red[(w * 48 + 2 * cp) * 4 + b]; s1 += red[(w * 48 + 2 * cp + 1) * 4 + b]; }
            const int h = cta >> 2, d = (cta & 3) * 48 + 2 * cp;
            const int ch = d >> 3, jj = (d & 7) >> 1;
            st_relaxed(&g_early[b * NH + h].q[(ch >> 2) * 16 + jj * 4 + (ch & 3)], pack_neg(s0, s1));
        }
        TS(28);
    }
    if (tid < 160) *reinterpret_cast<uint2*>(smem + SM_X + 4 * HPITCH + tid * 8) = make_uint2(0x3f803f80u, 0x3f803f80u);
    fin_sync<3>();
    const int side = lds32(sb + SM_SIDE);
    mbar_wait(sb + BAR_W, 0);
    TS(7);
    uint32_t part = sb + SM_RED + (warp * 32 + 8 * j + g) * 4;

#pragma unroll 1
    for (int b = 0; b < NB; b++) {
        if (b == NB - 1 && (is_f || is_g)) asm volatile("bar.arrive 9, 288;" ::: "memory");
        if (is_l) {
            uint32_t a[6][2][4];
#pragma unroll
            for (int s = 0; s < 6; s++) {
                const int row = warp * 96 + (s < 4 ? 48 * (s >> 1) + 8 * (s & 1) + 16 * (lane & 1) + (lane & 6) + (lane >> 4) : 48 * (s - 4) + 32 + frow);
#pragma unroll
                for (int mt = 0; mt < 2; mt++) ldsm4t(a[s][mt], sb + SM_A + (row * 4 + ((2 * mt + fcol) ^ ((row >> 1) & 3))) * 16);
            }
            const int bh = b * NH + 28 + (warp >> 1);
            const float4* osrc = oacc_at(p, side, bh, (warp & 1) * 32 + lane);
            const float2* lsrc = lsum_at(p, side, bh);
            if (lane == 0) wait_row_o(p, side, bh, 1);
            __syncwarp();
            float2 lv;
#pragma unroll 1
            for (int it = 0; it < SPIN_MAX; it++) {
                lv = ld_relaxed_f2(lsrc);
                if (__all_sync(0xffffffffu, lv.y == UPB)) break;
            }
            if (warp == 7) TSW(25);
            if (cta == NE_CTAS && lane < 28)
                reinterpret_cast<uint4*>(&g_early[bh])[(warp & 1) * 28 + lane] = make_uint4(0u, 0u, 0u, 0u);
            float rl = rcp_approx(lv.x);
            float4 ov;
            pin(osrc); pin(rl); hold(part);
#pragma unroll 1
            for (int it = 0;; it++) {
                ov = ld_relaxed_f4(osrc);
                if (__all_sync(0xffffffffu, ov.w == UPB || it == SPIN_MAX)) break;
            }
            CK(0, __float_as_uint(ov.x));
            const uint32_t xy = pack_bf16(ov.x * rl, ov.y * rl);
            const float z = ov.z * rl;
            float acc[2][2][4] = {};
#pragma unroll
            for (int s = 0; s < 6; s++) {
                uint32_t bf[2];
#pragma unroll
                for (int kh = 0; kh < 2; kh++) {
                    if (s < 4) bf[kh] = __shfl_sync(0xffffffffu, xy, 8 * s + 4 * kh + j);
                    else bf[kh] = pack_bf16(__shfl_sync(0xffffffffu, z, 16 * (s - 4) + 8 * kh + j), __shfl_sync(0xffffffffu, z, 16 * (s - 4) + 8 * kh + 4 + j));
                }
#pragma unroll
                for (int mt = 0; mt < 2; mt++) mma16816(acc[mt][s & 1], a[s][mt], bf[0], bf[1]);
            }
            sts32f(part, sel4(j, acc[0][0][0] + acc[0][1][0], acc[0][0][2] + acc[0][1][2], acc[1][0][0] + acc[1][1][0], acc[1][0][2] + acc[1][1][2]));
            CK(1, 0);
            fin_arrive<4>();
            if (warp == 7) TSW(30);
            if (warp == 5) TSW(31);
            fin_sync<5>();
            continue;
        }
        {
            const int bh = b * NH + (cta >> 2);
            if (tid == 0) wait_row_o(p, side, bh, UPB);
            aux_sync();
            if (warp < 5) {
                uint32_t ob[12][2];
                load_o<4>(p, ob, bh, 0, j);
                float acc[2][2][4] = {};
#pragma unroll
                for (int ks = 0; ks < 12; ks++) {
                    const int row = ks * 16 + frow;
#pragma unroll
                    for (int mt = 0; mt < 2; mt++) {
                        uint32_t a[4];
                        ldsm4t(a, sb + SM_A + warp * 12288 + (row * 4 + ((2 * mt + fcol) ^ ((row >> 1) & 3))) * 16);
                        mma16816(acc[mt][ks & 1], a, ob[ks][0], ob[ks][1]);
                    }
                }
                red_f2(&g_st.attn[b][(cta & 3) * 160 + warp * 32 + 8 * j + g].x,
                       sel4(j, acc[0][0][0] + acc[0][1][0], acc[0][0][2] + acc[0][1][2], acc[1][0][0] + acc[1][1][0], acc[1][0][2] + acc[1][1][2]), 1.f);
                TS(8);
            } else if (warp > 5 && (cta & 3) == 0 && tid - 192 < 56) {
                reinterpret_cast<uint4*>(&g_early[bh])[tid - 192] = make_uint4(0u, 0u, 0u, 0u);
            }
        }
        if (is_f) {
            const int kq = warp >> 1, tp = warp & 1;
            uint32_t hfrag = sb + SM_X + min(g, 4) * HPITCH + (kq * 80 + 4 * j) * 4;
            uint32_t fpart = sb + SM_RED + 2 * j * FPITCH + warp * 128 + g * 16;
            uint32_t dsum = sb + SM_RED + (lane >> 3) * FPITCH + tp * 128 + (lane & 7) * 16, csum = sb + SM_RED + 4 * FPITCH + tp * 128 + (lane & 7) * 16;
            uint32_t mom = sb + SM_MOM + (lane >> 3) * 8;
            uint32_t* dst = sided<uint32_t>(p, side ^ 1, X_A + (2 * fidx + tp) * 128 + (lane ^ 2 * tp) * 4);
            uint32_t* dst2 = other_side(dst);
            hold(fpart); hold(hfrag); hold(dsum); hold(csum); hold(mom); hold(dst); hold(dst2);
            uint4 hv[5] = {};
#pragma unroll
            for (int s = 0; s < 5; s++) lds128_if(hv[s], hfrag + s * 64, true);
            if (b == NB - 1) asm volatile("bar.sync 10, %0;" :: "n"((NAUX + NWORK) * 32) : "memory");
            uint32_t ga[10][2][4];
#pragma unroll
            for (int s = 0; s < 10; s++) {
                if (s % 5 == 0 && b == NB - 1) mbar_wait(sb + BAR_G + (kq * 2 + s / 5) * 8, 0);
                const int row = (kq * 10 + s) * 16 + frow;
#pragma unroll
                for (int t = 0; t < 2; t++) ldsm4t(ga[s][t], sb + SM_G + fcol * 40960 + (row * 4 + ((2 * tp + t) ^ ((row >> 1) & 3))) * 16);
            }
            if (warp == NAUX - 1) TSW(9);
            uint32_t dep = 0;
#pragma unroll
            for (int s = 0; s < 5; s++) dep ^= ga[s][0][0] ^ ga[s][1][0];
            fin_sync<7>(288 + (dep & (side >> 1)));
#pragma unroll
            for (int s = 0; s < 5; s++) lds128_if(hv[s], hfrag + s * 64, g == b);
            float acc[2][2][4] = {};
#pragma unroll
            for (int s = 0; s < 5; s++) {
#pragma unroll
                for (int t = 0; t < 2; t++) mma16816(acc[t][0], ga[2 * s][t], hv[s].x, hv[s].y);
#pragma unroll
                for (int t = 0; t < 2; t++) mma16816(acc[t][1], ga[2 * s + 1][t], hv[s].z, hv[s].w);
            }
#pragma unroll
            for (int e = 0; e < 2; e++)
                sts128f(fpart + e * FPITCH, acc[0][0][e] + acc[0][1][e], acc[0][0][2 + e] + acc[0][1][2 + e],
                        acc[1][0][e] + acc[1][1][e], acc[1][0][2 + e] + acc[1][1][2 + e], 2 * j + e < 5);
            CK(5, 0);
            if (warp < 2) {
                fin_sync<4>();
                CK(6, lds32(dsum));
                float2 m = lds64f(mom);
                m.y = rcp_approx(bf16r(sqrt_approx(m.y)));
                const float4 d = sum4x4(dsum), cs = sum4x4(csum);
                const float g0 = bf16r(fmaf(m.x, cs.x, -d.x) * m.y), g1 = bf16r(fmaf(m.x, cs.z, -d.z) * m.y);
                const float u0 = bf16r(fmaf(m.x, cs.y, -d.y) * m.y), u1 = bf16r(fmaf(m.x, cs.w, -d.w) * m.y);
                const uint32_t av = pack_neg(bf16r(g0 * sigmoid_approx(g0)) * u0, bf16r(g1 * sigmoid_approx(g1)) * u1);
                asm volatile("{\n.reg .pred p;\nsetp.eq.u32 p, %3, 3;\n@p st.relaxed.gpu.global.u32 [%0], %2;\n@p st.relaxed.gpu.global.u32 [%1], %2;\n}"
                             :: "l"(dst), "l"(dst2), "r"(av), "r"(b) : "memory");
                CK(7, 0);
                TS(14);
            } else {
                fin_arrive<4>();
            }
        } else if (is_g) {
            if (b == NB - 1) {
                mbar_wait(sb + BAR_G + warp * 8, 0);
                if (warp == NAUX - 1) TSW(10);
            }
            uint32_t wb[3][2][2][4];
#pragma unroll
            for (int s = 0; s < 12; s++) {
                const int odd = (lane >> 2) & 1, c = ((lane & 2) * 2 + (s & 1) * 2 + (lane >> 4)) ^ (2 * odd);
                const int row = (warp * 12 + (s >> 1) * 2 + odd) * 16 + (lane & 1) * 8 + c;
                ldsm4t(wb[s >> 2][(s >> 1) & 1][s & 1], sb + SM_G + (row * 2 + (fcol ^ ((row >> 2) & 1))) * 16);
            }
            const uint4* asrc[3];
#pragma unroll
            for (int q = 0; q < 3; q++) {
                asrc[q] = sided<uint4>(p, side, X_A + (warp * 12 + 4 * q + 2 * (g >> 2) + (j >> 1)) * 128 + (g & 3) * 32 + (j & 1) * 16);
                pin(asrc[q]);
            }
            uint32_t ypart = sb + SM_RED2 + (warp * 2 + (j >> 1)) * YPITCH + (j & 1) * 160 + g * 16;
            pin(ypart);
            fin_sync<7>();
            uint4 v[3] = {};
            uint32_t mq[3] = {};
#pragma unroll 1
            for (int it = b < NB - 1 ? SPIN_MAX : 0;; it++) {
                asm volatile("{\n.reg .pred p0, p1, p2;\nsetp.eq.u32 p0, %15, 0;\nsetp.eq.u32 p1, %16, 0;\nsetp.eq.u32 p2, %17, 0;\n"
                             "@p0 ld.relaxed.gpu.global.v4.u32 {%0,%1,%2,%3}, [%12];\n"
                             "@p1 ld.relaxed.gpu.global.v4.u32 {%4,%5,%6,%7}, [%13];\n"
                             "@p2 ld.relaxed.gpu.global.v4.u32 {%8,%9,%10,%11}, [%14];\n}"
                             : "+r"(v[0].x), "+r"(v[0].y), "+r"(v[0].z), "+r"(v[0].w), "+r"(v[1].x), "+r"(v[1].y), "+r"(v[1].z), "+r"(v[1].w),
                               "+r"(v[2].x), "+r"(v[2].y), "+r"(v[2].z), "+r"(v[2].w)
                             : "l"(asrc[0]), "l"(asrc[1]), "l"(asrc[2]), "r"(mq[0]), "r"(mq[1]), "r"(mq[2]) : "memory");
#pragma unroll
                for (int q = 0; q < 3; q++) mq[q] = min(min(v[q].x, v[q].y), min(v[q].z, v[q].w));
                const uint32_t lo = min(min(mq[0], mq[1]), mq[2]);
                if (__all_sync(0xffffffffu, lo != 0 || it == SPIN_MAX)) break;
            }
            CK(8, v[0].x);
            float acc[2][2][4] = {};
#pragma unroll
            for (int q = 0; q < 3; q++) {
#pragma unroll
                for (int pr = 0; pr < 2; pr++) {
                    mma16816(acc[pr][0], wb[q][pr][0], v[q].x, v[q].y);
                    mma16816(acc[pr][1], wb[q][pr][1], v[q].z, v[q].w);
                }
            }
            float y[4];
#pragma unroll
            for (int e = 0; e < 4; e++) y[e] = j < 2 ? acc[0][0][e] + acc[0][1][e] : acc[1][0][e] + acc[1][1][e];
            asm volatile("st.shared.v4.f32 [%0], {%1,%2,%3,%4};" :: "r"(ypart), "f"(y[0]), "f"(y[2]), "f"(y[1]), "f"(y[3]) : "memory");
            CK(9, 0);
            fin_arrive<6>();
        } else {
            continue;
        }
        if (b < NB - 1) fin_sync<5>();
    }
}

typedef CUresult (*EncodeFn)(CUtensorMap*, CUtensorMapDataType, cuuint32_t, void*, const cuuint64_t*, const cuuint64_t*,
                             const cuuint32_t*, const cuuint32_t*, CUtensorMapInterleave, CUtensorMapSwizzle,
                             CUtensorMapL2promotion, CUtensorMapFloatOOBfill);

CUtensorMap make_map(EncodeFn enc, void* ptr, uint64_t cols, uint64_t rows, uint32_t bcols, uint32_t brows,
                     CUtensorMapSwizzle sw, CUtensorMapL2promotion promo) {
    CUtensorMap m;
    const cuuint64_t dims[2] = {cols, rows};
    const cuuint64_t strides[1] = {cols * 2};
    const cuuint32_t box[2] = {bcols, brows};
    const cuuint32_t es[2] = {1, 1};
    enc(&m, CU_TENSOR_MAP_DATA_TYPE_BFLOAT16, 2, ptr, dims, strides, box, es, CU_TENSOR_MAP_INTERLEAVE_NONE, sw, promo,
        CU_TENSOR_MAP_FLOAT_OOB_FILL_NONE);
    return m;
}

}

extern "C" void kernel_launch(void* const* d_in, const int* in_sizes, int n_in, void* d_out, int out_size) {
    (void)in_sizes; (void)n_in; (void)out_size;
    static EncodeFn enc = nullptr;
    static int sms = 0;
    static void* raw = nullptr;
    if (!enc) {
        cudaDriverEntryPointQueryResult qr;
        cudaGetDriverEntryPoint("cuTensorMapEncodeTiled", (void**)&enc, cudaEnableDefault, &qr);
        int dev = 0;
        cudaGetDevice(&dev);
        cudaDeviceGetAttribute(&sms, cudaDevAttrMultiProcessorCount, dev);
        cudaGetSymbolAddress(&raw, g_raw);
        cudaFuncSetAttribute(fused_decode_kernel, cudaFuncAttributeMaxDynamicSharedMemorySize, SM_TOTAL);
    }
    if (sms < NCTAS) return;
    const CUtensorMapL2promotion WPROMO = CU_TENSOR_MAP_L2_PROMOTION_L2_128B;
    Params p;
    p.k = make_map(enc, d_in[1], 64, (uint64_t)NBH * SK * 3, 64, TILE_ROWS, CU_TENSOR_MAP_SWIZZLE_128B, CU_TENSOR_MAP_L2_PROMOTION_NONE);
    p.v = make_map(enc, d_in[2], 64, (uint64_t)NBH * SK * 3, 64, TILE_ROWS, CU_TENSOR_MAP_SWIZZLE_128B, CU_TENSOR_MAP_L2_PROMOTION_NONE);
    p.wq = make_map(enc, d_in[3], NH * DH, DM, 48, 160, CU_TENSOR_MAP_SWIZZLE_NONE, WPROMO);
    p.wo = make_map(enc, d_in[4], DM, NH * DH, 32, 48, CU_TENSOR_MAP_SWIZZLE_64B, WPROMO);
    p.wg = make_map(enc, d_in[7], FF, DM, 32, 80, CU_TENSOR_MAP_SWIZZLE_64B, WPROMO);
    p.wu = make_map(enc, d_in[8], FF, DM, 32, 80, CU_TENSOR_MAP_SWIZZLE_64B, WPROMO);
    p.wd = make_map(enc, d_in[9], DM, FF, 16, 192, CU_TENSOR_MAP_SWIZZLE_32B, WPROMO);
    p.scratch = reinterpret_cast<Scratch*>((reinterpret_cast<uintptr_t>(raw) + PAGE - 1) & ~(uintptr_t)(PAGE - 1));
    p.wq_raw = (const char*)d_in[3];
    p.x = (const __nv_bfloat16*)d_in[0];
    p.wr = (const __nv_bfloat16*)d_in[6];
    p.out = (__nv_bfloat16*)d_out;
    fused_decode_kernel<<<NCTAS, NTHREADS, SM_TOTAL, cudaStreamPerThread>>>(p);
}
```

```cpp
#include <cuda_runtime.h>
#include <cuda_bf16.h>
#include <cuda.h>
#include <stdint.h>

namespace {

constexpr int NB = 4, NH = 32, SK = 8192, DH = 192, DM = 640, FF = 1536;
constexpr int NBH = NB * NH;
constexpr int TILE = 64;
constexpr int UPB = SK / TILE;
constexpr int NUNITS = NBH * UPB;
constexpr int TILE_BYTES = TILE * DH * 2;
constexpr int TILE_ROWS = TILE * 3;
constexpr int NCTAS = 132;
constexpr int NQ_CTAS = 128;
constexpr int NE_CTAS = 112;

constexpr int SROW0 = NBH - 4;

#define GW 6
#define PRES 48
#define NWORK 2
#define NWL 2
#define SKEW 16
#define LAG 3
#define NPOOL 896
#define RED0 120
#define RING 12
#define K0_DELAY_NS 1600
#define K0_STEP_NS 900
#define WO_AT_NS 3600
#define WO_GAP_NS 550
#define VTRIG (NPOOL - 240)
#define TRIG_NS 2200
#define GCLK 250
#define DOFF 2100
#define DCLK 150
constexpr int NAUX = 8;
constexpr int NTHREADS = (NAUX + NWORK + 2) * 32;
constexpr int SPIN_MAX = 1 << 22;

constexpr int SM_KV = 0;
constexpr int SM_A = SM_KV + NWORK * TILE_BYTES;
constexpr int SM_WQ = SM_A + 61440;
constexpr int SM_G = SM_WQ;
constexpr int SM_X = SM_G + 81920;
constexpr int XPITCH = 648;
constexpr int HPITCH = 1344;
constexpr int SM_RED = SM_X + 5 * HPITCH;
constexpr int FPITCH = 1040;
constexpr int SM_RED2 = SM_RED;
constexpr int YPITCH = 320;
constexpr int SM_MISC = SM_RED + 6144;
constexpr int BAR_KV = SM_MISC, BAR_WQ = SM_MISC + 32, BAR_W = SM_MISC + 40, SM_SIDE = SM_MISC + 48, BAR_G = SM_MISC + 64, SM_MOM = SM_MISC + 128;
constexpr int SM_TOTAL = SM_MISC + 160;

struct Scratch;
struct Params {
    CUtensorMap k, v;
    CUtensorMap wq;
    CUtensorMap wo;
    CUtensorMap wg, wu;
    CUtensorMap wd;
    Scratch* scratch;
    const char* wq_raw;
    const __nv_bfloat16 *x, *wr;
    __nv_bfloat16* out;
};

struct Early {
    uint32_t q[96];
    uint32_t umax[UPB];
};
struct State {
    float4 oacc[SROW0][64];
    float2 attn[NB][DM];
    float2 lsum[SROW0][16];
    unsigned pool[64];
    uint32_t tstart[32];
    uint32_t score[NPOOL][32];
};
constexpr int STATE_V4 = ((sizeof(State) / 32 + NQ_CTAS - 1) / NQ_CTAS) * 2;
static_assert(sizeof(State) % 32 == 0, "State is cleared in whole sectors");
static_assert(sizeof(Early) == 56 * 16, "an Early entry is cleared by 56 threads");
constexpr uint32_t X_O = 0;
constexpr uint32_t X_L = X_O + 4 * 1024;
constexpr uint32_t X_H = X_L + 4 * 128;
constexpr uint32_t X_A = X_H + NB * DM * 2;
constexpr uint32_t X_P = X_A + NB * FF * 2;
constexpr uint32_t X_END = X_P + 4096;
static_assert(X_END <= 8 * 4096 && RED0 <= SROW0, "");
struct Scratch {
    unsigned char sided[8][2][4096];
    unsigned work[64];
    unsigned cnt_z[32];
    unsigned char pad0[1024];
    Early early[NBH];
    unsigned char pad1[1024];
    State st;
    unsigned char pad2[1792];
    float4 ring[RING][UPB][64];
};
constexpr size_t PAGE = 2u << 20;
static_assert(sizeof(Scratch) <= PAGE, "scratch must fit one page");
__device__ __align__(128) unsigned char g_raw[2 * PAGE];
template <typename T> __device__ __forceinline__ T* sided(const Params& p, int side, uint32_t x) {
    const uint32_t pair = (x >> 10) & 7;
    return reinterpret_cast<T*>(&p.scratch->sided[pair][(side ^ pair) & 1]
                                    [(x & 127) + ((x & 128) << 1) + ((x & 768) << 2) + ((x >> 6) & 128) + ((x >> 5) & 512)]);
}
template <typename T> __device__ __forceinline__ T* other_side(T* p) { return reinterpret_cast<T*>(reinterpret_cast<uintptr_t>(p) ^ 4096); }
#define g_early p.scratch->early
#define g_st p.scratch->st
#define g_ring p.scratch->ring
#define g_cnt_z p.scratch->cnt_z
#define g_work p.scratch->work
#define TS(i)
#define TSW(i)
#define TS2(i)
#define TSI(n, i)
#define PH(i)
#define CK(i, dep)
#define ARR()
#define PROG(u)
#define LT(i)

__device__ __forceinline__ int row_of(int u) { return (((unsigned)u >> (7 + NWL)) << NWL) | (u & ((1 << NWL) - 1)); }
__device__ __forceinline__ int pos_of(int u) { return ((unsigned)u >> NWL) & (UPB - 1); }
__device__ __forceinline__ int tile_of(int u) { return (row_of(u) * UPB + ((pos_of(u) + (u & ((1 << NWL) - 1)) * SKEW) & (UPB - 1))) * TILE_ROWS; }

__device__ __forceinline__ uint32_t s2u(const void* p) { return (uint32_t)__cvta_generic_to_shared(p); }
__device__ __forceinline__ void mbar_init(uint32_t bar, int cnt) {
    asm volatile("mbarrier.init.shared::cta.b64 [%0], %1;" :: "r"(bar), "r"(cnt) : "memory");
}
__device__ __forceinline__ void mbar_expect_tx(uint32_t bar, uint32_t bytes) {
    asm volatile("mbarrier.arrive.expect_tx.shared::cta.b64 _, [%0], %1;" :: "r"(bar), "r"(bytes) : "memory");
}
__device__ __forceinline__ void mbar_wait(uint32_t bar, uint32_t parity) {
    asm volatile("{\n.reg .pred p;\n.reg .u32 n;\nmov.u32 n, 0;\nWAIT_LOOP:\n"
                 "mbarrier.try_wait.parity.shared::cta.b64 p, [%0], %1;\n"
                 "@p bra WAIT_DONE;\nadd.u32 n, n, 1;\nsetp.lt.u32 p, n, %2;\n@p bra WAIT_LOOP;\nWAIT_DONE:\n}"
                 :: "r"(bar), "r"(parity), "n"(SPIN_MAX) : "memory");
}
__device__ __forceinline__ void request_tile(uint32_t dst, const CUtensorMap* tm, int unit, uint32_t bar, uint64_t pol) {
    asm volatile("{\n.reg .pred p;\nelect.sync _|p, 0xffffffff;\n"
                 "@p mbarrier.arrive.expect_tx.shared::cta.b64 _, [%2], %6;\n"
                 "@p cp.async.bulk.tensor.2d.shared::cluster.global.mbarrier::complete_tx::bytes.L2::cache_hint "
                 "[%0], [%1, {%3, %4}], [%2], %5;\n}"
                 :: "r"(dst), "l"(tm), "r"(bar), "r"(0), "r"(tile_of(unit)), "l"(pol), "n"(TILE_BYTES) : "memory");
}
__device__ __forceinline__ uint32_t now_ns() { uint32_t t; asm volatile("mov.u32 %0, %%globaltimer_lo;" : "=r"(t)); return t; }
__device__ __forceinline__ uint32_t now_clk() { uint32_t t; asm volatile("mov.u32 %0, %%clock;" : "=r"(t)); return t; }
__device__ __forceinline__ void wait_clk(uint32_t t) { while (__any_sync(0xffffffffu, (int)(now_clk() - t) < 0)) {} }
__device__ __forceinline__ uint64_t evict_first() {
    uint64_t pol;
    asm volatile("createpolicy.fractional.L2::evict_first.b64 %0, 1.0;" : "=l"(pol));
    return pol;
}
__device__ __forceinline__ void request_box(uint32_t dst, const CUtensorMap* tm, int col, int row, uint32_t bar) {
    asm volatile("{\n.reg .pred p;\nelect.sync _|p, 0xffffffff;\n"
                 "@p cp.async.bulk.tensor.2d.shared::cluster.global.mbarrier::complete_tx::bytes [%0], [%1, {%3, %4}], [%2];\n}"
                 :: "r"(dst), "l"(tm), "r"(bar), "r"(col), "r"(row) : "memory");
}
__device__ __forceinline__ void request_box(uint32_t dst, const CUtensorMap* tm, int col, int row, uint32_t bar, uint64_t pol) {
    asm volatile("{\n.reg .pred p;\nelect.sync _|p, 0xffffffff;\n"
                 "@p cp.async.bulk.tensor.2d.shared::cluster.global.mbarrier::complete_tx::bytes.L2::cache_hint [%0], [%1, {%3, %4}], [%2], %5;\n}"
                 :: "r"(dst), "l"(tm), "r"(bar), "r"(col), "r"(row), "l"(pol) : "memory");
}
__device__ __forceinline__ uint32_t lds32(uint32_t addr) {
    uint32_t v;
    asm volatile("ld.shared.u32 %0, [%1];" : "=r"(v) : "r"(addr) : "memory");
    return v;
}
__device__ __forceinline__ void ldsm4(uint32_t (&r)[4], uint32_t addr) {
    asm volatile("ldmatrix.sync.aligned.m8n8.x4.shared.b16 {%0,%1,%2,%3}, [%4];"
                 : "=r"(r[0]), "=r"(r[1]), "=r"(r[2]), "=r"(r[3]) : "r"(addr) : "memory");
}
__device__ __forceinline__ void ldsm4t(uint32_t (&r)[4], uint32_t addr) {
    asm volatile("ldmatrix.sync.aligned.m8n8.x4.trans.shared.b16 {%0,%1,%2,%3}, [%4];"
                 : "=r"(r[0]), "=r"(r[1]), "=r"(r[2]), "=r"(r[3]) : "r"(addr) : "memory");
}
__device__ __forceinline__ void mma16816(float (&c)[4], const uint32_t (&a)[4], uint32_t b0, uint32_t b1) {
    asm volatile("mma.sync.aligned.m16n8k16.row.col.f32.bf16.bf16.f32 {%0,%1,%2,%3}, {%4,%5,%6,%7}, {%8,%9}, {%0,%1,%2,%3};"
                 : "+f"(c[0]), "+f"(c[1]), "+f"(c[2]), "+f"(c[3])
                 : "r"(a[0]), "r"(a[1]), "r"(a[2]), "r"(a[3]), "r"(b0), "r"(b1));
}
__device__ __forceinline__ uint4 ld_relaxed_v4(const void* p) {
    uint4 v;
    asm volatile("ld.relaxed.gpu.global.v4.u32 {%0,%1,%2,%3}, [%4];" : "=r"(v.x), "=r"(v.y), "=r"(v.z), "=r"(v.w) : "l"(p) : "memory");
    return v;
}
__device__ __forceinline__ float4 ld_relaxed_f4(const void* p) {
    float4 v;
    asm volatile("ld.relaxed.gpu.global.v4.f32 {%0,%1,%2,%3}, [%4];" : "=f"(v.x), "=f"(v.y), "=f"(v.z), "=f"(v.w) : "l"(p) : "memory");
    return v;
}
__device__ __forceinline__ float2 ld_relaxed_f2(const void* p) {
    float2 v;
    asm volatile("ld.relaxed.gpu.global.v2.f32 {%0,%1}, [%2];" : "=f"(v.x), "=f"(v.y) : "l"(p) : "memory");
    return v;
}
__device__ __forceinline__ float4 ld_relaxed_b128(const void* p) {
    float4 v;
    asm volatile("{\n.reg .b128 t;\n.reg .b64 a, b;\nld.relaxed.gpu.global.b128 t, [%4];\nmov.b128 {a, b}, t;\n"
                 "mov.b64 {%0, %1}, a;\nmov.b64 {%2, %3}, b;\n}" : "=f"(v.x), "=f"(v.y), "=f"(v.z), "=f"(v.w) : "l"(p) : "memory");
    return v;
}
__device__ __forceinline__ void st_relaxed_b128(void* p, float x, float y, float z, float w) {
    asm volatile("{\n.reg .b128 t;\n.reg .b64 a, b;\nmov.b64 a, {%1, %2};\nmov.b64 b, {%3, %4};\nmov.b128 t, {a, b};\n"
                 "st.relaxed.gpu.global.b128 [%0], t;\n}" :: "l"(p), "f"(x), "f"(y), "f"(z), "f"(w) : "memory");
}
__device__ __forceinline__ unsigned ld_acquire(const unsigned* p) {
    unsigned v;
    asm volatile("ld.acquire.gpu.global.u32 %0, [%1];" : "=r"(v) : "l"(p) : "memory");
    return v;
}
__device__ __forceinline__ void st_relaxed(void* p, uint32_t v) {
    asm volatile("st.relaxed.gpu.global.u32 [%0], %1;" :: "l"(p), "r"(v) : "memory");
}
__device__ __forceinline__ void red_f2(float* p, float a, float b) {
    asm volatile("red.relaxed.gpu.global.add.v2.f32 [%0], {%1,%2};" :: "l"(p), "f"(a), "f"(b) : "memory");
}
__device__ __forceinline__ void red_f4(float* p, float a, float b, float c, float d) {
    asm volatile("red.relaxed.gpu.global.add.v4.f32 [%0], {%1,%2,%3,%4};" :: "l"(p), "f"(a), "f"(b), "f"(c), "f"(d) : "memory");
}
__device__ __forceinline__ void draw(int& ticket, unsigned* ctr, bool pred) {
    asm volatile("{\n.reg .pred p;\nsetp.ne.u32 p, %2, 0;\n@p atom.relaxed.gpu.global.inc.u32 %0, [%1], 0x7fffffff;\n}"
                 : "+r"(ticket) : "l"(ctr), "r"((uint32_t)pred) : "memory");
}
__device__ __forceinline__ void red_release(unsigned* p) {
    asm volatile("red.release.gpu.global.add.u32 [%0], 1;" :: "l"(p) : "memory");
}
__device__ __forceinline__ uint32_t ld_relaxed_u32(const void* p) {
    uint32_t v;
    asm volatile("ld.relaxed.gpu.global.u32 %0, [%1];" : "=r"(v) : "l"(p) : "memory");
    return v;
}
__device__ __forceinline__ float rcp_approx(float v) {
    float r;
    asm("rcp.approx.ftz.f32 %0, %1;" : "=f"(r) : "f"(v));
    return r;
}
__device__ __forceinline__ float sigmoid_approx(float v) {
    float e;
    asm("ex2.approx.ftz.f32 %0, %1;" : "=f"(e) : "f"(v * -1.4426950408889634f));
    return rcp_approx(1.0f + e);
}
__device__ __forceinline__ float sqrt_approx(float v) {
    float r;
    asm("sqrt.approx.ftz.f32 %0, %1;" : "=f"(r) : "f"(v));
    return r;
}
__device__ __forceinline__ uint2 ld_relaxed_v2(const void* p) {
    uint2 v;
    asm volatile("ld.relaxed.gpu.global.v2.u32 {%0,%1}, [%2];" : "=r"(v.x), "=r"(v.y) : "l"(p) : "memory");
    return v;
}
__device__ __forceinline__ void wait_count(const unsigned* p, unsigned target) {
#pragma unroll 1
    for (int it = 0; it < SPIN_MAX; it++) {
        if (ld_acquire(p) >= target) break;
        __nanosleep(400);
    }
}
__device__ __forceinline__ float4* oacc_at(const Params& p, int side, int row, int grp) {
    return row >= SROW0 ? sided<float4>(p, side, X_O + (row - SROW0) * 1024 + grp * 16) : &g_st.oacc[row][grp];
}
__device__ __forceinline__ float2* lsum_at(const Params& p, int side, int row) {
    return row >= SROW0 ? sided<float2>(p, side, X_L + (row - SROW0) * 128) : g_st.lsum[row];
}
__device__ __forceinline__ void wait_row(const Params& p, int side, int bh, float n) {
    const float2* l = lsum_at(p, side, bh);
#pragma unroll 1
    for (int it = 0; it < SPIN_MAX; it++) {
        const float c = ld_relaxed_f2(l).y;
        if (c >= n) break;
        if (c == 0.f) __nanosleep(600);
    }
}
__device__ __forceinline__ void wait_row_o(const Params& p, int side, int bh, float n) {
    wait_row(p, side, bh, n);
    if (bh >= RED0) return;
#pragma unroll 1
    for (int it = 0; it < SPIN_MAX; it++) {
        if (__uint_as_float(ld_relaxed_u32(&g_st.oacc[bh][0].w)) == UPB) break;
        __nanosleep(300);
    }
}
__device__ __forceinline__ uint32_t pack_bf16(float lo, float hi) {
    uint32_t r;
    asm("cvt.rn.bf16x2.f32 %0, %1, %2;" : "=r"(r) : "f"(hi), "f"(lo));
    return r;
}
__device__ __forceinline__ float bf16r(float v) { return __uint_as_float(pack_bf16(0.f, v)); }
__device__ __forceinline__ uint32_t pack_neg(float lo, float hi) {
    const uint32_t w = pack_bf16(-lo, -hi);
    return w ? w : 0x80008000u;
}
__device__ __forceinline__ float lo_f(uint32_t v) { return __uint_as_float(v << 16); }
__device__ __forceinline__ float hi_f(uint32_t v) { return __uint_as_float(v & 0xffff0000u); }
__device__ __forceinline__ float warp_sum(float v) {
#pragma unroll
    for (int o = 16; o; o >>= 1) v += __shfl_xor_sync(0xffffffffu, v, o);
    return v;
}
__device__ __forceinline__ void layernorm20(float (&v)[20]) {
    float s = 0.f;
#pragma unroll
    for (int i = 0; i < 20; i++) s += v[i];
    const float mean = warp_sum(s) * (1.0f / DM);
    float q = 0.f;
#pragma unroll
    for (int i = 0; i < 20; i++) { const float d = v[i] - mean; q += d * d; }
    const float var = bf16r(warp_sum(q) * (1.0f / DM));
    const float m = bf16r(mean);
    const float rden = 1.0f / bf16r(sqrtf(bf16r(var + 1e-5f)));
#pragma unroll
    for (int i = 0; i < 20; i++) v[i] = bf16r(bf16r(v[i] - m) * rden);
}

__device__ __forceinline__ float sel4(int j, float a, float b, float c, float d) {
    float lo, hi, r;
    asm("{\n.reg .pred p;\nsetp.ne.s32 p, %3, 0;\nselp.f32 %0, %2, %1, p;\n}" : "=f"(lo) : "f"(a), "f"(b), "r"(j & 1));
    asm("{\n.reg .pred p;\nsetp.ne.s32 p, %3, 0;\nselp.f32 %0, %2, %1, p;\n}" : "=f"(hi) : "f"(c), "f"(d), "r"(j & 1));
    asm("{\n.reg .pred p;\nsetp.ne.s32 p, %3, 0;\nselp.f32 %0, %2, %1, p;\n}" : "=f"(r) : "f"(lo), "f"(hi), "r"(j & 2));
    return r;
}
template <typename T> __device__ __forceinline__ void pin(T*& p) { asm volatile("" : "+l"(p)); }
__device__ __forceinline__ void pin(uint32_t& v) { asm volatile("" : "+r"(v)); }
__device__ __forceinline__ void pin(float& v) { asm volatile("" : "+f"(v)); }
__device__ __forceinline__ void hold(uint32_t& v) { v = __shfl_xor_sync(0xffffffffu, v, 0); }
template <typename T> __device__ __forceinline__ void hold(T*& p) {
    p = reinterpret_cast<T*>(__shfl_xor_sync(0xffffffffu, (unsigned long long)reinterpret_cast<uintptr_t>(p), 0));
}
__device__ __forceinline__ uint32_t after(uint32_t n, float v) {
    asm volatile("{\n.reg .pred p;\nsetp.eq.u32 p, %1, 0x7fc1a5a5;\n@p add.u32 %0, %0, 32;\n}" : "+r"(n) : "r"(__float_as_uint(v)));
    return n;
}
__device__ __forceinline__ float2 lds64f(uint32_t addr) {
    float2 v;
    asm volatile("ld.shared.v2.f32 {%0,%1}, [%2];" : "=f"(v.x), "=f"(v.y) : "r"(addr) : "memory");
    return v;
}
__device__ __forceinline__ float4 lds128f(uint32_t addr) {
    float4 v;
    asm volatile("ld.shared.v4.f32 {%0,%1,%2,%3}, [%4];" : "=f"(v.x), "=f"(v.y), "=f"(v.z), "=f"(v.w) : "r"(addr) : "memory");
    return v;
}
__device__ __forceinline__ void sts64f(uint32_t addr, float a, float b, bool pred) {
    asm volatile("{\n.reg .pred p;\nsetp.ne.u32 p, %3, 0;\n@p st.shared.v2.f32 [%0], {%1,%2};\n}" :: "r"(addr), "f"(a), "f"(b), "r"((uint32_t)pred) : "memory");
}
__device__ __forceinline__ void sts128f(uint32_t addr, float a, float b, float c, float d, bool pred) {
    asm volatile("{\n.reg .pred p;\nsetp.ne.u32 p, %5, 0;\n@p st.shared.v4.f32 [%0], {%1,%2,%3,%4};\n}"
                 :: "r"(addr), "f"(a), "f"(b), "f"(c), "f"(d), "r"((uint32_t)pred) : "memory");
}
__device__ __forceinline__ void lds128_if(uint4& v, uint32_t addr, bool pred) {
    asm volatile("{\n.reg .pred p;\nsetp.ne.u32 p, %5, 0;\n@p ld.shared.v4.u32 {%0,%1,%2,%3}, [%4];\n}"
                 : "+r"(v.x), "+r"(v.y), "+r"(v.z), "+r"(v.w) : "r"(addr), "r"((uint32_t)pred) : "memory");
}
__device__ __forceinline__ void sts32f(uint32_t addr, float v) { asm volatile("st.shared.f32 [%0], %1;" :: "r"(addr), "f"(v) : "memory"); }
template <int ID> __device__ __forceinline__ void fin_arrive() { asm volatile("bar.arrive %0, 288;" :: "n"(ID) : "memory"); }
template <int ID> __device__ __forceinline__ void fin_sync() { asm volatile("bar.sync %0, 288;" :: "n"(ID) : "memory"); }
template <int ID> __device__ __forceinline__ void fin_sync(uint32_t n) { asm volatile("bar.sync %0, %1;" :: "n"(ID), "r"(n) : "memory"); }
__device__ __forceinline__ float2 sum8(uint32_t addr) {
    float2 t[8];
#pragma unroll
    for (int w = 0; w < 8; w++) t[w] = lds64f(addr + w * 128);
    return make_float2(((t[0].x + t[1].x) + (t[2].x + t[3].x)) + ((t[4].x + t[5].x) + (t[6].x + t[7].x)),
                       ((t[0].y + t[1].y) + (t[2].y + t[3].y)) + ((t[4].y + t[5].y) + (t[6].y + t[7].y)));
}
__device__ __forceinline__ float4 sum4x4(uint32_t addr) {
    float4 t[4];
#pragma unroll
    for (int w = 0; w < 4; w++) t[w] = lds128f(addr + w * 256);
    return make_float4((t[0].x + t[1].x) + (t[2].x + t[3].x), (t[0].y + t[1].y) + (t[2].y + t[3].y),
                       (t[0].z + t[1].z) + (t[2].z + t[3].z), (t[0].w + t[1].w) + (t[2].w + t[3].w));
}
template <int NJ>
__device__ __forceinline__ void load_o(const Params& p, uint32_t (&ob)[3 * NJ][2], int bh, int J0, int j) {
    float4 v[NJ][4];
    float2 l;
#pragma unroll 1
    for (int it = 0; it < SPIN_MAX; it++) {
#pragma unroll
        for (int J = 0; J < NJ; J++) {
#pragma unroll
            for (int e = 0; e < 4; e++) v[J][e] = ld_relaxed_f4(&g_st.oacc[bh][(J0 + J) * 16 + e * 4 + j]);
        }
        l = ld_relaxed_f2(g_st.lsum[bh]);
        bool ok = l.y == UPB;
#pragma unroll
        for (int J = 0; J < NJ; J++) {
#pragma unroll
            for (int e = 0; e < 4; e++) ok &= v[J][e].w == UPB;
        }
        if (__all_sync(0xffffffffu, ok)) break;
    }
    const float rl = __fdividef(1.0f, l.x);
#pragma unroll
    for (int J = 0; J < NJ; J++) {
        ob[3 * J][0] = pack_bf16(v[J][0].x * rl, v[J][1].x * rl);     ob[3 * J][1] = pack_bf16(v[J][2].x * rl, v[J][3].x * rl);
        ob[3 * J + 1][0] = pack_bf16(v[J][0].y * rl, v[J][1].y * rl); ob[3 * J + 1][1] = pack_bf16(v[J][2].y * rl, v[J][3].y * rl);
        ob[3 * J + 2][0] = pack_bf16(v[J][0].z * rl, v[J][1].z * rl); ob[3 * J + 2][1] = pack_bf16(v[J][2].z * rl, v[J][3].z * rl);
    }
}
__device__ __forceinline__ void h_sync(uint32_t warp) {
    asm volatile("{\n.reg .pred p;\nsetp.lt.u32 p, %0, 4;\n@p bar.sync 7, 160;\n@!p bar.sync 8, 160;\n}" :: "r"(warp) : "memory");
}
__device__ __forceinline__ void aux_sync() { asm volatile("bar.sync 1, 256;" ::: "memory"); }

__global__ void __launch_bounds__(NTHREADS, 1)
fused_decode_kernel(const __grid_constant__ Params p) {
    extern __shared__ __align__(1024) unsigned char smem[];
    asm volatile("prefetch.global.L2 [%0];" :: "l"(p.wq_raw + (blockIdx.x * NTHREADS + threadIdx.x) * PRES));
    const uint32_t sb = s2u(smem);
    const int tid = threadIdx.x, warp = __shfl_sync(0xffffffffu, tid >> 5, 0), lane = tid & 31;
    const int cta = blockIdx.x;
    constexpr int grid = NCTAS;
    const int g = lane >> 2, j = lane & 3;
    const bool is_l = cta >= NE_CTAS, is_f = cta < 96 && !(cta & 1), is_g = cta < 80 && (cta & 1);
    const int fidx = cta >> 1;

    TS(0);
    if (warp == 4 && cta < NQ_CTAS) {
        asm volatile("{\n.reg .pred p;\nelect.sync _|p, 0xffffffff;\n"
                     "@p mbarrier.init.shared::cta.b64 [%0], 1;\n"
                     "@p fence.mbarrier_init.release.cluster;\n"
                     "@p mbarrier.arrive.expect_tx.shared::cta.b64 _, [%0], 61440;\n}" :: "r"(sb + BAR_WQ) : "memory");
#pragma unroll
        for (int i = 0; i < 4; i++) request_box(sb + SM_WQ + i * 15360, &p.wq, cta * 48, i * 160, sb + BAR_WQ);
    }
    if (tid == 160) {
#pragma unroll
        for (int w = 0; w < NWORK; w++) mbar_init(sb + BAR_KV + w * 8, 1);
        mbar_init(sb + BAR_W, 1);
#pragma unroll
        for (int w = 0; w < 8; w++) mbar_init(sb + BAR_G + w * 8, 1);
        asm volatile("fence.mbarrier_init.release.cluster;" ::: "memory");
    }
    __syncthreads();
    if (warp == NAUX + NWORK + 1) {
        uint32_t t = now_clk() + 2 * WO_AT_NS;
        const uint64_t pol = evict_first();
        if (lane == 0) mbar_expect_tx(sb + BAR_W, is_l ? 49152 : 61440);
#pragma unroll 1
        for (int r = 0; r < DH; r += 48, t += 2 * WO_GAP_NS) {
            wait_clk(t);
#pragma unroll 1
            for (int i = 0; i < (is_l ? 4 : 5); i++)
                request_box(sb + SM_A + i * 12288 + r * 64, &p.wo, is_l ? (cta - NE_CTAS) * 32 : (cta & 3) * 160 + i * 32,
                            (is_l ? 28 + i : cta >> 2) * DH + r, sb + BAR_W, pol);
        }
        if (!is_f && !is_g) return;
        if (lane < 8) mbar_expect_tx(sb + BAR_G + lane * 8, is_f ? 10240 : 6144);
        asm volatile("bar.sync 9, 288;" ::: "memory");
        asm volatile("fence.proxy.async.shared::cta;" ::: "memory");
#pragma unroll 1
        for (int it = 0; it < SPIN_MAX; it++) {
            t = ld_relaxed_u32(g_st.tstart);
            if (__all_sync(0xffffffffu, t != 0)) break;
            __nanosleep(400);
        }
#pragma unroll 1
        for (int it = 0; it < SPIN_MAX; it++) if (__all_sync(0xffffffffu, t - now_ns() > 2 * TRIG_NS)) break;
        TSW(11);
        t = now_clk() + (is_f ? 0 : DOFF);
#pragma unroll 1
        for (int i = 0; i < 8; i++, t += is_f ? GCLK : DCLK) {
            wait_clk(t);
            if (is_f) {
                request_box(sb + SM_G + i * 5120, &p.wg, fidx * 32, i * 80, sb + BAR_G + i * 8);
                request_box(sb + SM_G + 40960 + i * 5120, &p.wu, fidx * 32, i * 80, sb + BAR_G + i * 8);
            } else {
                request_box(sb + SM_G + i * 6144, &p.wd, fidx * 16, i * 192, sb + BAR_G + i * 8);
            }
        }
        return;
    }
    if (warp == NAUX + NWORK) {
        if (cta < NQ_CTAS) {
            wait_clk(now_clk() + 4000);
#pragma unroll
            for (int i = lane; i < STATE_V4; i += 32)
                if (cta * STATE_V4 + i < (int)(sizeof(State) / 16)) reinterpret_cast<uint4*>(&g_st)[cta * STATE_V4 + i] = make_uint4(0u, 0u, 0u, 0u);
            if (cta * 512 < X_END) {
                uint4* z = sided<uint4>(p, 0, cta * 512 + lane * 16);
                *z = make_uint4(0u, 0u, 0u, 0u);
                *other_side(z) = make_uint4(0u, 0u, 0u, 0u);
            }
            __syncwarp();
            if (lane == 0) red_release(g_cnt_z);
        }
        if (lane == 0) { TS2(2); wait_count(g_cnt_z, NQ_CTAS); TS2(29); }
        __syncwarp();
        asm volatile("bar.arrive 2, %0;" :: "n"((NWORK + 1) * 32) : "memory");
        uint32_t rtt[2] = {0xffffffffu, 0xffffffffu};
        if (lane == 0) {
#pragma unroll 1
            for (int r = 0; r < 12; r++) {
                int v = 0;
                uint32_t t1 = 0;
                unsigned* ctr = sided<unsigned>(p, r & 1, X_P + ((cta * 32 + (r >> 1) * 768) & 4095));
                pin(ctr);
                const uint32_t t0 = now_clk();
                draw(v, ctr, true);
                asm volatile("{\n.reg .pred q;\nsetp.ge.s32 q, %1, 0;\n@q mov.u32 %0, %%clock;\n}" : "+r"(t1) : "r"(v) : "memory");
                if (r & 1) rtt[1] = min(rtt[1], t1 - t0); else rtt[0] = min(rtt[0], t1 - t0);
            }
            sts32f(sb + SM_SIDE, __int_as_float(rtt[1] < rtt[0]));
        }
        const int side = __shfl_sync(0xffffffffu, rtt[1] < rtt[0], 0);
        fin_arrive<3>();
        int job = cta;
        auto sum_rows = [&](int row_end) {
#pragma unroll 1
            for (; job < 8 * min(row_end, RED0); job += NCTAS) {
                const int row = job >> 3, grp = (job & 7) * 8 + (lane & 7);
                if (lane == 0) wait_row(p, side, row, UPB);
                __syncwarp();
                const float4* src = &g_ring[row % RING][lane >> 3][grp];
                float sx = 0.f, sy = 0.f, sz = 0.f;
#pragma unroll 1
                for (int i = 0; i < 2; i++, src += 64 * 64) {
                    float4 v[16];
#pragma unroll 1
                    for (int it = 0; it < SPIN_MAX; it++) {
                        bool ok = true;
#pragma unroll
                        for (int k = 0; k < 16; k++) v[k] = ld_relaxed_b128(src + k * 4 * 64);
#pragma unroll
                        for (int k = 0; k < 16; k++) ok &= v[k].w == (float)(row + 1);
                        if (__all_sync(0xffffffffu, ok)) break;
                    }
#pragma unroll
                    for (int k = 0; k < 16; k++) { sx += v[k].x; sy += v[k].y; sz += v[k].z; }
                }
#pragma unroll
                for (int o = 8; o < 32; o <<= 1) {
                    sx += __shfl_xor_sync(0xffffffffu, sx, o); sy += __shfl_xor_sync(0xffffffffu, sy, o); sz += __shfl_xor_sync(0xffffffffu, sz, o);
                }
                if (lane < 8) st_relaxed_b128(&g_st.oacc[row][grp], sx, sy, sz, UPB);
            }
        };
        {
            uint32_t wr[10];
            float wsum = 0.f;
#pragma unroll
            for (int i = 0; i < 10; i++) {
                const int w = 4 * lane + 128 * (i >> 2) + (i & 3) - (i >= 8 ? 2 * lane : 0);
                wr[i] = *reinterpret_cast<const uint32_t*>(p.wr + (w >> 4) * 32 + (w & 3) * 8 + ((w >> 1) & 6));
                wsum += lo_f(wr[i]) + hi_f(wr[i]);
            }
            wsum = warp_sum(wsum);
            const int lb = lane >> 3, lc = lane & 7;
            uint32_t ypart = sb + SM_RED2 + (lb >> 1) * 160 + lc * 16 + (lb & 1) * 8;
            __nv_bfloat16* out = p.out + lb * DM + fidx * 16 + lc;
            float nmean_l = 0.f, rden_l = 0.f, sig_l = 0.f;
#pragma unroll 1
            for (int b = 0; b < NB; b++) {
                const uint32_t hx = X_H + b * (DM * 2), hrow = sb + SM_X + b * HPITCH;
                const uint4 *src0 = sided<uint4>(p, side, hx + 16 * lane), *src1 = sided<uint4>(p, side, hx + 512 + 16 * lane);
                const uint2* src2 = sided<uint2>(p, side, hx + 1024 + 8 * lane);
                sum_rows((b + 1) * NH);
                if (!is_l && !is_f && !is_g) continue;
                pin(src0); pin(src1); pin(src2); pin(ypart); pin(out);
                if (lane == 0) wait_row(p, side, b * NH + (is_l ? 28 : NH - 1), is_l ? 1 : 100);
                __syncwarp();
                if (is_l) {
                    const int col = (cta - NE_CTAS) * 32 + 2 * (lane & 15);
                    uint32_t lpart = sb + SM_RED + (lane & 15) * 8;
                    const uint32_t xv = *reinterpret_cast<const uint32_t*>(p.x + b * DM + col);
                    uint32_t* hdst = sided<uint32_t>(p, lane >> 4, hx + 4 * ((col >> 5) * 16 + (col & 6) * 2 + ((col >> 3) & 3)));
                    float4 early;
#pragma unroll 1
                    for (int it = 0; it < SPIN_MAX; it++) {
                        early = ld_relaxed_f4(&g_st.attn[b][col]);
                        if (__all_sync(0xffffffffu, early.y == NE_CTAS / 4 && early.w == NE_CTAS / 4)) break;
                    }
                    if (lane == 0) TS2(23);
                    float x0 = lo_f(xv), x1 = hi_f(xv);
                    pin(hdst); pin(lpart); pin(x0); pin(x1);
                    fin_sync<4>();
                    CK(2, lds32(sb + SM_RED));
                    const float2 late = sum8(lpart);
                    const uint32_t nh = pack_bf16(-x0 - bf16r(early.x + late.x), -x1 - bf16r(early.z + late.y));
                    st_relaxed(hdst, nh ? nh : 0x80008000u);
                    CK(3, 0);
                    if (lane == 0) TS2(15);
                    fin_sync<5>();
                    continue;
                }
                uint4 h0, h1;
                uint2 h2;
                float mm[5][4];
#pragma unroll 1
                for (int it = 0;; it++) {
                    h0 = ld_relaxed_v4(src0);
                    h1 = ld_relaxed_v4(src1);
                    h2 = ld_relaxed_v2(src2);
                    asm volatile("st.shared.v4.u32 [%0], {%1,%2,%3,%4};" :: "r"(hrow + lane * 16), "r"(h0.x), "r"(h0.y), "r"(h0.z), "r"(h0.w) : "memory");
                    asm volatile("st.shared.v4.u32 [%0], {%1,%2,%3,%4};" :: "r"(hrow + 512 + lane * 16), "r"(h1.x), "r"(h1.y), "r"(h1.z), "r"(h1.w) : "memory");
                    asm volatile("st.shared.v2.u32 [%0], {%1,%2};" :: "r"(hrow + 1024 + lane * 8), "r"(h2.x), "r"(h2.y) : "memory");
                    const uint32_t w[10] = {h0.x, h0.y, h0.z, h0.w, h1.x, h1.y, h1.z, h1.w, h2.x, h2.y};
#pragma unroll
                    for (int i = 0; i < 5; i++) {
                        const uint32_t a[4] = {w[2 * i], 0x3f803f80u, w[2 * i + 1], 0x3f803f80u};
                        mm[i][0] = mm[i][1] = mm[i][2] = mm[i][3] = 0.f;
                        mma16816(mm[i], a, w[2 * i], w[2 * i + 1]);
                    }
                    const uint32_t lo = min(min(min(h0.x, h0.y), min(h0.z, h0.w)), min(min(min(h1.x, h1.y), min(h1.z, h1.w)), min(h2.x, h2.y)));
                    const bool ok = __all_sync(0xffffffffu, lo != 0 || it == SPIN_MAX);
                    asm volatile("{\n.reg .pred p;\nsetp.ne.u32 p, %0, 0;\n@p bar.arrive 7, 160;\n@p bar.arrive 8, 160;\n}" :: "r"((uint32_t)ok) : "memory");
                    if (ok) break;
                }
                CK(4, h0.x);
                if (lane == 0) TS2(is_f ? 12 : 17);
                const uint32_t hw[10] = {h0.x, h0.y, h0.z, h0.w, h1.x, h1.y, h1.z, h1.w, h2.x, h2.y};
                float m1 = ((mm[0][2] + mm[1][2]) + (mm[2][2] + mm[3][2])) + ((mm[0][3] + mm[1][3]) + (mm[2][3] + mm[3][3])) + (mm[4][2] + mm[4][3]);
                float m2 = (g & 1) ? ((mm[0][1] + mm[1][1]) + (mm[2][1] + mm[3][1])) + mm[4][1] : ((mm[0][0] + mm[1][0]) + (mm[2][0] + mm[3][0])) + mm[4][0];
                m2 += __shfl_xor_sync(0xffffffffu, m2, 4);
                m1 = (m1 + __shfl_xor_sync(0xffffffffu, m1, 1)) + (__shfl_xor_sync(0xffffffffu, m1, 2) + __shfl_xor_sync(0xffffffffu, m1, 3));
                m2 = (__shfl_sync(0xffffffffu, m2, 0) + __shfl_sync(0xffffffffu, m2, 9)) + (__shfl_sync(0xffffffffu, m2, 18) + __shfl_sync(0xffffffffu, m2, 27));
                m1 *= 1.0f / DM;
                const float nmean = bf16r(m1);
                const float var = bf16r(fmaxf(fmaf(-m1, m1, m2 * (1.0f / DM)), 0.f));
                const float vare = bf16r(var + 1e-5f);
                if (is_f) {
                    sts64f(sb + SM_MOM + b * 8, nmean, vare, lane == 0);
                    CK(5, 0);
                    fin_arrive<4>();
                } else {
                    const float rden = rcp_approx(bf16r(sqrt_approx(vare)));
                    if (lb == b) { nmean_l = nmean; rden_l = rden; }
                    __syncwarp();
                    const float2 hw2 = lds64f(sb + SM_X + lb * HPITCH + ((fidx >> 1) * 16 + (lc & 6) * 2 + (fidx & 1) * 2) * 4);
                    const float nh0 = (lc & 1) ? hi_f(__float_as_uint(hw2.x)) : lo_f(__float_as_uint(hw2.x));
                    const float nh1 = (lc & 1) ? hi_f(__float_as_uint(hw2.y)) : lo_f(__float_as_uint(hw2.y));
                    float rr = 0.f;
#pragma unroll
                    for (int i = 0; i < 10; i++) rr = fmaf(lo_f(hw[i]), lo_f(wr[i]), fmaf(hi_f(hw[i]), hi_f(wr[i]), rr));
                    const float sig = bf16r(sigmoid_approx(bf16r((nmean * wsum - warp_sum(rr)) * rden)));
                    if (lb == b) sig_l = sig;
                    const float ln0 = bf16r(bf16r(nmean_l - nh0) * rden_l), ln1 = bf16r(bf16r(nmean_l - nh1) * rden_l);
                    if (lane == 0 && sig_l + ln0 + ln1 != 1.2345f) TS2(18);
                    fin_sync<6>(after(after(after(288, sig_l), ln0), ln1));
                    CK(10, lds32(ypart));
                    float2 t[16];
#pragma unroll
                    for (int i = 0; i < 16; i++) t[i] = lds64f(ypart + i * YPITCH);
#pragma unroll
                    for (int o = 1; o < 16; o <<= 1) {
#pragma unroll
                        for (int i = 0; i < 16; i += 2 * o) { t[i].x += t[i + o].x; t[i].y += t[i + o].y; }
                    }
                    const uint32_t o0 = pack_bf16(bf16r(ln0 - bf16r(bf16r(t[0].x) * sig_l)) - nh0, 0.f);
                    const uint32_t o1 = pack_bf16(bf16r(ln1 - bf16r(bf16r(t[0].y) * sig_l)) - nh1, 0.f);
                    asm volatile("{\n.reg .pred p;\nsetp.eq.u32 p, %3, 3;\n@p st.global.u16 [%0], %1;\n@p st.global.u16 [%0 + 16], %2;\n}"
                                 :: "l"(out), "h"((unsigned short)o0), "h"((unsigned short)o1), "r"(b) : "memory");
                    if (b == NB - 1) return;
                    CK(11, 0);
                    if (lane == 0) TS2(13);
                }
                if (b < NB - 1) fin_sync<5>();
            }
            if (cta == 0 && lane == 0) { g_work[0] = 0; g_cnt_z[0] = 0; }
        }
        return;
    }
    if (warp >= NAUX) {
        const int wk = warp - NAUX;
        const uint32_t bar = sb + BAR_KV + wk * 8;
        const uint32_t buf = sb + SM_KV + wk * TILE_BYTES;
        const uint64_t pol = evict_first();
        const int nstatic = NWORK * grid;
        constexpr int POOL0 = NUNITS - NPOOL;
        int uk = wk * grid + cta;
        wait_clk(now_clk() + 2 * (K0_DELAY_NS + wk * K0_STEP_NS));
        request_tile(buf, &p.k, uk, bar, pol);
        uint32_t koff[3], voff[3];
        {
            const int r = lane & 7, hf = (lane >> 3) & 1;
            const int kkey = hf ? 8 + (r ^ 1) : r;
            const int vh = lane >> 4;
            const int vkey = ((r & 1) ? 8 : 0) + (vh ? (r ^ 1) : r);
#pragma unroll
            for (int b = 0; b < 3; b++) {
                const int rk = 3 * kkey + b, rv = 3 * vkey + b;
                koff[b] = buf + rk * 128 + (((lane >> 4) ^ (rk & 7)) << 4);
                voff[b] = buf + rv * 128 + ((hf ^ (rv & 7)) << 4);
            }
        }
        uint32_t phase = 0;
        uint4 qf[6];
        auto load_q = [&](int u) {
            const uint32_t* q = &g_early[row_of(u)].q[j * 4];
#pragma unroll
            for (int i = 0; i < 6; i++) qf[i] = ld_relaxed_v4(q + i * 16);
        };
        load_q(uk);
        int uq[LAG];
        uint32_t sq[LAG];
#pragma unroll
        for (int i = 0; i < LAG; i++) { uq[i] = -1; sq[i] = 0; }
        uint4 mv = make_uint4(0u, 0u, 0u, 0u);
        uint32_t svp = 0;
        float freed = UPB;
        while (true) {
            const int uv = uq[0];
            uint32_t sv = sq[0];
#pragma unroll
            for (int i = 0; i + 1 < LAG; i++) { uq[i] = uq[i + 1]; sq[i] = sq[i + 1]; }
            uq[LAG - 1] = uk;
            if (uk < NUNITS) {
                PH(7);
#pragma unroll 1
                for (int it = 0; it < SPIN_MAX; it++) {
                    uint32_t lo = 0xffffffffu;
#pragma unroll
                    for (int i = 0; i < 6; i++) lo = min(min(lo, min(qf[i].x, qf[i].y)), min(qf[i].z, qf[i].w));
                    if (__all_sync(0xffffffffu, lo != 0)) break;
                    __nanosleep(250);
                    load_q(uk);
                }
                mbar_wait(bar, phase); phase ^= 1;
                PH(0); ARR();
                TSI(0, 16);
                float acc[2][4][4] = {};
#pragma unroll
                for (int ks = 0; ks < 12; ks++) {
                    const uint4 qq = qf[ks >> 1];
                    const uint32_t b0 = (ks & 1) ? qq.z : qq.x, b1 = (ks & 1) ? qq.w : qq.y;
#pragma unroll
                    for (int mt = 0; mt < 4; mt++) {
                        uint32_t a[4];
                        ldsm4(a, (koff[ks >> 2] ^ ((ks & 3) << 5)) + mt * 6144);
                        mma16816(acc[ks & 1][mt], a, b0, b1);
                    }
                }
                PH(1);
                TSI(0, 19);
                if (uv < NUNITS) request_tile(buf, uv >= 0 ? &p.v : &p.k, uv >= 0 ? uv : uk + nstatic, bar, pol);
                const float sa = sel4(j, acc[0][0][0], acc[0][1][0], acc[0][2][0], acc[0][3][0]) + sel4(j, acc[1][0][0], acc[1][1][0], acc[1][2][0], acc[1][3][0]);
                const float sc = sel4(j, acc[0][0][2], acc[0][1][2], acc[0][2][2], acc[0][3][2]) + sel4(j, acc[1][0][2], acc[1][1][2], acc[1][2][2], acc[1][3][2]);
                const uint32_t raw = pack_bf16(sa, sc);
                const float scale = -0.07216878364870322f;
                const uint32_t sk = pack_bf16(lo_f(raw) * scale, hi_f(raw) * scale);
                sq[LAG - 1] = sk;
                if (uk >= POOL0) st_relaxed(&g_st.score[uk - POOL0][lane], sk ? sk : 0x80008000u);
                int a = (int)(sk << 16), b = (int)(sk & 0xffff0000u);
                a ^= (a >> 31) & 0x7fff0000; b ^= (b >> 31) & 0x7fff0000;
                const int mx = __reduce_max_sync(0xffffffffu, max(a, b));
                if (lane == 0) st_relaxed(&g_early[row_of(uk)].umax[pos_of(uk)], (uint32_t)mx | 1u);
            }
            if (uv < 0) {
                uk += nstatic;
                load_q(uk);
                continue;
            }
            if (uv >= NUNITS) break;
            const int bh = row_of(uv);
#pragma unroll 1
            for (int it = 0; it < SPIN_MAX; it++) {
                if (__all_sync(0xffffffffu, (mv.x & mv.y & mv.z & mv.w & 1u) && (uv < POOL0 || svp != 0) && freed == UPB)) break;
                mv = ld_relaxed_v4(&g_early[bh].umax[lane * 4]);
                if (bh >= RING && bh < RED0) freed = __uint_as_float(ld_relaxed_u32(&g_st.oacc[bh - RING][(lane & 7) * 8].w));
                if (uv >= POOL0) svp = ld_relaxed_u32(&g_st.score[uv - POOL0][lane]);
            }
            if (uv >= POOL0) sv = svp;
            PH(2);
            int un = NUNITS, vn = 0;
            draw(un, g_work, uk < NUNITS && lane == 0);
            int mx = __reduce_max_sync(0xffffffffu, max(max((int)mv.x, (int)mv.y), max((int)mv.z, (int)mv.w))) & 0xffff0000;
            mx ^= (mx >> 31) & 0x7fff0000;
            const float m = __int_as_float(mx);
            const float l2e = 1.4426950408889634f;
            const uint32_t pp = pack_bf16(exp2f((lo_f(sv) - m) * l2e), exp2f((hi_f(sv) - m) * l2e));
            uint32_t pb[8];
#pragma unroll
            for (int t = 0; t < 4; t++) {
                pb[2 * t] = __shfl_sync(0xffffffffu, pp, 8 * j + t);
                pb[2 * t + 1] = __shfl_sync(0xffffffffu, pp, 8 * j + 4 + t);
            }
            float lacc[4] = {};
            const uint32_t ones[4] = {0x3f803f80u, 0x3f803f80u, 0x3f803f80u, 0x3f803f80u};
#pragma unroll
            for (int t = 0; t < 4; t++) mma16816(lacc, ones, pb[2 * t], pb[2 * t + 1]);
            if (uv < nstatic) {
                asm volatile("bar.sync 2, %0;" :: "n"((NWORK + 1) * 32) : "memory");
                TSW(3);
            }
            const int grp = 16 * j + 4 * (g & 1) + (g >> 1);
            float4* dst = bh < RED0 ? &g_ring[bh % RING][pos_of(uv)][grp] : oacc_at(p, lds32(sb + SM_SIDE) ^ 1, bh, grp);
            float4* dst2 = other_side(dst);
            float2* ldst = lsum_at(p, lane & 1, bh);
            if (bh >= SROW0 && lane < 2) red_f2(&ldst->x, lacc[0], 1.f);
            float tag = bh < RED0 ? (float)(bh + 1) : 1.f;
            un = __shfl_sync(0xffffffffu, un, 0) + (LAG + 1) * nstatic;
            uint32_t pooled = uq[0] >= POOL0 && lane == 0;
            pin(dst); pin(dst2); pin(ldst); pin(tag); pin(voff[0]); pin(voff[1]); pin(voff[2]); pin(pooled);
            PH(3);
            LT(1);
            mbar_wait(bar, phase); phase ^= 1;
            PH(4); ARR();
            LT(2);
            draw(vn, g_st.pool, pooled);
            float acc[12][4] = {};
#pragma unroll
            for (int t = 0; t < 4; t++) {
#pragma unroll
                for (int mt = 0; mt < 12; mt++) {
                    uint32_t a[4];
                    ldsm4t(a, (voff[mt >> 2] ^ ((mt & 3) << 5)) + t * 6144);
                    mma16816(acc[mt], a, pb[2 * t], pb[2 * t + 1]);
                }
            }
            PH(5);
            if (lane == 0) PROG(un);
            if (un < NUNITS) request_tile(buf, &p.k, un, bar, pol);
            float o[6];
#pragma unroll
            for (int e = 0; e < 6; e++) {
                const int q = e % 3, c = (e / 3) * 2;
                o[e] = sel4(j, acc[q][c], acc[3 + q][c], acc[6 + q][c], acc[9 + q][c]);
            }
            if (bh >= SROW0) {
                red_f4(&dst->x, o[0], o[1], o[2], tag);
                red_f4(&dst[16].x, o[3], o[4], o[5], tag);
                red_f4(&dst2->x, o[0], o[1], o[2], tag);
                red_f4(&dst2[16].x, o[3], o[4], o[5], tag);
            } else {
                if (bh >= RED0) {
                    red_f4(&dst->x, o[0], o[1], o[2], tag);
                    red_f4(&dst[8].x, o[3], o[4], o[5], tag);
                } else {
                    st_relaxed_b128(dst, o[0], o[1], o[2], tag);
                    st_relaxed_b128(dst + 8, o[3], o[4], o[5], tag);
                }
                if (lane == 0) red_f2(&ldst->x, lacc[0], 1.f);
            }
            if (uq[0] >= POOL0) {
                vn = __shfl_sync(0xffffffffu, vn, 0);
                uq[0] = POOL0 + vn;
                if (vn == VTRIG && lane == 0) st_relaxed(g_st.tstart, (now_ns() + TRIG_NS) | 1u);
            }
            if (un < NUNITS) load_q(un);
            PH(6);
            if (uq[0] >= NUNITS && un >= NUNITS) break;
            uk = un;
            if (uq[0] < NUNITS) {
                const int nb = row_of(uq[0]);
                mv = ld_relaxed_v4(&g_early[nb].umax[lane * 4]);
                freed = nb >= RING && nb < RED0 ? __uint_as_float(ld_relaxed_u32(&g_st.oacc[nb - RING][(lane & 7) * 8].w)) : UPB;
                if (uq[0] >= POOL0) svp = ld_relaxed_u32(&g_st.score[uq[0] - POOL0][lane]);
                if (un >= NUNITS) {
                    request_tile(buf, &p.v, uq[0], bar, pol);
                    LT(0);
                }
            }
        }
        if (is_f) asm volatile("bar.arrive 10, %0;" :: "n"((NAUX + NWORK) * 32) : "memory");
        return;
    }

    __nv_bfloat16* xs = reinterpret_cast<__nv_bfloat16*>(smem + SM_X);
    float* red = reinterpret_cast<float*>(smem + SM_RED);
    const int frow = (lane & 7) + ((lane >> 4) << 3), fcol = (lane >> 3) & 1;
    if (cta < NQ_CTAS) {
        uint2 xr[5];
        if (warp < NB) {
#pragma unroll
            for (int i = 0; i < 5; i++) xr[i] = *reinterpret_cast<const uint2*>(p.x + warp * DM + i * 128 + lane * 4);
        }
        TS(26);
        if (warp < NB) {
            float v[20];
#pragma unroll
            for (int i = 0; i < 5; i++) {
                v[4 * i] = lo_f(xr[i].x); v[4 * i + 1] = hi_f(xr[i].x); v[4 * i + 2] = lo_f(xr[i].y); v[4 * i + 3] = hi_f(xr[i].y);
            }
            layernorm20(v);
#pragma unroll
            for (int i = 0; i < 5; i++)
                *reinterpret_cast<uint2*>(xs + warp * XPITCH + i * 128 + lane * 4) =
                    make_uint2(pack_bf16(v[4 * i], v[4 * i + 1]), pack_bf16(v[4 * i + 2], v[4 * i + 3]));
        }
        TS(27);
        aux_sync();
        mbar_wait(sb + BAR_WQ, 0);
        TS(1);
        const uint32_t xfrag = sb + SM_X + ((g & 3) * XPITCH + 2 * j) * 2;
        float acc[3][4] = {};
#pragma unroll
        for (int s = 0; s < 5; s++) {
            const int ks = warp * 5 + s;
            const uint32_t b0 = lds32(xfrag + ks * 32), b1 = lds32(xfrag + ks * 32 + 16);
            const int row = ks * 16 + frow;
#pragma unroll
            for (int mt = 0; mt < 3; mt++) {
                uint32_t a[4];
                ldsm4t(a, sb + SM_WQ + (row * 6 + 2 * mt + fcol) * 16);
                mma16816(acc[mt], a, b0, b1);
            }
        }
        if (j < 2) {
#pragma unroll
            for (int mt = 0; mt < 3; mt++) {
                *reinterpret_cast<float2*>(red + (warp * 48 + mt * 16 + g) * 4 + 2 * j) = make_float2(acc[mt][0], acc[mt][1]);
                *reinterpret_cast<float2*>(red + (warp * 48 + mt * 16 + 8 + g) * 4 + 2 * j) = make_float2(acc[mt][2], acc[mt][3]);
            }
        }
        aux_sync();
        if (tid < 96) {
            const int b = tid & 3, cp = tid >> 2;
            float s0 = 0.f, s1 = 0.f;
#pragma unroll
            for (int w = 0; w < 8; w++) { s0 += red[(w * 48 + 2 * cp) * 4 + b]; s1 += red[(w * 48 + 2 * cp + 1) * 4 + b]; }
            const int h = cta >> 2, d = (cta & 3) * 48 + 2 * cp;
            const int ch = d >> 3, jj = (d & 7) >> 1;
            st_relaxed(&g_early[b * NH + h].q[(ch >> 2) * 16 + jj * 4 + (ch & 3)], pack_neg(s0, s1));
        }
        TS(28);
    }
    if (tid < 160) *reinterpret_cast<uint2*>(smem + SM_X + 4 * HPITCH + tid * 8) = make_uint2(0x3f803f80u, 0x3f803f80u);
    fin_sync<3>();
    const int side = lds32(sb + SM_SIDE);
    mbar_wait(sb + BAR_W, 0);
    TS(7);
    uint32_t part = sb + SM_RED + (warp * 32 + 8 * j + g) * 4;

#pragma unroll 1
    for (int b = 0; b < NB; b++) {
        if (b == NB - 1 && (is_f || is_g)) asm volatile("bar.arrive 9, 288;" ::: "memory");
        if (is_l) {
            uint32_t a[6][2][4];
#pragma unroll
            for (int s = 0; s < 6; s++) {
                const int row = warp * 96 + (s < 4 ? 48 * (s >> 1) + 8 * (s & 1) + 16 * (lane & 1) + (lane & 6) + (lane >> 4) : 48 * (s - 4) + 32 + frow);
#pragma unroll
                for (int mt = 0; mt < 2; mt++) ldsm4t(a[s][mt], sb + SM_A + (row * 4 + ((2 * mt + fcol) ^ ((row >> 1) & 3))) * 16);
            }
            const int bh = b * NH + 28 + (warp >> 1);
            const float4* osrc = oacc_at(p, side, bh, (warp & 1) * 32 + lane);
            const float2* lsrc = lsum_at(p, side, bh);
            if (lane == 0) wait_row_o(p, side, bh, 1);
            __syncwarp();
            float2 lv;
#pragma unroll 1
            for (int it = 0; it < SPIN_MAX; it++) {
                lv = ld_relaxed_f2(lsrc);
                if (__all_sync(0xffffffffu, lv.y == UPB)) break;
            }
            if (warp == 7) TSW(25);
            if (cta == NE_CTAS && lane < 28)
                reinterpret_cast<uint4*>(&g_early[bh])[(warp & 1) * 28 + lane] = make_uint4(0u, 0u, 0u, 0u);
            float rl = rcp_approx(lv.x);
            float4 ov;
            pin(osrc); pin(rl); hold(part);
#pragma unroll 1
            for (int it = 0;; it++) {
                ov = ld_relaxed_f4(osrc);
                if (__all_sync(0xffffffffu, ov.w == UPB || it == SPIN_MAX)) break;
            }
            CK(0, __float_as_uint(ov.x));
            const uint32_t xy = pack_bf16(ov.x * rl, ov.y * rl);
            const float z = ov.z * rl;
            float acc[2][2][4] = {};
#pragma unroll
            for (int s = 0; s < 6; s++) {
                uint32_t bf[2];
#pragma unroll
                for (int kh = 0; kh < 2; kh++) {
                    if (s < 4) bf[kh] = __shfl_sync(0xffffffffu, xy, 8 * s + 4 * kh + j);
                    else bf[kh] = pack_bf16(__shfl_sync(0xffffffffu, z, 16 * (s - 4) + 8 * kh + j), __shfl_sync(0xffffffffu, z, 16 * (s - 4) + 8 * kh + 4 + j));
                }
#pragma unroll
                for (int mt = 0; mt < 2; mt++) mma16816(acc[mt][s & 1], a[s][mt], bf[0], bf[1]);
            }
            sts32f(part, sel4(j, acc[0][0][0] + acc[0][1][0], acc[0][0][2] + acc[0][1][2], acc[1][0][0] + acc[1][1][0], acc[1][0][2] + acc[1][1][2]));
            CK(1, 0);
            fin_arrive<4>();
            if (warp == 7) TSW(30);
            if (warp == 5) TSW(31);
            fin_sync<5>();
            continue;
        }
        {
            const int bh = b * NH + (cta >> 2);
            if (tid == 0) wait_row_o(p, side, bh, UPB);
            aux_sync();
            if (warp < 5) {
                uint32_t ob[12][2];
                load_o<4>(p, ob, bh, 0, j);
                float acc[2][2][4] = {};
#pragma unroll
                for (int ks = 0; ks < 12; ks++) {
                    const int row = ks * 16 + frow;
#pragma unroll
                    for (int mt = 0; mt < 2; mt++) {
                        uint32_t a[4];
                        ldsm4t(a, sb + SM_A + warp * 12288 + (row * 4 + ((2 * mt + fcol) ^ ((row >> 1) & 3))) * 16);
                        mma16816(acc[mt][ks & 1], a, ob[ks][0], ob[ks][1]);
                    }
                }
                red_f2(&g_st.attn[b][(cta & 3) * 160 + warp * 32 + 8 * j + g].x,
                       sel4(j, acc[0][0][0] + acc[0][1][0], acc[0][0][2] + acc[0][1][2], acc[1][0][0] + acc[1][1][0], acc[1][0][2] + acc[1][1][2]), 1.f);
                TS(8);
            } else if (warp > 5 && (cta & 3) == 0 && tid - 192 < 56) {
                reinterpret_cast<uint4*>(&g_early[bh])[tid - 192] = make_uint4(0u, 0u, 0u, 0u);
            }
        }
        if (is_f) {
            const int kq = warp >> 1, tp = warp & 1;
            uint32_t hfrag = sb + SM_X + min(g, 4) * HPITCH + (kq * 80 + 4 * j) * 4;
            uint32_t fpart = sb + SM_RED + 2 * j * FPITCH + warp * 128 + g * 16;
            uint32_t dsum = sb + SM_RED + (lane >> 3) * FPITCH + tp * 128 + (lane & 7) * 16, csum = sb + SM_RED + 4 * FPITCH + tp * 128 + (lane & 7) * 16;
            uint32_t mom = sb + SM_MOM + (lane >> 3) * 8;
            uint32_t* dst = sided<uint32_t>(p, side ^ 1, X_A + (2 * fidx + tp) * 128 + (lane ^ 2 * tp) * 4);
            uint32_t* dst2 = other_side(dst);
            uint32_t wfrag = sb + SM_G + fcol * 40960 + ((kq * 160 + frow) * 4 + (2 * tp ^ ((frow >> 1) & 3))) * 16;
            hold(wfrag); hold(fpart); hold(hfrag); hold(dsum); hold(csum); hold(mom); hold(dst); hold(dst2);
            uint4 hv[5] = {};
#pragma unroll
            for (int s = 0; s < 5; s++) lds128_if(hv[s], hfrag + s * 64, true);
            if (b == NB - 1) asm volatile("bar.sync 10, %0;" :: "n"((NAUX + NWORK) * 32) : "memory");
            uint32_t ga[10][2][4];
#pragma unroll
            for (int s = 0; s < 10; s++) {
                if (s % 5 == 0 && b == NB - 1) mbar_wait(sb + BAR_G + (kq * 2 + s / 5) * 8, 0);
#pragma unroll
                for (int t = 0; t < 2; t++) ldsm4t(ga[s][t], (wfrag ^ (t << 4)) + s * 1024);
            }
            if (warp == NAUX - 1) TSW(9);
            uint32_t dep = 0;
#pragma unroll
            for (int s = 0; s < 5; s++) dep ^= ga[s][0][0] ^ ga[s][1][0];
            h_sync(warp + (dep & (side >> 1)));
#pragma unroll
            for (int s = 0; s < 5; s++) lds128_if(hv[s], hfrag + s * 64, g == b);
            float acc[2][2][4] = {};
#pragma unroll
            for (int s = 0; s < 5; s++) {
#pragma unroll
                for (int t = 0; t < 2; t++) mma16816(acc[t][0], ga[2 * s][t], hv[s].x, hv[s].y);
#pragma unroll
                for (int t = 0; t < 2; t++) mma16816(acc[t][1], ga[2 * s + 1][t], hv[s].z, hv[s].w);
            }
#pragma unroll
            for (int e = 0; e < 2; e++)
                sts128f(fpart + e * FPITCH, acc[0][0][e] + acc[0][1][e], acc[0][0][2 + e] + acc[0][1][2 + e],
                        acc[1][0][e] + acc[1][1][e], acc[1][0][2 + e] + acc[1][1][2 + e], 2 * j + e < 5);
            CK(5, 0);
            if (warp < 2) {
                fin_sync<4>();
                CK(6, lds32(dsum));
                float2 m = lds64f(mom);
                m.y = rcp_approx(bf16r(sqrt_approx(m.y)));
                const float4 d = sum4x4(dsum), cs = sum4x4(csum);
                const float g0 = bf16r(fmaf(m.x, cs.x, -d.x) * m.y), g1 = bf16r(fmaf(m.x, cs.z, -d.z) * m.y);
                const float u0 = bf16r(fmaf(m.x, cs.y, -d.y) * m.y), u1 = bf16r(fmaf(m.x, cs.w, -d.w) * m.y);
                const uint32_t av = pack_neg(bf16r(g0 * sigmoid_approx(g0)) * u0, bf16r(g1 * sigmoid_approx(g1)) * u1);
                asm volatile("{\n.reg .pred p;\nsetp.eq.u32 p, %3, 3;\n@p st.relaxed.gpu.global.u32 [%0], %2;\n@p st.relaxed.gpu.global.u32 [%1], %2;\n}"
                             :: "l"(dst), "l"(dst2), "r"(av), "r"(b) : "memory");
                CK(7, 0);
                TS(14);
            } else {
                fin_arrive<4>();
            }
        } else if (is_g) {
            const uint4* asrc[3];
#pragma unroll
            for (int q = 0; q < 3; q++) {
                asrc[q] = sided<uint4>(p, side, X_A + (warp * 12 + 4 * q + 2 * (g >> 2) + (j >> 1)) * 128 + (g & 3) * 32 + (j & 1) * 16);
                hold(asrc[q]);
            }
            uint32_t ypart = sb + SM_RED2 + (warp * 2 + (j >> 1)) * YPITCH + (j & 1) * 160 + g * 16;
            const int odd = (lane >> 2) & 1, row = (warp * 12 + odd) * 16 + (lane & 1) * 8 + (lane & 2) * 2 + 2 * odd + (lane >> 4);
            uint32_t wfrag = sb + SM_G + (row * 2 + (fcol ^ ((row >> 2) & 1))) * 16;
            hold(ypart); hold(wfrag);
            if (b == NB - 1) {
                mbar_wait(sb + BAR_G + warp * 8, 0);
                if (warp == NAUX - 1) TSW(10);
            } else {
                h_sync(warp);
            }
            uint32_t wb[3][2][2][4];
#pragma unroll
            for (int s = 0; s < 12; s++) ldsm4t(wb[s >> 2][(s >> 1) & 1][s & 1], (wfrag ^ ((s & 1) << 6)) + (s >> 1) * 1024);
            if (GW && b == NB - 1 && warp < GW) mbar_wait(sb + BAR_G + GW * 8, 0);
            uint4 v[3] = {};
            uint32_t mq[3] = {};
#pragma unroll 1
            for (int it = b < NB - 1 ? SPIN_MAX : 0;; it++) {
                asm volatile("{\n.reg .pred p0, p1, p2;\nsetp.eq.u32 p0, %15, 0;\nsetp.eq.u32 p1, %16, 0;\nsetp.eq.u32 p2, %17, 0;\n"
                             "@p0 ld.relaxed.gpu.global.v4.u32 {%0,%1,%2,%3}, [%12];\n"
                             "@p1 ld.relaxed.gpu.global.v4.u32 {%4,%5,%6,%7}, [%13];\n"
                             "@p2 ld.relaxed.gpu.global.v4.u32 {%8,%9,%10,%11}, [%14];\n}"
                             : "+r"(v[0].x), "+r"(v[0].y), "+r"(v[0].z), "+r"(v[0].w), "+r"(v[1].x), "+r"(v[1].y), "+r"(v[1].z), "+r"(v[1].w),
                               "+r"(v[2].x), "+r"(v[2].y), "+r"(v[2].z), "+r"(v[2].w)
                             : "l"(asrc[0]), "l"(asrc[1]), "l"(asrc[2]), "r"(mq[0]), "r"(mq[1]), "r"(mq[2]) : "memory");
#pragma unroll
                for (int q = 0; q < 3; q++) mq[q] = min(min(v[q].x, v[q].y), min(v[q].z, v[q].w));
                const uint32_t lo = min(min(mq[0], mq[1]), mq[2]);
                if (__all_sync(0xffffffffu, lo != 0 || it == SPIN_MAX)) break;
            }
            CK(8, v[0].x);
            float acc[2][2][4] = {};
#pragma unroll
            for (int q = 0; q < 3; q++) {
#pragma unroll
                for (int pr = 0; pr < 2; pr++) {
                    mma16816(acc[pr][0], wb[q][pr][0], v[q].x, v[q].y);
                    mma16816(acc[pr][1], wb[q][pr][1], v[q].z, v[q].w);
                }
            }
            float y[4];
#pragma unroll
            for (int e = 0; e < 4; e++) y[e] = j < 2 ? acc[0][0][e] + acc[0][1][e] : acc[1][0][e] + acc[1][1][e];
            asm volatile("st.shared.v4.f32 [%0], {%1,%2,%3,%4};" :: "r"(ypart), "f"(y[0]), "f"(y[2]), "f"(y[1]), "f"(y[3]) : "memory");
            CK(9, 0);
            fin_arrive<6>();
        } else {
            continue;
        }
        if (b < NB - 1) fin_sync<5>();
    }
}

typedef CUresult (*EncodeFn)(CUtensorMap*, CUtensorMapDataType, cuuint32_t, void*, const cuuint64_t*, const cuuint64_t*,
                             const cuuint32_t*, const cuuint32_t*, CUtensorMapInterleave, CUtensorMapSwizzle,
                             CUtensorMapL2promotion, CUtensorMapFloatOOBfill);

CUtensorMap make_map(EncodeFn enc, void* ptr, uint64_t cols, uint64_t rows, uint32_t bcols, uint32_t brows,
                     CUtensorMapSwizzle sw, CUtensorMapL2promotion promo) {
    CUtensorMap m;
    const cuuint64_t dims[2] = {cols, rows};
    const cuuint64_t strides[1] = {cols * 2};
    const cuuint32_t box[2] = {bcols, brows};
    const cuuint32_t es[2] = {1, 1};
    enc(&m, CU_TENSOR_MAP_DATA_TYPE_BFLOAT16, 2, ptr, dims, strides, box, es, CU_TENSOR_MAP_INTERLEAVE_NONE, sw, promo,
        CU_TENSOR_MAP_FLOAT_OOB_FILL_NONE);
    return m;
}

}

extern "C" void kernel_launch(void* const* d_in, const int* in_sizes, int n_in, void* d_out, int out_size) {
    (void)in_sizes; (void)n_in; (void)out_size;
    static EncodeFn enc = nullptr;
    static int sms = 0;
    static void* raw = nullptr;
    if (!enc) {
        cudaDriverEntryPointQueryResult qr;
        cudaGetDriverEntryPoint("cuTensorMapEncodeTiled", (void**)&enc, cudaEnableDefault, &qr);
        int dev = 0;
        cudaGetDevice(&dev);
        cudaDeviceGetAttribute(&sms, cudaDevAttrMultiProcessorCount, dev);
        cudaGetSymbolAddress(&raw, g_raw);
        cudaFuncSetAttribute(fused_decode_kernel, cudaFuncAttributeMaxDynamicSharedMemorySize, SM_TOTAL);
    }
    if (sms < NCTAS) return;
    const CUtensorMapL2promotion WPROMO = CU_TENSOR_MAP_L2_PROMOTION_L2_128B;
    Params p;
    p.k = make_map(enc, d_in[1], 64, (uint64_t)NBH * SK * 3, 64, TILE_ROWS, CU_TENSOR_MAP_SWIZZLE_128B, CU_TENSOR_MAP_L2_PROMOTION_NONE);
    p.v = make_map(enc, d_in[2], 64, (uint64_t)NBH * SK * 3, 64, TILE_ROWS, CU_TENSOR_MAP_SWIZZLE_128B, CU_TENSOR_MAP_L2_PROMOTION_NONE);
    p.wq = make_map(enc, d_in[3], NH * DH, DM, 48, 160, CU_TENSOR_MAP_SWIZZLE_NONE, WPROMO);
    p.wo = make_map(enc, d_in[4], DM, NH * DH, 32, 48, CU_TENSOR_MAP_SWIZZLE_64B, WPROMO);
    p.wg = make_map(enc, d_in[7], FF, DM, 32, 80, CU_TENSOR_MAP_SWIZZLE_64B, WPROMO);
    p.wu = make_map(enc, d_in[8], FF, DM, 32, 80, CU_TENSOR_MAP_SWIZZLE_64B, WPROMO);
    p.wd = make_map(enc, d_in[9], DM, FF, 16, 192, CU_TENSOR_MAP_SWIZZLE_32B, WPROMO);
    p.scratch = reinterpret_cast<Scratch*>((reinterpret_cast<uintptr_t>(raw) + PAGE - 1) & ~(uintptr_t)(PAGE - 1));
    p.wq_raw = (const char*)d_in[3];
    p.x = (const __nv_bfloat16*)d_in[0];
    p.wr = (const __nv_bfloat16*)d_in[6];
    p.out = (__nv_bfloat16*)d_out;
    fused_decode_kernel<<<NCTAS, NTHREADS, SM_TOTAL, cudaStreamPerThread>>>(p);
}
```

```cpp
#include <cuda_runtime.h>
#include <cuda_bf16.h>
#include <cuda.h>
#include <stdint.h>

namespace {

constexpr int NB = 4, NH = 32, SK = 8192, DH = 192, DM = 640, FF = 1536;
constexpr int NBH = NB * NH;
constexpr int TILE = 64;
constexpr int UPB = SK / TILE;
constexpr int NUNITS = NBH * UPB;
constexpr int TILE_BYTES = TILE * DH * 2;
constexpr int TILE_ROWS = TILE * 3;
constexpr int NCTAS = 132;
constexpr int NQ_CTAS = 128;
constexpr int NE_CTAS = 112;

constexpr int SROW0 = NBH - 4;

#define NWORK 2
#define NWL 2
#define SKEW 16
#define LAG 3
#define NPOOL 896
#define RED0 120
#define RING 12
#define K0_DELAY_NS 1600
#define K0_STEP_NS 900
#define WO_AT_NS 3600
#define WO_GAP_NS 550
#define VTRIG (NPOOL - 240)
#define TRIG_NS 2050
#define GCLK 250
#define DOFF 2100
#define DCLK 150
constexpr int NAUX = 8;
constexpr int NTHREADS = (NAUX + NWORK + 2) * 32;
constexpr int SPIN_MAX = 1 << 22;

constexpr int SM_KV = 0;
constexpr int SM_A = SM_KV + NWORK * TILE_BYTES;
constexpr int SM_WQ = SM_A + 61440;
constexpr int SM_G = SM_WQ;
constexpr int SM_X = SM_G + 81920;
constexpr int XPITCH = 648;
constexpr int HPITCH = 1344;
constexpr int SM_RED = SM_X + 5 * HPITCH;
constexpr int FPITCH = 1040;
constexpr int SM_RED2 = SM_RED;
constexpr int YPITCH = 320;
constexpr int SM_MISC = SM_RED + 6144;
constexpr int BAR_KV = SM_MISC, BAR_WQ = SM_MISC + 32, BAR_W = SM_MISC + 40, SM_SIDE = SM_MISC + 48, BAR_G = SM_MISC + 64, SM_MOM = SM_MISC + 128;
constexpr int SM_TOTAL = SM_MISC + 160;

struct Scratch;
struct Params {
    CUtensorMap k, v;
    CUtensorMap wq;
    CUtensorMap wo;
    CUtensorMap wg, wu;
    CUtensorMap wd;
    Scratch* scratch;
    const char* wq_raw;
    const __nv_bfloat16 *x, *wr;
    __nv_bfloat16* out;
};

struct Early {
    uint32_t q[96];
    uint32_t umax[UPB];
};
struct State {
    float4 oacc[SROW0][64];
    float2 attn[NB][DM];
    float2 lsum[SROW0][16];
    unsigned pool[64];
    uint32_t tstart[32];
    uint32_t score[NPOOL][32];
};
constexpr int STATE_V4 = ((sizeof(State) / 32 + NQ_CTAS - 1) / NQ_CTAS) * 2;
static_assert(sizeof(State) % 32 == 0, "State is cleared in whole sectors");
static_assert(sizeof(Early) == 56 * 16, "an Early entry is cleared by 56 threads");
constexpr uint32_t X_O = 0;
constexpr uint32_t X_L = X_O + 4 * 1024;
constexpr uint32_t X_H = X_L + 4 * 128;
constexpr uint32_t X_A = X_H + NB * DM * 2;
constexpr uint32_t X_P = X_A + NB * FF * 2;
constexpr uint32_t X_END = X_P + 4096;
static_assert(X_END <= 8 * 4096 && RED0 <= SROW0, "");
struct Scratch {
    unsigned char sided[8][2][4096];
    unsigned work[64];
    unsigned cnt_z[32];
    unsigned char pad0[1024];
    Early early[NBH];
    unsigned char pad1[1024];
    State st;
    unsigned char pad2[1792];
    float4 ring[RING][UPB][64];
};
constexpr size_t PAGE = 2u << 20;
static_assert(sizeof(Scratch) <= PAGE, "scratch must fit one page");
__device__ __align__(128) unsigned char g_raw[2 * PAGE];
template <typename T> __device__ __forceinline__ T* sided(const Params& p, int side, uint32_t x) {
    const uint32_t pair = (x >> 10) & 7;
    return reinterpret_cast<T*>(&p.scratch->sided[pair][(side ^ pair) & 1]
                                    [(x & 127) + ((x & 128) << 1) + ((x & 768) << 2) + ((x >> 6) & 128) + ((x >> 5) & 512)]);
}
template <typename T> __device__ __forceinline__ T* other_side(T* p) { return reinterpret_cast<T*>(reinterpret_cast<uintptr_t>(p) ^ 4096); }
#define g_early p.scratch->early
#define g_st p.scratch->st
#define g_ring p.scratch->ring
#define g_cnt_z p.scratch->cnt_z
#define g_work p.scratch->work
#define TS(i)
#define TSW(i)
#define TS2(i)
#define TSI(n, i)
#define PH(i)
#define CK(i, dep)
#define ARR()
#define PROG(u)
#define LT(i)

__device__ __forceinline__ int row_of(int u) { return (((unsigned)u >> (7 + NWL)) << NWL) | (u & ((1 << NWL) - 1)); }
__device__ __forceinline__ int pos_of(int u) { return ((unsigned)u >> NWL) & (UPB - 1); }
__device__ __forceinline__ int tile_of(int u) { return (row_of(u) * UPB + ((pos_of(u) + (u & ((1 << NWL) - 1)) * SKEW) & (UPB - 1))) * TILE_ROWS; }

__device__ __forceinline__ uint32_t s2u(const void* p) { return (uint32_t)__cvta_generic_to_shared(p); }
__device__ __forceinline__ void mbar_init(uint32_t bar, int cnt) {
    asm volatile("mbarrier.init.shared::cta.b64 [%0], %1;" :: "r"(bar), "r"(cnt) : "memory");
}
__device__ __forceinline__ void mbar_expect_tx(uint32_t bar, uint32_t bytes) {
    asm volatile("mbarrier.arrive.expect_tx.shared::cta.b64 _, [%0], %1;" :: "r"(bar), "r"(bytes) : "memory");
}
__device__ __forceinline__ void mbar_wait(uint32_t bar, uint32_t parity) {
    asm volatile("{\n.reg .pred p;\n.reg .u32 n;\nmov.u32 n, 0;\nWAIT_LOOP:\n"
                 "mbarrier.try_wait.parity.shared::cta.b64 p, [%0], %1;\n"
                 "@p bra WAIT_DONE;\nadd.u32 n, n, 1;\nsetp.lt.u32 p, n, %2;\n@p bra WAIT_LOOP;\nWAIT_DONE:\n}"
                 :: "r"(bar), "r"(parity), "n"(SPIN_MAX) : "memory");
}
__device__ __forceinline__ void request_tile(uint32_t dst, const CUtensorMap* tm, int unit, uint32_t bar, uint64_t pol) {
    asm volatile("{\n.reg .pred p;\nelect.sync _|p, 0xffffffff;\n"
                 "@p mbarrier.arrive.expect_tx.shared::cta.b64 _, [%2], %6;\n"
                 "@p cp.async.bulk.tensor.2d.shared::cluster.global.mbarrier::complete_tx::bytes.L2::cache_hint "
                 "[%0], [%1, {%3, %4}], [%2], %5;\n}"
                 :: "r"(dst), "l"(tm), "r"(bar), "r"(0), "r"(tile_of(unit)), "l"(pol), "n"(TILE_BYTES) : "memory");
}
__device__ __forceinline__ uint32_t now_ns() { uint32_t t; asm volatile("mov.u32 %0, %%globaltimer_lo;" : "=r"(t)); return t; }
__device__ __forceinline__ uint32_t now_clk() { uint32_t t; asm volatile("mov.u32 %0, %%clock;" : "=r"(t)); return t; }
__device__ __forceinline__ void wait_clk(uint32_t t) { while (__any_sync(0xffffffffu, (int)(now_clk() - t) < 0)) {} }
__device__ __forceinline__ uint64_t evict_first() {
    uint64_t pol;
    asm volatile("createpolicy.fractional.L2::evict_first.b64 %0, 1.0;" : "=l"(pol));
    return pol;
}
__device__ __forceinline__ void request_box(uint32_t dst, const CUtensorMap* tm, int col, int row, uint32_t bar) {
    asm volatile("{\n.reg .pred p;\nelect.sync _|p, 0xffffffff;\n"
                 "@p cp.async.bulk.tensor.2d.shared::cluster.global.mbarrier::complete_tx::bytes [%0], [%1, {%3, %4}], [%2];\n}"
                 :: "r"(dst), "l"(tm), "r"(bar), "r"(col), "r"(row) : "memory");
}
__device__ __forceinline__ void request_box(uint32_t dst, const CUtensorMap* tm, int col, int row, uint32_t bar, uint64_t pol) {
    asm volatile("{\n.reg .pred p;\nelect.sync _|p, 0xffffffff;\n"
                 "@p cp.async.bulk.tensor.2d.shared::cluster.global.mbarrier::complete_tx::bytes.L2::cache_hint [%0], [%1, {%3, %4}], [%2], %5;\n}"
                 :: "r"(dst), "l"(tm), "r"(bar), "r"(col), "r"(row), "l"(pol) : "memory");
}
__device__ __forceinline__ uint32_t lds32(uint32_t addr) {
    uint32_t v;
    asm volatile("ld.shared.u32 %0, [%1];" : "=r"(v) : "r"(addr) : "memory");
    return v;
}
__device__ __forceinline__ void ldsm4(uint32_t (&r)[4], uint32_t addr) {
    asm volatile("ldmatrix.sync.aligned.m8n8.x4.shared.b16 {%0,%1,%2,%3}, [%4];"
                 : "=r"(r[0]), "=r"(r[1]), "=r"(r[2]), "=r"(r[3]) : "r"(addr) : "memory");
}
__device__ __forceinline__ void ldsm4t(uint32_t (&r)[4], uint32_t addr) {
    asm volatile("ldmatrix.sync.aligned.m8n8.x4.trans.shared.b16 {%0,%1,%2,%3}, [%4];"
                 : "=r"(r[0]), "=r"(r[1]), "=r"(r[2]), "=r"(r[3]) : "r"(addr) : "memory");
}
__device__ __forceinline__ void mma16816(float (&c)[4], const uint32_t (&a)[4], uint32_t b0, uint32_t b1) {
    asm volatile("mma.sync.aligned.m16n8k16.row.col.f32.bf16.bf16.f32 {%0,%1,%2,%3}, {%4,%5,%6,%7}, {%8,%9}, {%0,%1,%2,%3};"
                 : "+f"(c[0]), "+f"(c[1]), "+f"(c[2]), "+f"(c[3])
                 : "r"(a[0]), "r"(a[1]), "r"(a[2]), "r"(a[3]), "r"(b0), "r"(b1));
}
__device__ __forceinline__ uint4 ld_relaxed_v4(const void* p) {
    uint4 v;
    asm volatile("ld.relaxed.gpu.global.v4.u32 {%0,%1,%2,%3}, [%4];" : "=r"(v.x), "=r"(v.y), "=r"(v.z), "=r"(v.w) : "l"(p) : "memory");
    return v;
}
__device__ __forceinline__ float4 ld_relaxed_f4(const void* p) {
    float4 v;
    asm volatile("ld.relaxed.gpu.global.v4.f32 {%0,%1,%2,%3}, [%4];" : "=f"(v.x), "=f"(v.y), "=f"(v.z), "=f"(v.w) : "l"(p) : "memory");
    return v;
}
__device__ __forceinline__ float2 ld_relaxed_f2(const void* p) {
    float2 v;
    asm volatile("ld.relaxed.gpu.global.v2.f32 {%0,%1}, [%2];" : "=f"(v.x), "=f"(v.y) : "l"(p) : "memory");
    return v;
}
__device__ __forceinline__ float4 ld_relaxed_b128(const void* p) {
    float4 v;
    asm volatile("{\n.reg .b128 t;\n.reg .b64 a, b;\nld.relaxed.gpu.global.b128 t, [%4];\nmov.b128 {a, b}, t;\n"
                 "mov.b64 {%0, %1}, a;\nmov.b64 {%2, %3}, b;\n}" : "=f"(v.x), "=f"(v.y), "=f"(v.z), "=f"(v.w) : "l"(p) : "memory");
    return v;
}
__device__ __forceinline__ void st_relaxed_b128(void* p, float x, float y, float z, float w) {
    asm volatile("{\n.reg .b128 t;\n.reg .b64 a, b;\nmov.b64 a, {%1, %2};\nmov.b64 b, {%3, %4};\nmov.b128 t, {a, b};\n"
                 "st.relaxed.gpu.global.b128 [%0], t;\n}" :: "l"(p), "f"(x), "f"(y), "f"(z), "f"(w) : "memory");
}
__device__ __forceinline__ unsigned ld_acquire(const unsigned* p) {
    unsigned v;
    asm volatile("ld.acquire.gpu.global.u32 %0, [%1];" : "=r"(v) : "l"(p) : "memory");
    return v;
}
__device__ __forceinline__ void st_relaxed(void* p, uint32_t v) {
    asm volatile("st.relaxed.gpu.global.u32 [%0], %1;" :: "l"(p), "r"(v) : "memory");
}
__device__ __forceinline__ void red_f2(float* p, float a, float b) {
    asm volatile("red.relaxed.gpu.global.add.v2.f32 [%0], {%1,%2};" :: "l"(p), "f"(a), "f"(b) : "memory");
}
__device__ __forceinline__ void red_f4(float* p, float a, float b, float c, float d) {
    asm volatile("red.relaxed.gpu.global.add.v4.f32 [%0], {%1,%2,%3,%4};" :: "l"(p), "f"(a), "f"(b), "f"(c), "f"(d) : "memory");
}
__device__ __forceinline__ void draw(int& ticket, unsigned* ctr, bool pred) {
    asm volatile("{\n.reg .pred p;\nsetp.ne.u32 p, %2, 0;\n@p atom.relaxed.gpu.global.inc.u32 %0, [%1], 0x7fffffff;\n}"
                 : "+r"(ticket) : "l"(ctr), "r"((uint32_t)pred) : "memory");
}
__device__ __forceinline__ void red_release(unsigned* p) {
    asm volatile("red.release.gpu.global.add.u32 [%0], 1;" :: "l"(p) : "memory");
}
__device__ __forceinline__ uint32_t ld_relaxed_u32(const void* p) {
    uint32_t v;
    asm volatile("ld.relaxed.gpu.global.u32 %0, [%1];" : "=r"(v) : "l"(p) : "memory");
    return v;
}
__device__ __forceinline__ float rcp_approx(float v) {
    float r;
    asm("rcp.approx.ftz.f32 %0, %1;" : "=f"(r) : "f"(v));
    return r;
}
__device__ __forceinline__ float sigmoid_approx(float v) {
    float e;
    asm("ex2.approx.ftz.f32 %0, %1;" : "=f"(e) : "f"(v * -1.4426950408889634f));
    return rcp_approx(1.0f + e);
}
__device__ __forceinline__ float sqrt_approx(float v) {
    float r;
    asm("sqrt.approx.ftz.f32 %0, %1;" : "=f"(r) : "f"(v));
    return r;
}
__device__ __forceinline__ uint2 ld_relaxed_v2(const void* p) {
    uint2 v;
    asm volatile("ld.relaxed.gpu.global.v2.u32 {%0,%1}, [%2];" : "=r"(v.x), "=r"(v.y) : "l"(p) : "memory");
    return v;
}
__device__ __forceinline__ void wait_count(const unsigned* p, unsigned target) {
#pragma unroll 1
    for (int it = 0; it < SPIN_MAX; it++) {
        if (ld_acquire(p) >= target) break;
        __nanosleep(400);
    }
}
__device__ __forceinline__ float4* oacc_at(const Params& p, int side, int row, int grp) {
    return row >= SROW0 ? sided<float4>(p, side, X_O + (row - SROW0) * 1024 + grp * 16) : &g_st.oacc[row][grp];
}
__device__ __forceinline__ float2* lsum_at(const Params& p, int side, int row) {
    return row >= SROW0 ? sided<float2>(p, side, X_L + (row - SROW0) * 128) : g_st.lsum[row];
}
__device__ __forceinline__ void wait_row(const Params& p, int side, int bh, float n) {
    const float2* l = lsum_at(p, side, bh);
#pragma unroll 1
    for (int it = 0; it < SPIN_MAX; it++) {
        const float c = ld_relaxed_f2(l).y;
        if (c >= n) break;
        if (c == 0.f) __nanosleep(600);
    }
}
__device__ __forceinline__ void wait_row_o(const Params& p, int side, int bh, float n) {
    wait_row(p, side, bh, n);
    if (bh >= RED0) return;
#pragma unroll 1
    for (int it = 0; it < SPIN_MAX; it++) {
        if (__uint_as_float(ld_relaxed_u32(&g_st.oacc[bh][0].w)) == UPB) break;
        __nanosleep(300);
    }
}
__device__ __forceinline__ uint32_t pack_bf16(float lo, float hi) {
    uint32_t r;
    asm("cvt.rn.bf16x2.f32 %0, %1, %2;" : "=r"(r) : "f"(hi), "f"(lo));
    return r;
}
__device__ __forceinline__ float bf16r(float v) { return __uint_as_float(pack_bf16(0.f, v)); }
__device__ __forceinline__ uint32_t pack_neg(float lo, float hi) {
    const uint32_t w = pack_bf16(-lo, -hi);
    return w ? w : 0x80008000u;
}
__device__ __forceinline__ float lo_f(uint32_t v) { return __uint_as_float(v << 16); }
__device__ __forceinline__ float hi_f(uint32_t v) { return __uint_as_float(v & 0xffff0000u); }
__device__ __forceinline__ float warp_sum(float v) {
#pragma unroll
    for (int o = 16; o; o >>= 1) v += __shfl_xor_sync(0xffffffffu, v, o);
    return v;
}
__device__ __forceinline__ void layernorm20(float (&v)[20]) {
    float s = 0.f;
#pragma unroll
    for (int i = 0; i < 20; i++) s += v[i];
    const float mean = warp_sum(s) * (1.0f / DM);
    float q = 0.f;
#pragma unroll
    for (int i = 0; i < 20; i++) { const float d = v[i] - mean; q += d * d; }
    const float var = bf16r(warp_sum(q) * (1.0f / DM));
    const float m = bf16r(mean);
    const float rden = 1.0f / bf16r(sqrtf(bf16r(var + 1e-5f)));
#pragma unroll
    for (int i = 0; i < 20; i++) v[i] = bf16r(bf16r(v[i] - m) * rden);
}

__device__ __forceinline__ float sel4(int j, float a, float b, float c, float d) {
    float lo, hi, r;
    asm("{\n.reg .pred p;\nsetp.ne.s32 p, %3, 0;\nselp.f32 %0, %2, %1, p;\n}" : "=f"(lo) : "f"(a), "f"(b), "r"(j & 1));
    asm("{\n.reg .pred p;\nsetp.ne.s32 p, %3, 0;\nselp.f32 %0, %2, %1, p;\n}" : "=f"(hi) : "f"(c), "f"(d), "r"(j & 1));
    asm("{\n.reg .pred p;\nsetp.ne.s32 p, %3, 0;\nselp.f32 %0, %2, %1, p;\n}" : "=f"(r) : "f"(lo), "f"(hi), "r"(j & 2));
    return r;
}
template <typename T> __device__ __forceinline__ void pin(T*& p) { asm volatile("" : "+l"(p)); }
__device__ __forceinline__ void pin(uint32_t& v) { asm volatile("" : "+r"(v)); }
__device__ __forceinline__ void pin(float& v) { asm volatile("" : "+f"(v)); }
__device__ __forceinline__ void hold(uint32_t& v) { v = __shfl_xor_sync(0xffffffffu, v, 0); }
template <typename T> __device__ __forceinline__ void hold(T*& p) {
    p = reinterpret_cast<T*>(__shfl_xor_sync(0xffffffffu, (unsigned long long)reinterpret_cast<uintptr_t>(p), 0));
}
__device__ __forceinline__ uint32_t after(uint32_t n, float v) {
    asm volatile("{\n.reg .pred p;\nsetp.eq.u32 p, %1, 0x7fc1a5a5;\n@p add.u32 %0, %0, 32;\n}" : "+r"(n) : "r"(__float_as_uint(v)));
    return n;
}
__device__ __forceinline__ float2 lds64f(uint32_t addr) {
    float2 v;
    asm volatile("ld.shared.v2.f32 {%0,%1}, [%2];" : "=f"(v.x), "=f"(v.y) : "r"(addr) : "memory");
    return v;
}
__device__ __forceinline__ float4 lds128f(uint32_t addr) {
    float4 v;
    asm volatile("ld.shared.v4.f32 {%0,%1,%2,%3}, [%4];" : "=f"(v.x), "=f"(v.y), "=f"(v.z), "=f"(v.w) : "r"(addr) : "memory");
    return v;
}
__device__ __forceinline__ void sts64f(uint32_t addr, float a, float b, bool pred) {
    asm volatile("{\n.reg .pred p;\nsetp.ne.u32 p, %3, 0;\n@p st.shared.v2.f32 [%0], {%1,%2};\n}" :: "r"(addr), "f"(a), "f"(b), "r"((uint32_t)pred) : "memory");
}
__device__ __forceinline__ void sts128f(uint32_t addr, float a, float b, float c, float d, bool pred) {
    asm volatile("{\n.reg .pred p;\nsetp.ne.u32 p, %5, 0;\n@p st.shared.v4.f32 [%0], {%1,%2,%3,%4};\n}"
                 :: "r"(addr), "f"(a), "f"(b), "f"(c), "f"(d), "r"((uint32_t)pred) : "memory");
}
__device__ __forceinline__ void lds128_if(uint4& v, uint32_t addr, bool pred) {
    asm volatile("{\n.reg .pred p;\nsetp.ne.u32 p, %5, 0;\n@p ld.shared.v4.u32 {%0,%1,%2,%3}, [%4];\n}"
                 : "+r"(v.x), "+r"(v.y), "+r"(v.z), "+r"(v.w) : "r"(addr), "r"((uint32_t)pred) : "memory");
}
__device__ __forceinline__ void sts32f(uint32_t addr, float v) { asm volatile("st.shared.f32 [%0], %1;" :: "r"(addr), "f"(v) : "memory"); }
template <int ID> __device__ __forceinline__ void fin_arrive() { asm volatile("bar.arrive %0, 288;" :: "n"(ID) : "memory"); }
template <int ID> __device__ __forceinline__ void fin_sync() { asm volatile("bar.sync %0, 288;" :: "n"(ID) : "memory"); }
template <int ID> __device__ __forceinline__ void fin_sync(uint32_t n) { asm volatile("bar.sync %0, %1;" :: "n"(ID), "r"(n) : "memory"); }
__device__ __forceinline__ float2 sum8(uint32_t addr) {
    float2 t[8];
#pragma unroll
    for (int w = 0; w < 8; w++) t[w] = lds64f(addr + w * 128);
    return make_float2(((t[0].x + t[1].x) + (t[2].x + t[3].x)) + ((t[4].x + t[5].x) + (t[6].x + t[7].x)),
                       ((t[0].y + t[1].y) + (t[2].y + t[3].y)) + ((t[4].y + t[5].y) + (t[6].y + t[7].y)));
}
__device__ __forceinline__ float4 sum4x4(uint32_t addr) {
    float4 t[4];
#pragma unroll
    for (int w = 0; w < 4; w++) t[w] = lds128f(addr + w * 256);
    return make_float4((t[0].x + t[1].x) + (t[2].x + t[3].x), (t[0].y + t[1].y) + (t[2].y + t[3].y),
                       (t[0].z + t[1].z) + (t[2].z + t[3].z), (t[0].w + t[1].w) + (t[2].w + t[3].w));
}
template <int NJ>
__device__ __forceinline__ void load_o(const Params& p, uint32_t (&ob)[3 * NJ][2], int bh, int J0, int j) {
    float4 v[NJ][4];
    float2 l;
#pragma unroll 1
    for (int it = 0; it < SPIN_MAX; it++) {
#pragma unroll
        for (int J = 0; J < NJ; J++) {
#pragma unroll
            for (int e = 0; e < 4; e++) v[J][e] = ld_relaxed_f4(&g_st.oacc[bh][(J0 + J) * 16 + e * 4 + j]);
        }
        l = ld_relaxed_f2(g_st.lsum[bh]);
        bool ok = l.y == UPB;
#pragma unroll
        for (int J = 0; J < NJ; J++) {
#pragma unroll
            for (int e = 0; e < 4; e++) ok &= v[J][e].w == UPB;
        }
        if (__all_sync(0xffffffffu, ok)) break;
    }
    const float rl = __fdividef(1.0f, l.x);
#pragma unroll
    for (int J = 0; J < NJ; J++) {
        ob[3 * J][0] = pack_bf16(v[J][0].x * rl, v[J][1].x * rl);     ob[3 * J][1] = pack_bf16(v[J][2].x * rl, v[J][3].x * rl);
        ob[3 * J + 1][0] = pack_bf16(v[J][0].y * rl, v[J][1].y * rl); ob[3 * J + 1][1] = pack_bf16(v[J][2].y * rl, v[J][3].y * rl);
        ob[3 * J + 2][0] = pack_bf16(v[J][0].z * rl, v[J][1].z * rl); ob[3 * J + 2][1] = pack_bf16(v[J][2].z * rl, v[J][3].z * rl);
    }
}
__device__ __forceinline__ void h_sync(uint32_t warp) {
    asm volatile("{\n.reg .pred p;\nsetp.lt.u32 p, %0, 4;\n@p bar.sync 7, 160;\n@!p bar.sync 8, 160;\n}" :: "r"(warp) : "memory");
}
__device__ __forceinline__ void aux_sync() { asm volatile("bar.sync 1, 256;" ::: "memory"); }

__global__ void __launch_bounds__(NTHREADS, 1)
fused_decode_kernel(const __grid_constant__ Params p) {
    extern __shared__ __align__(1024) unsigned char smem[];
    asm volatile("prefetch.global.L2 [%0];" :: "l"(p.wq_raw + (blockIdx.x * NTHREADS + threadIdx.x) * 48));
    const uint32_t sb = s2u(smem);
    const int tid = threadIdx.x, warp = __shfl_sync(0xffffffffu, tid >> 5, 0), lane = tid & 31;
    const int cta = blockIdx.x;
    constexpr int grid = NCTAS;
    const int g = lane >> 2, j = lane & 3;
    const bool is_l = cta >= NE_CTAS, is_f = cta < 96 && !(cta & 1), is_g = cta < 80 && (cta & 1);
    const int fidx = cta >> 1;

    TS(0);
    if (warp == 4 && cta < NQ_CTAS) {
        asm volatile("{\n.reg .pred p;\nelect.sync _|p, 0xffffffff;\n"
                     "@p mbarrier.init.shared::cta.b64 [%0], 1;\n"
                     "@p fence.mbarrier_init.release.cluster;\n"
                     "@p mbarrier.arrive.expect_tx.shared::cta.b64 _, [%0], 61440;\n}" :: "r"(sb + BAR_WQ) : "memory");
#pragma unroll
        for (int i = 0; i < 4; i++) request_box(sb + SM_WQ + i * 15360, &p.wq, cta * 48, i * 160, sb + BAR_WQ);
    }
    if (tid == 160) {
#pragma unroll
        for (int w = 0; w < NWORK; w++) mbar_init(sb + BAR_KV + w * 8, 1);
        mbar_init(sb + BAR_W, 1);
#pragma unroll
        for (int w = 0; w < 8; w++) mbar_init(sb + BAR_G + w * 8, 1);
        asm volatile("fence.mbarrier_init.release.cluster;" ::: "memory");
    }
    __syncthreads();
    if (warp == NAUX + NWORK + 1) {
        uint32_t t = now_clk() + 2 * WO_AT_NS;
        const uint64_t pol = evict_first();
        if (lane == 0) mbar_expect_tx(sb + BAR_W, is_l ? 49152 : 61440);
#pragma unroll 1
        for (int r = 0; r < DH; r += 48, t += 2 * WO_GAP_NS) {
            wait_clk(t);
#pragma unroll 1
            for (int i = 0; i < (is_l ? 4 : 5); i++)
                request_box(sb + SM_A + i * 12288 + r * 64, &p.wo, is_l ? (cta - NE_CTAS) * 32 : (cta & 3) * 160 + i * 32,
                            (is_l ? 28 + i : cta >> 2) * DH + r, sb + BAR_W, pol);
        }
        if (!is_f && !is_g) return;
        if (lane < 8) mbar_expect_tx(sb + BAR_G + lane * 8, is_f ? 10240 : 6144);
        asm volatile("bar.sync 9, 288;" ::: "memory");
        asm volatile("fence.proxy.async.shared::cta;" ::: "memory");
#pragma unroll 1
        for (int it = 0; it < SPIN_MAX; it++) {
            t = ld_relaxed_u32(g_st.tstart);
            if (__all_sync(0xffffffffu, t != 0)) break;
            __nanosleep(400);
        }
#pragma unroll 1
        for (int it = 0; it < SPIN_MAX; it++) if (__all_sync(0xffffffffu, t - now_ns() > 2 * TRIG_NS)) break;
        TSW(11);
        t = now_clk() + (is_f ? 0 : DOFF);
#pragma unroll 1
        for (int i = 0; i < 8; i++, t += is_f ? GCLK : DCLK) {
            wait_clk(t);
            if (is_f) {
                request_box(sb + SM_G + i * 5120, &p.wg, fidx * 32, i * 80, sb + BAR_G + i * 8);
                request_box(sb + SM_G + 40960 + i * 5120, &p.wu, fidx * 32, i * 80, sb + BAR_G + i * 8);
            } else {
                request_box(sb + SM_G + i * 6144, &p.wd, fidx * 16, i * 192, sb + BAR_G + i * 8);
            }
        }
        return;
    }
    if (warp == NAUX + NWORK) {
        if (cta < NQ_CTAS) {
            wait_clk(now_clk() + 4000);
#pragma unroll
            for (int i = lane; i < STATE_V4; i += 32)
                if (cta * STATE_V4 + i < (int)(sizeof(State) / 16)) reinterpret_cast<uint4*>(&g_st)[cta * STATE_V4 + i] = make_uint4(0u, 0u, 0u, 0u);
            if (cta * 512 < X_END) {
                uint4* z = sided<uint4>(p, 0, cta * 512 + lane * 16);
                *z = make_uint4(0u, 0u, 0u, 0u);
                *other_side(z) = make_uint4(0u, 0u, 0u, 0u);
            }
            __syncwarp();
            if (lane == 0) red_release(g_cnt_z);
        }
        if (lane == 0) { TS2(2); wait_count(g_cnt_z, NQ_CTAS); TS2(29); }
        __syncwarp();
        asm volatile("bar.arrive 2, %0;" :: "n"((NWORK + 1) * 32) : "memory");
        uint32_t rtt[2] = {0xffffffffu, 0xffffffffu};
        if (lane == 0) {
#pragma unroll 1
            for (int r = 0; r < 12; r++) {
                int v = 0;
                uint32_t t1 = 0;
                unsigned* ctr = sided<unsigned>(p, r & 1, X_P + ((cta * 32 + (r >> 1) * 768) & 4095));
                pin(ctr);
                const uint32_t t0 = now_clk();
                draw(v, ctr, true);
                asm volatile("{\n.reg .pred q;\nsetp.ge.s32 q, %1, 0;\n@q mov.u32 %0, %%clock;\n}" : "+r"(t1) : "r"(v) : "memory");
                if (r & 1) rtt[1] = min(rtt[1], t1 - t0); else rtt[0] = min(rtt[0], t1 - t0);
            }
            sts32f(sb + SM_SIDE, __int_as_float(rtt[1] < rtt[0]));
        }
        const int side = __shfl_sync(0xffffffffu, rtt[1] < rtt[0], 0);
        fin_arrive<3>();
        int job = cta;
        auto sum_rows = [&](int row_end) {
#pragma unroll 1
            for (; job < 8 * min(row_end, RED0); job += NCTAS) {
                const int row = job >> 3, grp = (job & 7) * 8 + (lane & 7);
                if (lane == 0) wait_row(p, side, row, UPB);
                __syncwarp();
                const float4* src = &g_ring[row % RING][lane >> 3][grp];
                float sx = 0.f, sy = 0.f, sz = 0.f;
#pragma unroll 1
                for (int i = 0; i < 2; i++, src += 64 * 64) {
                    float4 v[16];
#pragma unroll 1
                    for (int it = 0; it < SPIN_MAX; it++) {
                        bool ok = true;
#pragma unroll
                        for (int k = 0; k < 16; k++) v[k] = ld_relaxed_b128(src + k * 4 * 64);
#pragma unroll
                        for (int k = 0; k < 16; k++) ok &= v[k].w == (float)(row + 1);
                        if (__all_sync(0xffffffffu, ok)) break;
                    }
#pragma unroll
                    for (int k = 0; k < 16; k++) { sx += v[k].x; sy += v[k].y; sz += v[k].z; }
                }
#pragma unroll
                for (int o = 8; o < 32; o <<= 1) {
                    sx += __shfl_xor_sync(0xffffffffu, sx, o); sy += __shfl_xor_sync(0xffffffffu, sy, o); sz += __shfl_xor_sync(0xffffffffu, sz, o);
                }
                if (lane < 8) st_relaxed_b128(&g_st.oacc[row][grp], sx, sy, sz, UPB);
            }
        };
        {
            uint32_t wr[10];
            float wsum = 0.f;
#pragma unroll
            for (int i = 0; i < 10; i++) {
                const int w = 4 * lane + 128 * (i >> 2) + (i & 3) - (i >= 8 ? 2 * lane : 0);
                wr[i] = *reinterpret_cast<const uint32_t*>(p.wr + (w >> 4) * 32 + (w & 3) * 8 + ((w >> 1) & 6));
                wsum += lo_f(wr[i]) + hi_f(wr[i]);
            }
            wsum = warp_sum(wsum);
            const int lb = lane >> 3, lc = lane & 7;
            uint32_t ypart = sb + SM_RED2 + (lb >> 1) * 160 + lc * 16 + (lb & 1) * 8;
            __nv_bfloat16* out = p.out + lb * DM + fidx * 16 + lc;
            float nmean_l = 0.f, rden_l = 0.f, sig_l = 0.f;
#pragma unroll 1
            for (int b = 0; b < NB; b++) {
                const uint32_t hx = X_H + b * (DM * 2), hrow = sb + SM_X + b * HPITCH;
                const uint4 *src0 = sided<uint4>(p, side, hx + 16 * lane), *src1 = sided<uint4>(p, side, hx + 512 + 16 * lane);
                const uint2* src2 = sided<uint2>(p, side, hx + 1024 + 8 * lane);
                sum_rows((b + 1) * NH);
                if (!is_l && !is_f && !is_g) continue;
                pin(src0); pin(src1); pin(src2); pin(ypart); pin(out);
                if (lane == 0) wait_row(p, side, b * NH + (is_l ? 28 : NH - 1), is_l ? 1 : 100);
                __syncwarp();
                if (is_l) {
                    const int col = (cta - NE_CTAS) * 32 + 2 * (lane & 15);
                    uint32_t lpart = sb + SM_RED + (lane & 15) * 8;
                    const uint32_t xv = *reinterpret_cast<const uint32_t*>(p.x + b * DM + col);
                    uint32_t* hdst = sided<uint32_t>(p, lane >> 4, hx + 4 * ((col >> 5) * 16 + (col & 6) * 2 + ((col >> 3) & 3)));
                    float4 early;
#pragma unroll 1
                    for (int it = 0; it < SPIN_MAX; it++) {
                        early = ld_relaxed_f4(&g_st.attn[b][col]);
                        if (__all_sync(0xffffffffu, early.y == NE_CTAS / 4 && early.w == NE_CTAS / 4)) break;
                    }
                    if (lane == 0) TS2(23);
                    float x0 = lo_f(xv), x1 = hi_f(xv);
                    pin(hdst); pin(lpart); pin(x0); pin(x1);
                    fin_sync<4>();
                    CK(2, lds32(sb + SM_RED));
                    const float2 late = sum8(lpart);
                    const uint32_t nh = pack_bf16(-x0 - bf16r(early.x + late.x), -x1 - bf16r(early.z + late.y));
                    st_relaxed(hdst, nh ? nh : 0x80008000u);
                    CK(3, 0);
                    if (lane == 0) TS2(15);
                    fin_sync<5>();
                    continue;
                }
                uint4 h0, h1;
                uint2 h2;
                float mm[5][4];
#pragma unroll 1
                for (int it = 0;; it++) {
                    h0 = ld_relaxed_v4(src0);
                    h1 = ld_relaxed_v4(src1);
                    h2 = ld_relaxed_v2(src2);
                    asm volatile("st.shared.v4.u32 [%0], {%1,%2,%3,%4};" :: "r"(hrow + lane * 16), "r"(h0.x), "r"(h0.y), "r"(h0.z), "r"(h0.w) : "memory");
                    asm volatile("st.shared.v4.u32 [%0], {%1,%2,%3,%4};" :: "r"(hrow + 512 + lane * 16), "r"(h1.x), "r"(h1.y), "r"(h1.z), "r"(h1.w) : "memory");
                    asm volatile("st.shared.v2.u32 [%0], {%1,%2};" :: "r"(hrow + 1024 + lane * 8), "r"(h2.x), "r"(h2.y) : "memory");
                    const uint32_t w[10] = {h0.x, h0.y, h0.z, h0.w, h1.x, h1.y, h1.z, h1.w, h2.x, h2.y};
#pragma unroll
                    for (int i = 0; i < 5; i++) {
                        const uint32_t a[4] = {w[2 * i], 0x3f803f80u, w[2 * i + 1], 0x3f803f80u};
                        mm[i][0] = mm[i][1] = mm[i][2] = mm[i][3] = 0.f;
                        mma16816(mm[i], a, w[2 * i], w[2 * i + 1]);
                    }
                    const uint32_t lo = min(min(min(h0.x, h0.y), min(h0.z, h0.w)), min(min(min(h1.x, h1.y), min(h1.z, h1.w)), min(h2.x, h2.y)));
                    const bool ok = __all_sync(0xffffffffu, lo != 0 || it == SPIN_MAX);
                    asm volatile("{\n.reg .pred p;\nsetp.ne.u32 p, %0, 0;\n@p bar.arrive 7, 160;\n@p bar.arrive 8, 160;\n}" :: "r"((uint32_t)ok) : "memory");
                    if (ok) break;
                }
                CK(4, h0.x);
                if (lane == 0) TS2(is_f ? 12 : 17);
                const uint32_t hw[10] = {h0.x, h0.y, h0.z, h0.w, h1.x, h1.y, h1.z, h1.w, h2.x, h2.y};
                float m1 = ((mm[0][2] + mm[1][2]) + (mm[2][2] + mm[3][2])) + ((mm[0][3] + mm[1][3]) + (mm[2][3] + mm[3][3])) + (mm[4][2] + mm[4][3]);
                float m2 = (g & 1) ? ((mm[0][1] + mm[1][1]) + (mm[2][1] + mm[3][1])) + mm[4][1] : ((mm[0][0] + mm[1][0]) + (mm[2][0] + mm[3][0])) + mm[4][0];
                m2 += __shfl_xor_sync(0xffffffffu, m2, 4);
                m1 = (m1 + __shfl_xor_sync(0xffffffffu, m1, 1)) + (__shfl_xor_sync(0xffffffffu, m1, 2) + __shfl_xor_sync(0xffffffffu, m1, 3));
                m2 = (__shfl_sync(0xffffffffu, m2, 0) + __shfl_sync(0xffffffffu, m2, 9)) + (__shfl_sync(0xffffffffu, m2, 18) + __shfl_sync(0xffffffffu, m2, 27));
                m1 *= 1.0f / DM;
                const float nmean = bf16r(m1);
                const float var = bf16r(fmaxf(fmaf(-m1, m1, m2 * (1.0f / DM)), 0.f));
                const float vare = bf16r(var + 1e-5f);
                if (is_f) {
                    sts64f(sb + SM_MOM + b * 8, nmean, vare, lane == 0);
                    CK(5, 0);
                    fin_arrive<4>();
                } else {
                    const float rden = rcp_approx(bf16r(sqrt_approx(vare)));
                    if (lb == b) { nmean_l = nmean; rden_l = rden; }
                    __syncwarp();
                    const float2 hw2 = lds64f(sb + SM_X + lb * HPITCH + ((fidx >> 1) * 16 + (lc & 6) * 2 + (fidx & 1) * 2) * 4);
                    const float nh0 = (lc & 1) ? hi_f(__float_as_uint(hw2.x)) : lo_f(__float_as_uint(hw2.x));
                    const float nh1 = (lc & 1) ? hi_f(__float_as_uint(hw2.y)) : lo_f(__float_as_uint(hw2.y));
                    float rr = 0.f;
#pragma unroll
                    for (int i = 0; i < 10; i++) rr = fmaf(lo_f(hw[i]), lo_f(wr[i]), fmaf(hi_f(hw[i]), hi_f(wr[i]), rr));
                    const float sig = bf16r(sigmoid_approx(bf16r((nmean * wsum - warp_sum(rr)) * rden)));
                    if (lb == b) sig_l = sig;
                    const float ln0 = bf16r(bf16r(nmean_l - nh0) * rden_l), ln1 = bf16r(bf16r(nmean_l - nh1) * rden_l);
                    fin_sync<6>(after(after(after(288, sig_l), ln0), ln1));
                    CK(10, lds32(ypart));
                    float2 t[16];
#pragma unroll
                    for (int i = 0; i < 16; i++) t[i] = lds64f(ypart + i * YPITCH);
#pragma unroll
                    for (int o = 1; o < 16; o <<= 1) {
#pragma unroll
                        for (int i = 0; i < 16; i += 2 * o) { t[i].x += t[i + o].x; t[i].y += t[i + o].y; }
                    }
                    const uint32_t o0 = pack_bf16(bf16r(ln0 - bf16r(bf16r(t[0].x) * sig_l)) - nh0, 0.f);
                    const uint32_t o1 = pack_bf16(bf16r(ln1 - bf16r(bf16r(t[0].y) * sig_l)) - nh1, 0.f);
                    asm volatile("{\n.reg .pred p;\nsetp.eq.u32 p, %3, 3;\n@p st.global.u16 [%0], %1;\n@p st.global.u16 [%0 + 16], %2;\n}"
                                 :: "l"(out), "h"((unsigned short)o0), "h"((unsigned short)o1), "r"(b) : "memory");
                    if (b == NB - 1) return;
                    CK(11, 0);
                    if (lane == 0) TS2(13);
                }
                if (b < NB - 1) fin_sync<5>();
            }
            if (cta == 0 && lane == 0) { g_work[0] = 0; g_cnt_z[0] = 0; }
        }
        return;
    }
    if (warp >= NAUX) {
        const int wk = warp - NAUX;
        const uint32_t bar = sb + BAR_KV + wk * 8;
        const uint32_t buf = sb + SM_KV + wk * TILE_BYTES;
        const uint64_t pol = evict_first();
        const int nstatic = NWORK * grid;
        constexpr int POOL0 = NUNITS - NPOOL;
        int uk = wk * grid + cta;
        wait_clk(now_clk() + 2 * (K0_DELAY_NS + wk * K0_STEP_NS));
        request_tile(buf, &p.k, uk, bar, pol);
        uint32_t koff[3], voff[3];
        {
            const int r = lane & 7, hf = (lane >> 3) & 1;
            const int kkey = hf ? 8 + (r ^ 1) : r;
            const int vh = lane >> 4;
            const int vkey = ((r & 1) ? 8 : 0) + (vh ? (r ^ 1) : r);
#pragma unroll
            for (int b = 0; b < 3; b++) {
                const int rk = 3 * kkey + b, rv = 3 * vkey + b;
                koff[b] = buf + rk * 128 + (((lane >> 4) ^ (rk & 7)) << 4);
                voff[b] = buf + rv * 128 + ((hf ^ (rv & 7)) << 4);
            }
        }
        uint32_t phase = 0;
        uint4 qf[6];
        auto load_q = [&](int u) {
            const uint32_t* q = &g_early[row_of(u)].q[j * 4];
#pragma unroll
            for (int i = 0; i < 6; i++) qf[i] = ld_relaxed_v4(q + i * 16);
        };
        load_q(uk);
        int uq[LAG];
        uint32_t sq[LAG];
#pragma unroll
        for (int i = 0; i < LAG; i++) { uq[i] = -1; sq[i] = 0; }
        uint4 mv = make_uint4(0u, 0u, 0u, 0u);
        uint32_t svp = 0;
        float freed = UPB;
        while (true) {
            const int uv = uq[0];
            uint32_t sv = sq[0];
#pragma unroll
            for (int i = 0; i + 1 < LAG; i++) { uq[i] = uq[i + 1]; sq[i] = sq[i + 1]; }
            uq[LAG - 1] = uk;
            if (uk < NUNITS) {
                PH(7);
#pragma unroll 1
                for (int it = 0; it < SPIN_MAX; it++) {
                    uint32_t lo = 0xffffffffu;
#pragma unroll
                    for (int i = 0; i < 6; i++) lo = min(min(lo, min(qf[i].x, qf[i].y)), min(qf[i].z, qf[i].w));
                    if (__all_sync(0xffffffffu, lo != 0)) break;
                    __nanosleep(250);
                    load_q(uk);
                }
                mbar_wait(bar, phase); phase ^= 1;
                PH(0); ARR();
                TSI(0, 16);
                float acc[2][4][4] = {};
#pragma unroll
                for (int ks = 0; ks < 12; ks++) {
                    const uint4 qq = qf[ks >> 1];
                    const uint32_t b0 = (ks & 1) ? qq.z : qq.x, b1 = (ks & 1) ? qq.w : qq.y;
#pragma unroll
                    for (int mt = 0; mt < 4; mt++) {
                        uint32_t a[4];
                        ldsm4(a, (koff[ks >> 2] ^ ((ks & 3) << 5)) + mt * 6144);
                        mma16816(acc[ks & 1][mt], a, b0, b1);
                    }
                }
                PH(1);
                TSI(0, 19);
                if (uv < NUNITS) request_tile(buf, uv >= 0 ? &p.v : &p.k, uv >= 0 ? uv : uk + nstatic, bar, pol);
                const float sa = sel4(j, acc[0][0][0], acc[0][1][0], acc[0][2][0], acc[0][3][0]) + sel4(j, acc[1][0][0], acc[1][1][0], acc[1][2][0], acc[1][3][0]);
                const float sc = sel4(j, acc[0][0][2], acc[0][1][2], acc[0][2][2], acc[0][3][2]) + sel4(j, acc[1][0][2], acc[1][1][2], acc[1][2][2], acc[1][3][2]);
                const uint32_t raw = pack_bf16(sa, sc);
                const float scale = -0.07216878364870322f;
                const uint32_t sk = pack_bf16(lo_f(raw) * scale, hi_f(raw) * scale);
                sq[LAG - 1] = sk;
                if (uk >= POOL0) st_relaxed(&g_st.score[uk - POOL0][lane], sk ? sk : 0x80008000u);
                int a = (int)(sk << 16), b = (int)(sk & 0xffff0000u);
                a ^= (a >> 31) & 0x7fff0000; b ^= (b >> 31) & 0x7fff0000;
                const int mx = __reduce_max_sync(0xffffffffu, max(a, b));
                if (lane == 0) st_relaxed(&g_early[row_of(uk)].umax[pos_of(uk)], (uint32_t)mx | 1u);
            }
            if (uv < 0) {
                uk += nstatic;
                load_q(uk);
                continue;
            }
            if (uv >= NUNITS) break;
            const int bh = row_of(uv);
#pragma unroll 1
            for (int it = 0; it < SPIN_MAX; it++) {
                if (__all_sync(0xffffffffu, (mv.x & mv.y & mv.z & mv.w & 1u) && (uv < POOL0 || svp != 0) && freed == UPB)) break;
                mv = ld_relaxed_v4(&g_early[bh].umax[lane * 4]);
                if (bh >= RING && bh < RED0) freed = __uint_as_float(ld_relaxed_u32(&g_st.oacc[bh - RING][(lane & 7) * 8].w));
                if (uv >= POOL0) svp = ld_relaxed_u32(&g_st.score[uv - POOL0][lane]);
            }
            if (uv >= POOL0) sv = svp;
            PH(2);
            int un = NUNITS, vn = 0;
            draw(un, g_work, uk < NUNITS && lane == 0);
            int mx = __reduce_max_sync(0xffffffffu, max(max((int)mv.x, (int)mv.y), max((int)mv.z, (int)mv.w))) & 0xffff0000;
            mx ^= (mx >> 31) & 0x7fff0000;
            const float m = __int_as_float(mx);
            const float l2e = 1.4426950408889634f;
            const uint32_t pp = pack_bf16(exp2f((lo_f(sv) - m) * l2e), exp2f((hi_f(sv) - m) * l2e));
            uint32_t pb[8];
#pragma unroll
            for (int t = 0; t < 4; t++) {
                pb[2 * t] = __shfl_sync(0xffffffffu, pp, 8 * j + t);
                pb[2 * t + 1] = __shfl_sync(0xffffffffu, pp, 8 * j + 4 + t);
            }
            float lacc[4] = {};
            const uint32_t ones[4] = {0x3f803f80u, 0x3f803f80u, 0x3f803f80u, 0x3f803f80u};
#pragma unroll
            for (int t = 0; t < 4; t++) mma16816(lacc, ones, pb[2 * t], pb[2 * t + 1]);
            if (uv < nstatic) {
                asm volatile("bar.sync 2, %0;" :: "n"((NWORK + 1) * 32) : "memory");
                TSW(3);
            }
            const int grp = 16 * j + 4 * (g & 1) + (g >> 1);
            float4* dst = bh < RED0 ? &g_ring[bh % RING][pos_of(uv)][grp] : oacc_at(p, lds32(sb + SM_SIDE) ^ 1, bh, grp);
            float4* dst2 = other_side(dst);
            float2* ldst = lsum_at(p, lane & 1, bh);
            if (bh >= SROW0 && lane < 2) red_f2(&ldst->x, lacc[0], 1.f);
            float tag = bh < RED0 ? (float)(bh + 1) : 1.f;
            un = __shfl_sync(0xffffffffu, un, 0) + (LAG + 1) * nstatic;
            uint32_t pooled = uq[0] >= POOL0 && lane == 0;
            pin(dst); pin(dst2); pin(ldst); pin(tag); pin(voff[0]); pin(voff[1]); pin(voff[2]); pin(pooled);
            PH(3);
            LT(1);
            mbar_wait(bar, phase); phase ^= 1;
            PH(4); ARR();
            LT(2);
            draw(vn, g_st.pool, pooled);
            float acc[12][4] = {};
#pragma unroll
            for (int t = 0; t < 4; t++) {
#pragma unroll
                for (int mt = 0; mt < 12; mt++) {
                    uint32_t a[4];
                    ldsm4t(a, (voff[mt >> 2] ^ ((mt & 3) << 5)) + t * 6144);
                    mma16816(acc[mt], a, pb[2 * t], pb[2 * t + 1]);
                }
            }
            PH(5);
            if (lane == 0) PROG(un);
            if (un < NUNITS) request_tile(buf, &p.k, un, bar, pol);
            float o[6];
#pragma unroll
            for (int e = 0; e < 6; e++) {
                const int q = e % 3, c = (e / 3) * 2;
                o[e] = sel4(j, acc[q][c], acc[3 + q][c], acc[6 + q][c], acc[9 + q][c]);
            }
            if (bh >= SROW0) {
                red_f4(&dst->x, o[0], o[1], o[2], tag);
                red_f4(&dst[16].x, o[3], o[4], o[5], tag);
                red_f4(&dst2->x, o[0], o[1], o[2], tag);
                red_f4(&dst2[16].x, o[3], o[4], o[5], tag);
            } else {
                if (bh >= RED0) {
                    red_f4(&dst->x, o[0], o[1], o[2], tag);
                    red_f4(&dst[8].x, o[3], o[4], o[5], tag);
                } else {
                    st_relaxed_b128(dst, o[0], o[1], o[2], tag);
                    st_relaxed_b128(dst + 8, o[3], o[4], o[5], tag);
                }
                if (lane == 0) red_f2(&ldst->x, lacc[0], 1.f);
            }
            if (uq[0] >= POOL0) {
                vn = __shfl_sync(0xffffffffu, vn, 0);
                uq[0] = POOL0 + vn;
                constexpr int LAST = NUNITS - (UPB << NWL);
                static_assert(LAST >= POOL0, "");
                if (uq[0] >= LAST && uq[0] < NUNITS) uq[0] = LAST + (((uq[0] & (UPB - 1)) << NWL) | ((uq[0] - LAST) / UPB));
                if (vn == VTRIG && lane == 0) st_relaxed(g_st.tstart, (now_ns() + TRIG_NS) | 1u);
            }
            if (un < NUNITS) load_q(un);
            PH(6);
            if (uq[0] >= NUNITS && un >= NUNITS) break;
            uk = un;
            if (uq[0] < NUNITS) {
                const int nb = row_of(uq[0]);
                mv = ld_relaxed_v4(&g_early[nb].umax[lane * 4]);
                freed = nb >= RING && nb < RED0 ? __uint_as_float(ld_relaxed_u32(&g_st.oacc[nb - RING][(lane & 7) * 8].w)) : UPB;
                if (uq[0] >= POOL0) svp = ld_relaxed_u32(&g_st.score[uq[0] - POOL0][lane]);
                if (un >= NUNITS) {
                    request_tile(buf, &p.v, uq[0], bar, pol);
                    LT(0);
                }
            }
        }
        if (is_f) asm volatile("bar.arrive 10, %0;" :: "n"((NAUX + NWORK) * 32) : "memory");
        return;
    }

    __nv_bfloat16* xs = reinterpret_cast<__nv_bfloat16*>(smem + SM_X);
    float* red = reinterpret_cast<float*>(smem + SM_RED);
    const int frow = (lane & 7) + ((lane >> 4) << 3), fcol = (lane >> 3) & 1;
    if (cta < NQ_CTAS) {
        uint2 xr[5];
        if (warp < NB) {
#pragma unroll
            for (int i = 0; i < 5; i++) xr[i] = *reinterpret_cast<const uint2*>(p.x + warp * DM + i * 128 + lane * 4);
        }
        TS(26);
        if (warp < NB) {
            float v[20];
#pragma unroll
            for (int i = 0; i < 5; i++) {
                v[4 * i] = lo_f(xr[i].x); v[4 * i + 1] = hi_f(xr[i].x); v[4 * i + 2] = lo_f(xr[i].y); v[4 * i + 3] = hi_f(xr[i].y);
            }
            layernorm20(v);
#pragma unroll
            for (int i = 0; i < 5; i++)
                *reinterpret_cast<uint2*>(xs + warp * XPITCH + i * 128 + lane * 4) =
                    make_uint2(pack_bf16(v[4 * i], v[4 * i + 1]), pack_bf16(v[4 * i + 2], v[4 * i + 3]));
        }
        TS(27);
        aux_sync();
        mbar_wait(sb + BAR_WQ, 0);
        TS(1);
        const uint32_t xfrag = sb + SM_X + ((g & 3) * XPITCH + 2 * j) * 2;
        float acc[3][4] = {};
#pragma unroll
        for (int s = 0; s < 5; s++) {
            const int ks = warp * 5 + s;
            const uint32_t b0 = lds32(xfrag + ks * 32), b1 = lds32(xfrag + ks * 32 + 16);
            const int row = ks * 16 + frow;
#pragma unroll
            for (int mt = 0; mt < 3; mt++) {
                uint32_t a[4];
                ldsm4t(a, sb + SM_WQ + (row * 6 + 2 * mt + fcol) * 16);
                mma16816(acc[mt], a, b0, b1);
            }
        }
        if (j < 2) {
#pragma unroll
            for (int mt = 0; mt < 3; mt++) {
                *reinterpret_cast<float2*>(red + (warp * 48 + mt * 16 + g) * 4 + 2 * j) = make_float2(acc[mt][0], acc[mt][1]);
                *reinterpret_cast<float2*>(red + (warp * 48 + mt * 16 + 8 + g) * 4 + 2 * j) = make_float2(acc[mt][2], acc[mt][3]);
            }
        }
        aux_sync();
        if (tid < 96) {
            const int b = tid & 3, cp = tid >> 2;
            float s0 = 0.f, s1 = 0.f;
#pragma unroll
            for (int w = 0; w < 8; w++) { s0 += red[(w * 48 + 2 * cp) * 4 + b]; s1 += red[(w * 48 + 2 * cp + 1) * 4 + b]; }
            const int h = cta >> 2, d = (cta & 3) * 48 + 2 * cp;
            const int ch = d >> 3, jj = (d & 7) >> 1;
            st_relaxed(&g_early[b * NH + h].q[(ch >> 2) * 16 + jj * 4 + (ch & 3)], pack_neg(s0, s1));
        }
        TS(28);
    }
    if (tid < 160) *reinterpret_cast<uint2*>(smem + SM_X + 4 * HPITCH + tid * 8) = make_uint2(0x3f803f80u, 0x3f803f80u);
    fin_sync<3>();
    const int side = lds32(sb + SM_SIDE);
    mbar_wait(sb + BAR_W, 0);
    TS(7);
    uint32_t part = sb + SM_RED + (warp * 32 + 8 * j + g) * 4;

#pragma unroll 1
    for (int b = 0; b < NB; b++) {
        if (b == NB - 1 && (is_f || is_g)) asm volatile("bar.arrive 9, 288;" ::: "memory");
        if (is_l) {
            uint32_t a[6][2][4];
#pragma unroll
            for (int s = 0; s < 6; s++) {
                const int row = warp * 96 + (s < 4 ? 48 * (s >> 1) + 8 * (s & 1) + 16 * (lane & 1) + (lane & 6) + (lane >> 4) : 48 * (s - 4) + 32 + frow);
#pragma unroll
                for (int mt = 0; mt < 2; mt++) ldsm4t(a[s][mt], sb + SM_A + (row * 4 + ((2 * mt + fcol) ^ ((row >> 1) & 3))) * 16);
            }
            const int bh = b * NH + 28 + (warp >> 1);
            const float4* osrc = oacc_at(p, side, bh, (warp & 1) * 32 + lane);
            const float2* lsrc = lsum_at(p, side, bh);
            if (lane == 0) wait_row_o(p, side, bh, 1);
            __syncwarp();
            float2 lv;
#pragma unroll 1
            for (int it = 0; it < SPIN_MAX; it++) {
                lv = ld_relaxed_f2(lsrc);
                if (__all_sync(0xffffffffu, lv.y == UPB)) break;
            }
            if (warp == 7) TSW(25);
            if (cta == NE_CTAS && lane < 28)
                reinterpret_cast<uint4*>(&g_early[bh])[(warp & 1) * 28 + lane] = make_uint4(0u, 0u, 0u, 0u);
            float rl = rcp_approx(lv.x);
            float4 ov;
            pin(osrc); pin(rl); hold(part);
#pragma unroll 1
            for (int it = 0;; it++) {
                ov = ld_relaxed_f4(osrc);
                if (__all_sync(0xffffffffu, ov.w == UPB || it == SPIN_MAX)) break;
            }
            CK(0, __float_as_uint(ov.x));
            const uint32_t xy = pack_bf16(ov.x * rl, ov.y * rl);
            const float z = ov.z * rl;
            float acc[2][2][4] = {};
#pragma unroll
            for (int s = 0; s < 6; s++) {
                uint32_t bf[2];
#pragma unroll
                for (int kh = 0; kh < 2; kh++) {
                    if (s < 4) bf[kh] = __shfl_sync(0xffffffffu, xy, 8 * s + 4 * kh + j);
                    else bf[kh] = pack_bf16(__shfl_sync(0xffffffffu, z, 16 * (s - 4) + 8 * kh + j), __shfl_sync(0xffffffffu, z, 16 * (s - 4) + 8 * kh + 4 + j));
                }
#pragma unroll
                for (int mt = 0; mt < 2; mt++) mma16816(acc[mt][s & 1], a[s][mt], bf[0], bf[1]);
            }
            sts32f(part, sel4(j, acc[0][0][0] + acc[0][1][0], acc[0][0][2] + acc[0][1][2], acc[1][0][0] + acc[1][1][0], acc[1][0][2] + acc[1][1][2]));
            CK(1, 0);
            fin_arrive<4>();
            if (warp == 7) TSW(30);
            if (warp == 5) TSW(31);
            fin_sync<5>();
            continue;
        }
        {
            const int bh = b * NH + (cta >> 2);
            if (tid == 0) wait_row_o(p, side, bh, UPB);
            aux_sync();
            if (warp < 5) {
                uint32_t ob[12][2];
                load_o<4>(p, ob, bh, 0, j);
                float acc[2][2][4] = {};
#pragma unroll
                for (int ks = 0; ks < 12; ks++) {
                    const int row = ks * 16 + frow;
#pragma unroll
                    for (int mt = 0; mt < 2; mt++) {
                        uint32_t a[4];
                        ldsm4t(a, sb + SM_A + warp * 12288 + (row * 4 + ((2 * mt + fcol) ^ ((row >> 1) & 3))) * 16);
                        mma16816(acc[mt][ks & 1], a, ob[ks][0], ob[ks][1]);
                    }
                }
                red_f2(&g_st.attn[b][(cta & 3) * 160 + warp * 32 + 8 * j + g].x,
                       sel4(j, acc[0][0][0] + acc[0][1][0], acc[0][0][2] + acc[0][1][2], acc[1][0][0] + acc[1][1][0], acc[1][0][2] + acc[1][1][2]), 1.f);
                TS(8);
            } else if (warp > 5 && (cta & 3) == 0 && tid - 192 < 56) {
                reinterpret_cast<uint4*>(&g_early[bh])[tid - 192] = make_uint4(0u, 0u, 0u, 0u);
            }
        }
        if (is_f) {
            const int kq = warp >> 1, tp = warp & 1;
            uint32_t hfrag = sb + SM_X + min(g, 4) * HPITCH + (kq * 80 + 4 * j) * 4;
            uint32_t fpart = sb + SM_RED + 2 * j * FPITCH + warp * 128 + g * 16;
            uint32_t dsum = sb + SM_RED + (lane >> 3) * FPITCH + tp * 128 + (lane & 7) * 16, csum = sb + SM_RED + 4 * FPITCH + tp * 128 + (lane & 7) * 16;
            uint32_t mom = sb + SM_MOM + (lane >> 3) * 8;
            uint32_t* dst = sided<uint32_t>(p, side ^ 1, X_A + (2 * fidx + tp) * 128 + (lane ^ 2 * tp) * 4);
            uint32_t* dst2 = other_side(dst);
            uint32_t wfrag = sb + SM_G + fcol * 40960 + ((kq * 160 + frow) * 4 + (2 * tp ^ ((frow >> 1) & 3))) * 16;
            hold(wfrag); hold(fpart); hold(hfrag); hold(dsum); hold(csum); hold(mom); hold(dst); hold(dst2);
            uint4 hv[5] = {};
#pragma unroll
            for (int s = 0; s < 5; s++) lds128_if(hv[s], hfrag + s * 64, true);
            if (b == NB - 1) asm volatile("bar.sync 10, %0;" :: "n"((NAUX + NWORK) * 32) : "memory");
            uint32_t ga[10][2][4];
#pragma unroll
            for (int s = 0; s < 10; s++) {
                if (s % 5 == 0 && b == NB - 1) mbar_wait(sb + BAR_G + (kq * 2 + s / 5) * 8, 0);
#pragma unroll
                for (int t = 0; t < 2; t++) ldsm4t(ga[s][t], (wfrag ^ (t << 4)) + s * 1024);
            }
            if (warp == NAUX - 1) TSW(9);
            uint32_t dep = 0;
#pragma unroll
            for (int s = 0; s < 5; s++) dep ^= ga[s][0][0] ^ ga[s][1][0];
            h_sync(warp + (dep & (side >> 1)));
#pragma unroll
            for (int s = 0; s < 5; s++) lds128_if(hv[s], hfrag + s * 64, g == b);
            float acc[2][2][4] = {};
#pragma unroll
            for (int s = 0; s < 5; s++) {
#pragma unroll
                for (int t = 0; t < 2; t++) mma16816(acc[t][0], ga[2 * s][t], hv[s].x, hv[s].y);
#pragma unroll
                for (int t = 0; t < 2; t++) mma16816(acc[t][1], ga[2 * s + 1][t], hv[s].z, hv[s].w);
            }
#pragma unroll
            for (int e = 0; e < 2; e++)
                sts128f(fpart + e * FPITCH, acc[0][0][e] + acc[0][1][e], acc[0][0][2 + e] + acc[0][1][2 + e],
                        acc[1][0][e] + acc[1][1][e], acc[1][0][2 + e] + acc[1][1][2 + e], 2 * j + e < 5);
            CK(5, 0);
            if (warp < 2) {
                fin_sync<4>();
                CK(6, lds32(dsum));
                float2 m = lds64f(mom);
                m.y = rcp_approx(bf16r(sqrt_approx(m.y)));
                const float4 d = sum4x4(dsum), cs = sum4x4(csum);
                const float g0 = bf16r(fmaf(m.x, cs.x, -d.x) * m.y), g1 = bf16r(fmaf(m.x, cs.z, -d.z) * m.y);
                const float u0 = bf16r(fmaf(m.x, cs.y, -d.y) * m.y), u1 = bf16r(fmaf(m.x, cs.w, -d.w) * m.y);
                const uint32_t av = pack_neg(bf16r(g0 * sigmoid_approx(g0)) * u0, bf16r(g1 * sigmoid_approx(g1)) * u1);
                asm volatile("{\n.reg .pred p;\nsetp.eq.u32 p, %3, 3;\n@p st.relaxed.gpu.global.u32 [%0], %2;\n@p st.relaxed.gpu.global.u32 [%1], %2;\n}"
                             :: "l"(dst), "l"(dst2), "r"(av), "r"(b) : "memory");
                CK(7, 0);
                TS(14);
            } else {
                fin_arrive<4>();
            }
        } else if (is_g) {
            const uint4* asrc[3];
#pragma unroll
            for (int q = 0; q < 3; q++) {
                asrc[q] = sided<uint4>(p, side, X_A + (warp * 12 + 4 * q + 2 * (g >> 2) + (j >> 1)) * 128 + (g & 3) * 32 + (j & 1) * 16);
                hold(asrc[q]);
            }
            uint32_t ypart = sb + SM_RED2 + (warp * 2 + (j >> 1)) * YPITCH + (j & 1) * 160 + g * 16;
            const int odd = (lane >> 2) & 1, row = (warp * 12 + odd) * 16 + (lane & 1) * 8 + (lane & 2) * 2 + 2 * odd + (lane >> 4);
            uint32_t wfrag = sb + SM_G + (row * 2 + (fcol ^ ((row >> 2) & 1))) * 16;
            hold(ypart); hold(wfrag);
            if (b == NB - 1) {
                mbar_wait(sb + BAR_G + warp * 8, 0);
                if (warp == NAUX - 1) TSW(10);
            } else {
                h_sync(warp);
            }
            uint32_t wb[3][2][2][4];
#pragma unroll
            for (int s = 0; s < 12; s++) ldsm4t(wb[s >> 2][(s >> 1) & 1][s & 1], (wfrag ^ ((s & 1) << 6)) + (s >> 1) * 1024);
            if (b == NB - 1 && warp < 6) mbar_wait(sb + BAR_G + 6 * 8, 0);
            uint4 v[3] = {};
            uint32_t mq[3];
            mq[0] = mq[1] = mq[2] = b < NB - 1;
#pragma unroll 1
            for (int it = b < NB - 1 ? SPIN_MAX : 0;; it++) {
                asm volatile("{\n.reg .pred p0, p1, p2;\nsetp.eq.u32 p0, %15, 0;\nsetp.eq.u32 p1, %16, 0;\nsetp.eq.u32 p2, %17, 0;\n"
                             "@p0 ld.relaxed.gpu.global.v4.u32 {%0,%1,%2,%3}, [%12];\n"
                             "@p1 ld.relaxed.gpu.global.v4.u32 {%4,%5,%6,%7}, [%13];\n"
                             "@p2 ld.relaxed.gpu.global.v4.u32 {%8,%9,%10,%11}, [%14];\n}"
                             : "+r"(v[0].x), "+r"(v[0].y), "+r"(v[0].z), "+r"(v[0].w), "+r"(v[1].x), "+r"(v[1].y), "+r"(v[1].z), "+r"(v[1].w),
                               "+r"(v[2].x), "+r"(v[2].y), "+r"(v[2].z), "+r"(v[2].w)
                             : "l"(asrc[0]), "l"(asrc[1]), "l"(asrc[2]), "r"(mq[0]), "r"(mq[1]), "r"(mq[2]) : "memory");
#pragma unroll
                for (int q = 0; q < 3; q++) mq[q] = min(min(v[q].x, v[q].y), min(v[q].z, v[q].w));
                const uint32_t lo = min(min(mq[0], mq[1]), mq[2]);
                if (__all_sync(0xffffffffu, lo != 0 || it == SPIN_MAX)) break;
            }
            CK(8, v[0].x);
            float acc[2][2][4] = {};
#pragma unroll
            for (int q = 0; q < 3; q++) {
#pragma unroll
                for (int pr = 0; pr < 2; pr++) {
                    mma16816(acc[pr][0], wb[q][pr][0], v[q].x, v[q].y);
                    mma16816(acc[pr][1], wb[q][pr][1], v[q].z, v[q].w);
                }
            }
            float y[4];
#pragma unroll
            for (int e = 0; e < 4; e++) y[e] = j < 2 ? acc[0][0][e] + acc[0][1][e] : acc[1][0][e] + acc[1][1][e];
            asm volatile("st.shared.v4.f32 [%0], {%1,%2,%3,%4};" :: "r"(ypart), "f"(y[0]), "f"(y[2]), "f"(y[1]), "f"(y[3]) : "memory");
            CK(9, 0);
            fin_arrive<6>();
        } else {
            continue;
        }
        if (b < NB - 1) fin_sync<5>();
    }
}

typedef CUresult (*EncodeFn)(CUtensorMap*, CUtensorMapDataType, cuuint32_t, void*, const cuuint64_t*, const cuuint64_t*,
                             const cuuint32_t*, const cuuint32_t*, CUtensorMapInterleave, CUtensorMapSwizzle,
                             CUtensorMapL2promotion, CUtensorMapFloatOOBfill);

CUtensorMap make_map(EncodeFn enc, void* ptr, uint64_t cols, uint64_t rows, uint32_t bcols, uint32_t brows,
                     CUtensorMapSwizzle sw, CUtensorMapL2promotion promo) {
    CUtensorMap m;
    const cuuint64_t dims[2] = {cols, rows};
    const cuuint64_t strides[1] = {cols * 2};
    const cuuint32_t box[2] = {bcols, brows};
    const cuuint32_t es[2] = {1, 1};
    enc(&m, CU_TENSOR_MAP_DATA_TYPE_BFLOAT16, 2, ptr, dims, strides, box, es, CU_TENSOR_MAP_INTERLEAVE_NONE, sw, promo,
        CU_TENSOR_MAP_FLOAT_OOB_FILL_NONE);
    return m;
}

}

extern "C" void kernel_launch(void* const* d_in, const int* in_sizes, int n_in, void* d_out, int out_size) {
    (void)in_sizes; (void)n_in; (void)out_size;
    static EncodeFn enc = nullptr;
    static int sms = 0;
    static void* raw = nullptr;
    if (!enc) {
        cudaDriverEntryPointQueryResult qr;
        cudaGetDriverEntryPoint("cuTensorMapEncodeTiled", (void**)&enc, cudaEnableDefault, &qr);
        int dev = 0;
        cudaGetDevice(&dev);
        cudaDeviceGetAttribute(&sms, cudaDevAttrMultiProcessorCount, dev);
        cudaGetSymbolAddress(&raw, g_raw);
        cudaFuncSetAttribute(fused_decode_kernel, cudaFuncAttributeMaxDynamicSharedMemorySize, SM_TOTAL);
    }
    if (sms < NCTAS) return;
    const CUtensorMapL2promotion WPROMO = CU_TENSOR_MAP_L2_PROMOTION_L2_128B;
    Params p;
    p.k = make_map(enc, d_in[1], 64, (uint64_t)NBH * SK * 3, 64, TILE_ROWS, CU_TENSOR_MAP_SWIZZLE_128B, CU_TENSOR_MAP_L2_PROMOTION_NONE);
    p.v = make_map(enc, d_in[2], 64, (uint64_t)NBH * SK * 3, 64, TILE_ROWS, CU_TENSOR_MAP_SWIZZLE_128B, CU_TENSOR_MAP_L2_PROMOTION_NONE);
    p.wq = make_map(enc, d_in[3], NH * DH, DM, 48, 160, CU_TENSOR_MAP_SWIZZLE_NONE, WPROMO);
    p.wo = make_map(enc, d_in[4], DM, NH * DH, 32, 48, CU_TENSOR_MAP_SWIZZLE_64B, WPROMO);
    p.wg = make_map(enc, d_in[7], FF, DM, 32, 80, CU_TENSOR_MAP_SWIZZLE_64B, WPROMO);
    p.wu = make_map(enc, d_in[8], FF, DM, 32, 80, CU_TENSOR_MAP_SWIZZLE_64B, WPROMO);
    p.wd = make_map(enc, d_in[9], DM, FF, 16, 192, CU_TENSOR_MAP_SWIZZLE_32B, WPROMO);
    p.scratch = reinterpret_cast<Scratch*>((reinterpret_cast<uintptr_t>(raw) + PAGE - 1) & ~(uintptr_t)(PAGE - 1));
    p.wq_raw = (const char*)d_in[3];
    p.x = (const __nv_bfloat16*)d_in[0];
    p.wr = (const __nv_bfloat16*)d_in[6];
    p.out = (__nv_bfloat16*)d_out;
    fused_decode_kernel<<<NCTAS, NTHREADS, SM_TOTAL, cudaStreamPerThread>>>(p);
}
```

```cpp
#include <cuda_runtime.h>
#include <cuda_bf16.h>
#include <cuda.h>
#include <stdint.h>

namespace {

constexpr int NB = 4, NH = 32, SK = 8192, DH = 192, DM = 640, FF = 1536;
constexpr int NBH = NB * NH;
constexpr int TILE = 64;
constexpr int UPB = SK / TILE;
constexpr int NUNITS = NBH * UPB;
constexpr int TILE_BYTES = TILE * DH * 2;
constexpr int TILE_ROWS = TILE * 3;
constexpr int NCTAS = 132;
constexpr int NQ_CTAS = 128;
constexpr int NE_CTAS = 112;
enum { ROLE_NONE, ROLE_L, ROLE_F, ROLE_G };

constexpr int SROW0 = NBH - 4;

#define NWORK 2
#define NWL 2
#define SKEW 16
#define LAG 3
#define NPOOL 896
#define RED0 120
#define RING 12
#define K0_DELAY_NS 1600
#define K0_STEP_NS 900
#define WO_AT_NS 3400
#define WO_GAP_NS 600
#define VTRIG (NPOOL - 240)
#define TRIG_NS 2100
#define GCLK 290
#define DOFF 2100
#define DCLK 150
constexpr int NAUX = 8;
constexpr int NTHREADS = (NAUX + NWORK + 2) * 32;
constexpr int SPIN_MAX = 1 << 22;

constexpr int SM_KV = 0;
constexpr int SM_A = SM_KV + NWORK * TILE_BYTES;
constexpr int SM_WQ = SM_A + 61440;
constexpr int SM_G = SM_WQ;
constexpr int SM_X = SM_G + 81920;
constexpr int XPITCH = 648;
constexpr int HPITCH = 1344;
constexpr int SM_RED = SM_X + 5 * HPITCH;
constexpr int FPITCH = 1040;
constexpr int SM_RED2 = SM_RED;
constexpr int YPITCH = 320;
constexpr int SM_MISC = SM_RED + 6144;
constexpr int BAR_KV = SM_MISC, BAR_WQ = SM_MISC + 32, BAR_W = SM_MISC + 40, SM_SIDE = SM_MISC + 48, BAR_G = SM_MISC + 64, SM_MOM = SM_MISC + 128;
constexpr int SM_TOTAL = SM_MISC + 160;

struct Scratch;
struct Params {
    CUtensorMap k, v;
    CUtensorMap wq;
    CUtensorMap wo;
    CUtensorMap wg, wu;
    CUtensorMap wd;
    Scratch* scratch;
    const char* wq_raw;
    const __nv_bfloat16 *x, *wr;
    __nv_bfloat16* out;
    uint16_t role[NCTAS];
};

struct Early {
    uint32_t q[96];
    uint32_t umax[UPB];
};
struct State {
    float4 oacc[SROW0][64];
    float2 attn[NB][DM];
    float2 lsum[SROW0][16];
    unsigned pool[64];
    uint32_t tstart[32];
    uint32_t score[NPOOL][32];
};
constexpr int STATE_V4 = ((sizeof(State) / 32 + NQ_CTAS - 1) / NQ_CTAS) * 2;
static_assert(sizeof(State) % 32 == 0, "State is cleared in whole sectors");
static_assert(sizeof(Early) == 56 * 16, "an Early entry is cleared by 56 threads");
constexpr uint32_t X_O = 0;
constexpr uint32_t X_L = X_O + 4 * 1024;
constexpr uint32_t X_H = X_L + 4 * 128;
constexpr uint32_t X_A = X_H + NB * DM * 2;
constexpr uint32_t X_P = X_A + NB * FF * 2;
constexpr uint32_t X_END = X_P + 4096;
static_assert(X_END <= 8 * 4096 && RED0 <= SROW0, "");
struct Scratch {
    unsigned char sided[8][2][4096];
    unsigned work[64];
    unsigned cnt_z[32];
    unsigned char pad0[1024];
    Early early[NBH];
    unsigned char pad1[1024];
    State st;
    unsigned char pad2[1792];
    float4 ring[RING][UPB][64];
};
constexpr size_t PAGE = 2u << 20;
static_assert(sizeof(Scratch) <= PAGE, "scratch must fit one page");
__device__ __align__(128) unsigned char g_raw[2 * PAGE];
template <typename T> __device__ __forceinline__ T* sided(const Params& p, int side, uint32_t x) {
    const uint32_t pair = (x >> 10) & 7;
    return reinterpret_cast<T*>(&p.scratch->sided[pair][(side ^ pair) & 1]
                                    [(x & 127) + ((x & 128) << 1) + ((x & 768) << 2) + ((x >> 6) & 128) + ((x >> 5) & 512)]);
}
template <typename T> __device__ __forceinline__ T* other_side(T* p) { return reinterpret_cast<T*>(reinterpret_cast<uintptr_t>(p) ^ 4096); }
#define g_early p.scratch->early
#define g_st p.scratch->st
#define g_ring p.scratch->ring
#define g_cnt_z p.scratch->cnt_z
#define g_work p.scratch->work
#define TS(i)
#define TSW(i)
#define TS2(i)
#define TSI(n, i)
#define PH(i)
#define CK(i, dep)
#define ARR()
#define PROG(u)
#define LT(i)

__device__ __forceinline__ int row_of(int u) { return (((unsigned)u >> (7 + NWL)) << NWL) | (u & ((1 << NWL) - 1)); }
__device__ __forceinline__ int pos_of(int u) { return ((unsigned)u >> NWL) & (UPB - 1); }
__device__ __forceinline__ int tile_of(int u) { return (row_of(u) * UPB + ((pos_of(u) + (u & ((1 << NWL) - 1)) * SKEW) & (UPB - 1))) * TILE_ROWS; }

__device__ __forceinline__ uint32_t s2u(const void* p) { return (uint32_t)__cvta_generic_to_shared(p); }
__device__ __forceinline__ void mbar_init(uint32_t bar, int cnt) {
    asm volatile("mbarrier.init.shared::cta.b64 [%0], %1;" :: "r"(bar), "r"(cnt) : "memory");
}
__device__ __forceinline__ void mbar_expect_tx(uint32_t bar, uint32_t bytes) {
    asm volatile("mbarrier.arrive.expect_tx.shared::cta.b64 _, [%0], %1;" :: "r"(bar), "r"(bytes) : "memory");
}
__device__ __forceinline__ void mbar_wait(uint32_t bar, uint32_t parity) {
    asm volatile("{\n.reg .pred p;\n.reg .u32 n;\nmov.u32 n, 0;\nWAIT_LOOP:\n"
                 "mbarrier.try_wait.parity.shared::cta.b64 p, [%0], %1;\n"
                 "@p bra WAIT_DONE;\nadd.u32 n, n, 1;\nsetp.lt.u32 p, n, %2;\n@p bra WAIT_LOOP;\nWAIT_DONE:\n}"
                 :: "r"(bar), "r"(parity), "n"(SPIN_MAX) : "memory");
}
__device__ __forceinline__ void request_tile(uint32_t dst, const CUtensorMap* tm, int unit, uint32_t bar, uint64_t pol) {
    asm volatile("{\n.reg .pred p;\nelect.sync _|p, 0xffffffff;\n"
                 "@p mbarrier.arrive.expect_tx.shared::cta.b64 _, [%2], %6;\n"
                 "@p cp.async.bulk.tensor.2d.shared::cluster.global.mbarrier::complete_tx::bytes.L2::cache_hint "
                 "[%0], [%1, {%3, %4}], [%2], %5;\n}"
                 :: "r"(dst), "l"(tm), "r"(bar), "r"(0), "r"(tile_of(unit)), "l"(pol), "n"(TILE_BYTES) : "memory");
}
__device__ __forceinline__ uint32_t now_ns() { uint32_t t; asm volatile("mov.u32 %0, %%globaltimer_lo;" : "=r"(t)); return t; }
__device__ __forceinline__ uint32_t now_clk() { uint32_t t; asm volatile("mov.u32 %0, %%clock;" : "=r"(t)); return t; }
__device__ __forceinline__ void wait_clk(uint32_t t) { while (__any_sync(0xffffffffu, (int)(now_clk() - t) < 0)) {} }
__device__ __forceinline__ uint64_t evict_first() {
    uint64_t pol;
    asm volatile("createpolicy.fractional.L2::evict_first.b64 %0, 1.0;" : "=l"(pol));
    return pol;
}
__device__ __forceinline__ void request_box(uint32_t dst, const CUtensorMap* tm, int col, int row, uint32_t bar) {
    asm volatile("{\n.reg .pred p;\nelect.sync _|p, 0xffffffff;\n"
                 "@p cp.async.bulk.tensor.2d.shared::cluster.global.mbarrier::complete_tx::bytes [%0], [%1, {%3, %4}], [%2];\n}"
                 :: "r"(dst), "l"(tm), "r"(bar), "r"(col), "r"(row) : "memory");
}
__device__ __forceinline__ void request_box(uint32_t dst, const CUtensorMap* tm, int col, int row, uint32_t bar, uint64_t pol) {
    asm volatile("{\n.reg .pred p;\nelect.sync _|p, 0xffffffff;\n"
                 "@p cp.async.bulk.tensor.2d.shared::cluster.global.mbarrier::complete_tx::bytes.L2::cache_hint [%0], [%1, {%3, %4}], [%2], %5;\n}"
                 :: "r"(dst), "l"(tm), "r"(bar), "r"(col), "r"(row), "l"(pol) : "memory");
}
__device__ __forceinline__ uint32_t lds32(uint32_t addr) {
    uint32_t v;
    asm volatile("ld.shared.u32 %0, [%1];" : "=r"(v) : "r"(addr) : "memory");
    return v;
}
__device__ __forceinline__ void ldsm4(uint32_t (&r)[4], uint32_t addr) {
    asm volatile("ldmatrix.sync.aligned.m8n8.x4.shared.b16 {%0,%1,%2,%3}, [%4];"
                 : "=r"(r[0]), "=r"(r[1]), "=r"(r[2]), "=r"(r[3]) : "r"(addr) : "memory");
}
__device__ __forceinline__ void ldsm4t(uint32_t (&r)[4], uint32_t addr) {
    asm volatile("ldmatrix.sync.aligned.m8n8.x4.trans.shared.b16 {%0,%1,%2,%3}, [%4];"
                 : "=r"(r[0]), "=r"(r[1]), "=r"(r[2]), "=r"(r[3]) : "r"(addr) : "memory");
}
__device__ __forceinline__ void mma16816(float (&c)[4], const uint32_t (&a)[4], uint32_t b0, uint32_t b1) {
    asm volatile("mma.sync.aligned.m16n8k16.row.col.f32.bf16.bf16.f32 {%0,%1,%2,%3}, {%4,%5,%6,%7}, {%8,%9}, {%0,%1,%2,%3};"
                 : "+f"(c[0]), "+f"(c[1]), "+f"(c[2]), "+f"(c[3])
                 : "r"(a[0]), "r"(a[1]), "r"(a[2]), "r"(a[3]), "r"(b0), "r"(b1));
}
__device__ __forceinline__ uint4 ld_relaxed_v4(const void* p) {
    uint4 v;
    asm volatile("ld.relaxed.gpu.global.v4.u32 {%0,%1,%2,%3}, [%4];" : "=r"(v.x), "=r"(v.y), "=r"(v.z), "=r"(v.w) : "l"(p) : "memory");
    return v;
}
__device__ __forceinline__ float4 ld_relaxed_f4(const void* p) {
    float4 v;
    asm volatile("ld.relaxed.gpu.global.v4.f32 {%0,%1,%2,%3}, [%4];" : "=f"(v.x), "=f"(v.y), "=f"(v.z), "=f"(v.w) : "l"(p) : "memory");
    return v;
}
__device__ __forceinline__ float2 ld_relaxed_f2(const void* p) {
    float2 v;
    asm volatile("ld.relaxed.gpu.global.v2.f32 {%0,%1}, [%2];" : "=f"(v.x), "=f"(v.y) : "l"(p) : "memory");
    return v;
}
__device__ __forceinline__ float4 ld_relaxed_b128(const void* p) {
    float4 v;
    asm volatile("{\n.reg .b128 t;\n.reg .b64 a, b;\nld.relaxed.gpu.global.b128 t, [%4];\nmov.b128 {a, b}, t;\n"
                 "mov.b64 {%0, %1}, a;\nmov.b64 {%2, %3}, b;\n}" : "=f"(v.x), "=f"(v.y), "=f"(v.z), "=f"(v.w) : "l"(p) : "memory");
    return v;
}
__device__ __forceinline__ void st_relaxed_b128(void* p, float x, float y, float z, float w) {
    asm volatile("{\n.reg .b128 t;\n.reg .b64 a, b;\nmov.b64 a, {%1, %2};\nmov.b64 b, {%3, %4};\nmov.b128 t, {a, b};\n"
                 "st.relaxed.gpu.global.b128 [%0], t;\n}" :: "l"(p), "f"(x), "f"(y), "f"(z), "f"(w) : "memory");
}
__device__ __forceinline__ unsigned ld_acquire(const unsigned* p) {
    unsigned v;
    asm volatile("ld.acquire.gpu.global.u32 %0, [%1];" : "=r"(v) : "l"(p) : "memory");
    return v;
}
__device__ __forceinline__ void st_relaxed(void* p, uint32_t v) {
    asm volatile("st.relaxed.gpu.global.u32 [%0], %1;" :: "l"(p), "r"(v) : "memory");
}
__device__ __forceinline__ void red_f2(float* p, float a, float b) {
    asm volatile("red.relaxed.gpu.global.add.v2.f32 [%0], {%1,%2};" :: "l"(p), "f"(a), "f"(b) : "memory");
}
__device__ __forceinline__ void red_f4(float* p, float a, float b, float c, float d) {
    asm volatile("red.relaxed.gpu.global.add.v4.f32 [%0], {%1,%2,%3,%4};" :: "l"(p), "f"(a), "f"(b), "f"(c), "f"(d) : "memory");
}
__device__ __forceinline__ void draw(int& ticket, unsigned* ctr, bool pred) {
    asm volatile("{\n.reg .pred p;\nsetp.ne.u32 p, %2, 0;\n@p atom.relaxed.gpu.global.inc.u32 %0, [%1], 0x7fffffff;\n}"
                 : "+r"(ticket) : "l"(ctr), "r"((uint32_t)pred) : "memory");
}
__device__ __forceinline__ void red_release(unsigned* p) {
    asm volatile("red.release.gpu.global.add.u32 [%0], 1;" :: "l"(p) : "memory");
}
__device__ __forceinline__ uint32_t ld_relaxed_u32(const void* p) {
    uint32_t v;
    asm volatile("ld.relaxed.gpu.global.u32 %0, [%1];" : "=r"(v) : "l"(p) : "memory");
    return v;
}
__device__ __forceinline__ float rcp_approx(float v) {
    float r;
    asm("rcp.approx.ftz.f32 %0, %1;" : "=f"(r) : "f"(v));
    return r;
}
__device__ __forceinline__ float sigmoid_approx(float v) {
    float e;
    asm("ex2.approx.ftz.f32 %0, %1;" : "=f"(e) : "f"(v * -1.4426950408889634f));
    return rcp_approx(1.0f + e);
}
__device__ __forceinline__ float sqrt_approx(float v) {
    float r;
    asm("sqrt.approx.ftz.f32 %0, %1;" : "=f"(r) : "f"(v));
    return r;
}
__device__ __forceinline__ uint2 ld_relaxed_v2(const void* p) {
    uint2 v;
    asm volatile("ld.relaxed.gpu.global.v2.u32 {%0,%1}, [%2];" : "=r"(v.x), "=r"(v.y) : "l"(p) : "memory");
    return v;
}
__device__ __forceinline__ void wait_count(const unsigned* p, unsigned target) {
#pragma unroll 1
    for (int it = 0; it < SPIN_MAX; it++) {
        if (ld_acquire(p) >= target) break;
        __nanosleep(400);
    }
}
__device__ __forceinline__ float4* oacc_at(const Params& p, int side, int row, int grp) {
    return row >= SROW0 ? sided<float4>(p, side, X_O + (row - SROW0) * 1024 + grp * 16) : &g_st.oacc[row][grp];
}
__device__ __forceinline__ float2* lsum_at(const Params& p, int side, int row) {
    return row >= SROW0 ? sided<float2>(p, side, X_L + (row - SROW0) * 128) : g_st.lsum[row];
}
__device__ __forceinline__ void wait_row(const Params& p, int side, int bh, float n) {
    const float2* l = lsum_at(p, side, bh);
#pragma unroll 1
    for (int it = 0; it < SPIN_MAX; it++) {
        const float c = ld_relaxed_f2(l).y;
        if (c >= n) break;
        if (c == 0.f) __nanosleep(600);
    }
}
__device__ __forceinline__ void wait_row_o(const Params& p, int side, int bh, float n) {
    wait_row(p, side, bh, n);
    if (bh >= RED0) return;
#pragma unroll 1
    for (int it = 0; it < SPIN_MAX; it++) {
        if (__uint_as_float(ld_relaxed_u32(&g_st.oacc[bh][0].w)) == UPB) break;
        __nanosleep(300);
    }
}
__device__ __forceinline__ uint32_t pack_bf16(float lo, float hi) {
    uint32_t r;
    asm("cvt.rn.bf16x2.f32 %0, %1, %2;" : "=r"(r) : "f"(hi), "f"(lo));
    return r;
}
__device__ __forceinline__ float bf16r(float v) { return __uint_as_float(pack_bf16(0.f, v)); }
__device__ __forceinline__ uint32_t pack_neg(float lo, float hi) {
    const uint32_t w = pack_bf16(-lo, -hi);
    return w ? w : 0x80008000u;
}
__device__ __forceinline__ float lo_f(uint32_t v) { return __uint_as_float(v << 16); }
__device__ __forceinline__ float hi_f(uint32_t v) { return __uint_as_float(v & 0xffff0000u); }
__device__ __forceinline__ float warp_sum(float v) {
#pragma unroll
    for (int o = 16; o; o >>= 1) v += __shfl_xor_sync(0xffffffffu, v, o);
    return v;
}
__device__ __forceinline__ void layernorm20(float (&v)[20]) {
    float s = 0.f;
#pragma unroll
    for (int i = 0; i < 20; i++) s += v[i];
    const float mean = warp_sum(s) * (1.0f / DM);
    float q = 0.f;
#pragma unroll
    for (int i = 0; i < 20; i++) { const float d = v[i] - mean; q += d * d; }
    const float var = bf16r(warp_sum(q) * (1.0f / DM));
    const float m = bf16r(mean);
    const float rden = 1.0f / bf16r(sqrtf(bf16r(var + 1e-5f)));
#pragma unroll
    for (int i = 0; i < 20; i++) v[i] = bf16r(bf16r(v[i] - m) * rden);
}

__device__ __forceinline__ float sel4(int j, float a, float b, float c, float d) {
    float lo, hi, r;
    asm("{\n.reg .pred p;\nsetp.ne.s32 p, %3, 0;\nselp.f32 %0, %2, %1, p;\n}" : "=f"(lo) : "f"(a), "f"(b), "r"(j & 1));
    asm("{\n.reg .pred p;\nsetp.ne.s32 p, %3, 0;\nselp.f32 %0, %2, %1, p;\n}" : "=f"(hi) : "f"(c), "f"(d), "r"(j & 1));
    asm("{\n.reg .pred p;\nsetp.ne.s32 p, %3, 0;\nselp.f32 %0, %2, %1, p;\n}" : "=f"(r) : "f"(lo), "f"(hi), "r"(j & 2));
    return r;
}
template <typename T> __device__ __forceinline__ void pin(T*& p) { asm volatile("" : "+l"(p)); }
__device__ __forceinline__ void pin(uint32_t& v) { asm volatile("" : "+r"(v)); }
__device__ __forceinline__ void pin(float& v) { asm volatile("" : "+f"(v)); }
__device__ __forceinline__ void hold(uint32_t& v) { v = __shfl_xor_sync(0xffffffffu, v, 0); }
template <typename T> __device__ __forceinline__ void hold(T*& p) {
    p = reinterpret_cast<T*>(__shfl_xor_sync(0xffffffffu, (unsigned long long)reinterpret_cast<uintptr_t>(p), 0));
}
__device__ __forceinline__ uint32_t after(uint32_t n, float v) {
    asm volatile("{\n.reg .pred p;\nsetp.eq.u32 p, %1, 0x7fc1a5a5;\n@p add.u32 %0, %0, 32;\n}" : "+r"(n) : "r"(__float_as_uint(v)));
    return n;
}
__device__ __forceinline__ float2 lds64f(uint32_t addr) {
    float2 v;
    asm volatile("ld.shared.v2.f32 {%0,%1}, [%2];" : "=f"(v.x), "=f"(v.y) : "r"(addr) : "memory");
    return v;
}
__device__ __forceinline__ float4 lds128f(uint32_t addr) {
    float4 v;
    asm volatile("ld.shared.v4.f32 {%0,%1,%2,%3}, [%4];" : "=f"(v.x), "=f"(v.y), "=f"(v.z), "=f"(v.w) : "r"(addr) : "memory");
    return v;
}
__device__ __forceinline__ void sts64f(uint32_t addr, float a, float b, bool pred) {
    asm volatile("{\n.reg .pred p;\nsetp.ne.u32 p, %3, 0;\n@p st.shared.v2.f32 [%0], {%1,%2};\n}" :: "r"(addr), "f"(a), "f"(b), "r"((uint32_t)pred) : "memory");
}
__device__ __forceinline__ void sts128f(uint32_t addr, float a, float b, float c, float d, bool pred) {
    asm volatile("{\n.reg .pred p;\nsetp.ne.u32 p, %5, 0;\n@p st.shared.v4.f32 [%0], {%1,%2,%3,%4};\n}"
                 :: "r"(addr), "f"(a), "f"(b), "f"(c), "f"(d), "r"((uint32_t)pred) : "memory");
}
__device__ __forceinline__ void lds128_if(uint4& v, uint32_t addr, bool pred) {
    asm volatile("{\n.reg .pred p;\nsetp.ne.u32 p, %5, 0;\n@p ld.shared.v4.u32 {%0,%1,%2,%3}, [%4];\n}"
                 : "+r"(v.x), "+r"(v.y), "+r"(v.z), "+r"(v.w) : "r"(addr), "r"((uint32_t)pred) : "memory");
}
__device__ __forceinline__ void sts32f(uint32_t addr, float v) { asm volatile("st.shared.f32 [%0], %1;" :: "r"(addr), "f"(v) : "memory"); }
template <int ID> __device__ __forceinline__ void fin_arrive() { asm volatile("bar.arrive %0, 288;" :: "n"(ID) : "memory"); }
template <int ID> __device__ __forceinline__ void fin_sync() { asm volatile("bar.sync %0, 288;" :: "n"(ID) : "memory"); }
template <int ID> __device__ __forceinline__ void fin_sync(uint32_t n) { asm volatile("bar.sync %0, %1;" :: "n"(ID), "r"(n) : "memory"); }
__device__ __forceinline__ float2 sum8(uint32_t addr) {
    float2 t[8];
#pragma unroll
    for (int w = 0; w < 8; w++) t[w] = lds64f(addr + w * 128);
    return make_float2(((t[0].x + t[1].x) + (t[2].x + t[3].x)) + ((t[4].x + t[5].x) + (t[6].x + t[7].x)),
                       ((t[0].y + t[1].y) + (t[2].y + t[3].y)) + ((t[4].y + t[5].y) + (t[6].y + t[7].y)));
}
__device__ __forceinline__ float4 sum4x4(uint32_t addr) {
    float4 t[4];
#pragma unroll
    for (int w = 0; w < 4; w++) t[w] = lds128f(addr + w * 256);
    return make_float4((t[0].x + t[1].x) + (t[2].x + t[3].x), (t[0].y + t[1].y) + (t[2].y + t[3].y),
                       (t[0].z + t[1].z) + (t[2].z + t[3].z), (t[0].w + t[1].w) + (t[2].w + t[3].w));
}
template <int NJ>
__device__ __forceinline__ void load_o(const Params& p, uint32_t (&ob)[3 * NJ][2], int bh, int J0, int j) {
    float4 v[NJ][4];
    float2 l;
#pragma unroll 1
    for (int it = 0; it < SPIN_MAX; it++) {
#pragma unroll
        for (int J = 0; J < NJ; J++) {
#pragma unroll
            for (int e = 0; e < 4; e++) v[J][e] = ld_relaxed_f4(&g_st.oacc[bh][(J0 + J) * 16 + e * 4 + j]);
        }
        l = ld_relaxed_f2(g_st.lsum[bh]);
        bool ok = l.y == UPB;
#pragma unroll
        for (int J = 0; J < NJ; J++) {
#pragma unroll
            for (int e = 0; e < 4; e++) ok &= v[J][e].w == UPB;
        }
        if (__all_sync(0xffffffffu, ok)) break;
    }
    const float rl = __fdividef(1.0f, l.x);
#pragma unroll
    for (int J = 0; J < NJ; J++) {
        ob[3 * J][0] = pack_bf16(v[J][0].x * rl, v[J][1].x * rl);     ob[3 * J][1] = pack_bf16(v[J][2].x * rl, v[J][3].x * rl);
        ob[3 * J + 1][0] = pack_bf16(v[J][0].y * rl, v[J][1].y * rl); ob[3 * J + 1][1] = pack_bf16(v[J][2].y * rl, v[J][3].y * rl);
        ob[3 * J + 2][0] = pack_bf16(v[J][0].z * rl, v[J][1].z * rl); ob[3 * J + 2][1] = pack_bf16(v[J][2].z * rl, v[J][3].z * rl);
    }
}
__device__ __forceinline__ void h_sync(uint32_t warp) {
    asm volatile("{\n.reg .pred p;\nsetp.lt.u32 p, %0, 4;\n@p bar.sync 7, 160;\n@!p bar.sync 8, 160;\n}" :: "r"(warp) : "memory");
}
__device__ __forceinline__ void aux_sync() { asm volatile("bar.sync 1, 256;" ::: "memory"); }

__global__ void __launch_bounds__(NTHREADS, 1)
fused_decode_kernel(const __grid_constant__ Params p) {
    extern __shared__ __align__(1024) unsigned char smem[];
    asm volatile("prefetch.global.L2 [%0];" :: "l"(p.wq_raw + (blockIdx.x * NTHREADS + threadIdx.x) * 48));
    const uint32_t sb = s2u(smem);
    const int tid = threadIdx.x, warp = __shfl_sync(0xffffffffu, tid >> 5, 0), lane = tid & 31;
    const int cta = blockIdx.x;
    constexpr int grid = NCTAS;
    const int g = lane >> 2, j = lane & 3;

    TS(0);
    if (warp == 4 && cta < NQ_CTAS) {
        asm volatile("{\n.reg .pred p;\nelect.sync _|p, 0xffffffff;\n"
                     "@p mbarrier.init.shared::cta.b64 [%0], 1;\n"
                     "@p fence.mbarrier_init.release.cluster;\n"
                     "@p mbarrier.arrive.expect_tx.shared::cta.b64 _, [%0], 61440;\n}" :: "r"(sb + BAR_WQ) : "memory");
#pragma unroll
        for (int i = 0; i < 4; i++) request_box(sb + SM_WQ + i * 15360, &p.wq, cta * 48, i * 160, sb + BAR_WQ);
    }
    if (tid == 160) {
#pragma unroll
        for (int w = 0; w < NWORK; w++) mbar_init(sb + BAR_KV + w * 8, 1);
        mbar_init(sb + BAR_W, 1);
#pragma unroll
        for (int w = 0; w < 8; w++) mbar_init(sb + BAR_G + w * 8, 1);
        asm volatile("fence.mbarrier_init.release.cluster;" ::: "memory");
    }
    __syncthreads();
    const uint32_t role = p.role[cta];
    const bool is_l = role >> 14 == ROLE_L, is_f = role >> 14 == ROLE_F, is_g = role >> 14 == ROLE_G;
    const int fidx = (role >> 7) & 127, eidx = role & 127;
    if (warp == NAUX + NWORK + 1) {
        uint32_t t = now_clk() + 2 * WO_AT_NS;
        const uint64_t pol = evict_first();
        if (lane == 0) mbar_expect_tx(sb + BAR_W, is_l ? 49152 : 61440);
#pragma unroll 1
        for (int r = 0; r < DH; r += 48, t += 2 * WO_GAP_NS) {
            wait_clk(t);
#pragma unroll 1
            for (int i = 0; i < (is_l ? 4 : 5); i++)
                request_box(sb + SM_A + i * 12288 + r * 64, &p.wo, is_l ? fidx * 32 : (eidx & 3) * 160 + i * 32,
                            (is_l ? 28 + i : eidx >> 2) * DH + r, sb + BAR_W, pol);
        }
        if (!is_f && !is_g) return;
        if (lane < 8) mbar_expect_tx(sb + BAR_G + lane * 8, is_f ? 10240 : 6144);
        asm volatile("bar.sync 9, 288;" ::: "memory");
        asm volatile("fence.proxy.async.shared::cta;" ::: "memory");
#pragma unroll 1
        for (int it = 0; it < SPIN_MAX; it++) {
            t = ld_relaxed_u32(g_st.tstart);
            if (__all_sync(0xffffffffu, t != 0)) break;
            __nanosleep(400);
        }
#pragma unroll 1
        for (int it = 0; it < SPIN_MAX; it++) if (__all_sync(0xffffffffu, t - now_ns() > 2 * TRIG_NS)) break;
        TSW(11);
        t = now_clk() + (is_f ? 0 : DOFF);
#pragma unroll 1
        for (int i = 0; i < 8; i++, t += is_f ? GCLK : DCLK) {
            wait_clk(t);
            if (is_f) {
                request_box(sb + SM_G + i * 5120, &p.wg, fidx * 32, i * 80, sb + BAR_G + i * 8);
                request_box(sb + SM_G + 40960 + i * 5120, &p.wu, fidx * 32, i * 80, sb + BAR_G + i * 8);
            } else {
                request_box(sb + SM_G + i * 6144, &p.wd, fidx * 16, i * 192, sb + BAR_G + i * 8);
            }
        }
        return;
    }
    if (warp == NAUX + NWORK) {
        if (cta < NQ_CTAS) {
            wait_clk(now_clk() + 4000);
#pragma unroll
            for (int i = lane; i < STATE_V4; i += 32)
                if (cta * STATE_V4 + i < (int)(sizeof(State) / 16)) reinterpret_cast<uint4*>(&g_st)[cta * STATE_V4 + i] = make_uint4(0u, 0u, 0u, 0u);
            if (cta * 512 < X_END) {
                uint4* z = sided<uint4>(p, 0, cta * 512 + lane * 16);
                *z = make_uint4(0u, 0u, 0u, 0u);
                *other_side(z) = make_uint4(0u, 0u, 0u, 0u);
            }
            __syncwarp();
            if (lane == 0) red_release(g_cnt_z);
        }
        if (lane == 0) { TS2(2); wait_count(g_cnt_z, NQ_CTAS); TS2(29); }
        __syncwarp();
        asm volatile("bar.arrive 2, %0;" :: "n"((NWORK + 1) * 32) : "memory");
        uint32_t rtt[2] = {0xffffffffu, 0xffffffffu};
        if (lane == 0) {
#pragma unroll 1
            for (int r = 0; r < 12; r++) {
                int v = 0;
                uint32_t t1 = 0;
                unsigned* ctr = sided<unsigned>(p, r & 1, X_P + ((cta * 32 + (r >> 1) * 768) & 4095));
                pin(ctr);
                const uint32_t t0 = now_clk();
                draw(v, ctr, true);
                asm volatile("{\n.reg .pred q;\nsetp.ge.s32 q, %1, 0;\n@q mov.u32 %0, %%clock;\n}" : "+r"(t1) : "r"(v) : "memory");
                if (r & 1) rtt[1] = min(rtt[1], t1 - t0); else rtt[0] = min(rtt[0], t1 - t0);
            }
            sts32f(sb + SM_SIDE, __int_as_float(rtt[1] < rtt[0]));
        }
        const int side = __shfl_sync(0xffffffffu, rtt[1] < rtt[0], 0);
        fin_arrive<3>();
        int job = cta;
        auto sum_rows = [&](int row_end) {
#pragma unroll 1
            for (; job < 8 * min(row_end, RED0); job += NCTAS) {
                const int row = job >> 3, grp = (job & 7) * 8 + (lane & 7);
                if (lane == 0) wait_row(p, side, row, UPB);
                __syncwarp();
                const float4* src = &g_ring[row % RING][lane >> 3][grp];
                float sx = 0.f, sy = 0.f, sz = 0.f;
#pragma unroll 1
                for (int i = 0; i < 2; i++, src += 64 * 64) {
                    float4 v[16];
#pragma unroll 1
                    for (int it = 0; it < SPIN_MAX; it++) {
                        bool ok = true;
#pragma unroll
                        for (int k = 0; k < 16; k++) v[k] = ld_relaxed_b128(src + k * 4 * 64);
#pragma unroll
                        for (int k = 0; k < 16; k++) ok &= v[k].w == (float)(row + 1);
                        if (__all_sync(0xffffffffu, ok)) break;
                    }
#pragma unroll
                    for (int k = 0; k < 16; k++) { sx += v[k].x; sy += v[k].y; sz += v[k].z; }
                }
#pragma unroll
                for (int o = 8; o < 32; o <<= 1) {
                    sx += __shfl_xor_sync(0xffffffffu, sx, o); sy += __shfl_xor_sync(0xffffffffu, sy, o); sz += __shfl_xor_sync(0xffffffffu, sz, o);
                }
                if (lane < 8) st_relaxed_b128(&g_st.oacc[row][grp], sx, sy, sz, UPB);
            }
        };
        {
            uint32_t wr[10];
            float wsum = 0.f;
#pragma unroll
            for (int i = 0; i < 10; i++) {
                const int w = 4 * lane + 128 * (i >> 2) + (i & 3) - (i >= 8 ? 2 * lane : 0);
                wr[i] = *reinterpret_cast<const uint32_t*>(p.wr + (w >> 4) * 32 + (w & 3) * 8 + ((w >> 1) & 6));
                wsum += lo_f(wr[i]) + hi_f(wr[i]);
            }
            wsum = warp_sum(wsum);
            const int lb = lane >> 3, lc = lane & 7;
            uint32_t ypart = sb + SM_RED2 + (lb >> 1) * 160 + lc * 16 + (lb & 1) * 8;
            __nv_bfloat16* out = p.out + lb * DM + fidx * 16 + lc;
            float nmean_l = 0.f, rden_l = 0.f, sig_l = 0.f;
#pragma unroll 1
            for (int b = 0; b < NB; b++) {
                const uint32_t hx = X_H + b * (DM * 2), hrow = sb + SM_X + b * HPITCH;
                const uint4 *src0 = sided<uint4>(p, side, hx + 16 * lane), *src1 = sided<uint4>(p, side, hx + 512 + 16 * lane);
                const uint2* src2 = sided<uint2>(p, side, hx + 1024 + 8 * lane);
                sum_rows((b + 1) * NH);
                if (!is_l && !is_f && !is_g) continue;
                pin(src0); pin(src1); pin(src2); pin(ypart); pin(out);
                if (lane == 0) wait_row(p, side, b * NH + (is_l ? 28 : NH - 1), is_l ? 1 : 100);
                __syncwarp();
                if (is_l) {
                    const int col = fidx * 32 + 2 * (lane & 15);
                    uint32_t lpart = sb + SM_RED + (lane & 15) * 8;
                    const uint32_t xv = *reinterpret_cast<const uint32_t*>(p.x + b * DM + col);
                    uint32_t* hdst = sided<uint32_t>(p, lane >> 4, hx + 4 * ((col >> 5) * 16 + (col & 6) * 2 + ((col >> 3) & 3)));
                    float4 early;
#pragma unroll 1
                    for (int it = 0; it < SPIN_MAX; it++) {
                        early = ld_relaxed_f4(&g_st.attn[b][col]);
                        if (__all_sync(0xffffffffu, early.y == NE_CTAS / 4 && early.w == NE_CTAS / 4)) break;
                    }
                    if (lane == 0) TS2(23);
                    float x0 = lo_f(xv), x1 = hi_f(xv);
                    pin(hdst); pin(lpart); pin(x0); pin(x1);
                    fin_sync<4>();
                    CK(2, lds32(sb + SM_RED));
                    const float2 late = sum8(lpart);
                    const uint32_t nh = pack_bf16(-x0 - bf16r(early.x + late.x), -x1 - bf16r(early.z + late.y));
                    st_relaxed(hdst, nh ? nh : 0x80008000u);
                    CK(3, 0);
                    if (lane == 0) TS2(15);
                    fin_sync<5>();
                    continue;
                }
                uint4 h0, h1;
                uint2 h2;
                float mm[5][4];
#pragma unroll 1
                for (int it = 0;; it++) {
                    h0 = ld_relaxed_v4(src0);
                    h1 = ld_relaxed_v4(src1);
                    h2 = ld_relaxed_v2(src2);
                    asm volatile("st.shared.v4.u32 [%0], {%1,%2,%3,%4};" :: "r"(hrow + lane * 16), "r"(h0.x), "r"(h0.y), "r"(h0.z), "r"(h0.w) : "memory");
                    asm volatile("st.shared.v4.u32 [%0], {%1,%2,%3,%4};" :: "r"(hrow + 512 + lane * 16), "r"(h1.x), "r"(h1.y), "r"(h1.z), "r"(h1.w) : "memory");
                    asm volatile("st.shared.v2.u32 [%0], {%1,%2};" :: "r"(hrow + 1024 + lane * 8), "r"(h2.x), "r"(h2.y) : "memory");
                    const uint32_t w[10] = {h0.x, h0.y, h0.z, h0.w, h1.x, h1.y, h1.z, h1.w, h2.x, h2.y};
#pragma unroll
                    for (int i = 0; i < 5; i++) {
                        const uint32_t a[4] = {w[2 * i], 0x3f803f80u, w[2 * i + 1], 0x3f803f80u};
                        mm[i][0] = mm[i][1] = mm[i][2] = mm[i][3] = 0.f;
                        mma16816(mm[i], a, w[2 * i], w[2 * i + 1]);
                    }
                    const uint32_t lo = min(min(min(h0.x, h0.y), min(h0.z, h0.w)), min(min(min(h1.x, h1.y), min(h1.z, h1.w)), min(h2.x, h2.y)));
                    const bool ok = __all_sync(0xffffffffu, lo != 0 || it == SPIN_MAX);
                    asm volatile("{\n.reg .pred p;\nsetp.ne.u32 p, %0, 0;\n@p bar.arrive 7, 160;\n@p bar.arrive 8, 160;\n}" :: "r"((uint32_t)ok) : "memory");
                    if (ok) break;
                }
                CK(4, h0.x);
                if (lane == 0) TS2(is_f ? 12 : 17);
                const uint32_t hw[10] = {h0.x, h0.y, h0.z, h0.w, h1.x, h1.y, h1.z, h1.w, h2.x, h2.y};
                float m1 = ((mm[0][2] + mm[1][2]) + (mm[2][2] + mm[3][2])) + ((mm[0][3] + mm[1][3]) + (mm[2][3] + mm[3][3])) + (mm[4][2] + mm[4][3]);
                float m2 = (g & 1) ? ((mm[0][1] + mm[1][1]) + (mm[2][1] + mm[3][1])) + mm[4][1] : ((mm[0][0] + mm[1][0]) + (mm[2][0] + mm[3][0])) + mm[4][0];
                m2 += __shfl_xor_sync(0xffffffffu, m2, 4);
                m1 = (m1 + __shfl_xor_sync(0xffffffffu, m1, 1)) + (__shfl_xor_sync(0xffffffffu, m1, 2) + __shfl_xor_sync(0xffffffffu, m1, 3));
                m2 = (__shfl_sync(0xffffffffu, m2, 0) + __shfl_sync(0xffffffffu, m2, 9)) + (__shfl_sync(0xffffffffu, m2, 18) + __shfl_sync(0xffffffffu, m2, 27));
                m1 *= 1.0f / DM;
                const float nmean = bf16r(m1);
                const float var = bf16r(fmaxf(fmaf(-m1, m1, m2 * (1.0f / DM)), 0.f));
                const float vare = bf16r(var + 1e-5f);
                if (is_f) {
                    sts64f(sb + SM_MOM + b * 8, nmean, vare, lane == 0);
                    CK(5, 0);
                    fin_arrive<4>();
                } else {
                    const float rden = rcp_approx(bf16r(sqrt_approx(vare)));
                    if (lb == b) { nmean_l = nmean; rden_l = rden; }
                    __syncwarp();
                    const float2 hw2 = lds64f(sb + SM_X + lb * HPITCH + ((fidx >> 1) * 16 + (lc & 6) * 2 + (fidx & 1) * 2) * 4);
                    const float nh0 = (lc & 1) ? hi_f(__float_as_uint(hw2.x)) : lo_f(__float_as_uint(hw2.x));
                    const float nh1 = (lc & 1) ? hi_f(__float_as_uint(hw2.y)) : lo_f(__float_as_uint(hw2.y));
                    float rr = 0.f;
#pragma unroll
                    for (int i = 0; i < 10; i++) rr = fmaf(lo_f(hw[i]), lo_f(wr[i]), fmaf(hi_f(hw[i]), hi_f(wr[i]), rr));
                    const float sig = bf16r(sigmoid_approx(bf16r((nmean * wsum - warp_sum(rr)) * rden)));
                    if (lb == b) sig_l = sig;
                    const float ln0 = bf16r(bf16r(nmean_l - nh0) * rden_l), ln1 = bf16r(bf16r(nmean_l - nh1) * rden_l);
                    fin_sync<6>(after(after(after(288, sig_l), ln0), ln1));
                    CK(10, lds32(ypart));
                    float2 t[16];
#pragma unroll
                    for (int i = 0; i < 16; i++) t[i] = lds64f(ypart + i * YPITCH);
#pragma unroll
                    for (int o = 1; o < 16; o <<= 1) {
#pragma unroll
                        for (int i = 0; i < 16; i += 2 * o) { t[i].x += t[i + o].x; t[i].y += t[i + o].y; }
                    }
                    const uint32_t o0 = pack_bf16(bf16r(ln0 - bf16r(bf16r(t[0].x) * sig_l)) - nh0, 0.f);
                    const uint32_t o1 = pack_bf16(bf16r(ln1 - bf16r(bf16r(t[0].y) * sig_l)) - nh1, 0.f);
                    asm volatile("{\n.reg .pred p;\nsetp.eq.u32 p, %3, 3;\n@p st.global.u16 [%0], %1;\n@p st.global.u16 [%0 + 16], %2;\n}"
                                 :: "l"(out), "h"((unsigned short)o0), "h"((unsigned short)o1), "r"(b) : "memory");
                    if (b == NB - 1) return;
                    CK(11, 0);
                    if (lane == 0) TS2(13);
                }
                if (b < NB - 1) fin_sync<5>();
            }
            if (is_f && fidx == 0 && lane == 0) { g_work[0] = 0; g_cnt_z[0] = 0; }
        }
        return;
    }
    if (warp >= NAUX) {
        const int wk = warp - NAUX;
        const uint32_t bar = sb + BAR_KV + wk * 8;
        const uint32_t buf = sb + SM_KV + wk * TILE_BYTES;
        const uint64_t pol = evict_first();
        const int nstatic = NWORK * grid;
        constexpr int POOL0 = NUNITS - NPOOL;
        int uk = wk * grid + cta;
        wait_clk(now_clk() + 2 * (K0_DELAY_NS + wk * K0_STEP_NS));
        request_tile(buf, &p.k, uk, bar, pol);
        uint32_t koff[3], voff[3];
        {
            const int r = lane & 7, hf = (lane >> 3) & 1;
            const int kkey = hf ? 8 + (r ^ 1) : r;
            const int vh = lane >> 4;
            const int vkey = ((r & 1) ? 8 : 0) + (vh ? (r ^ 1) : r);
#pragma unroll
            for (int b = 0; b < 3; b++) {
                const int rk = 3 * kkey + b, rv = 3 * vkey + b;
                koff[b] = buf + rk * 128 + (((lane >> 4) ^ (rk & 7)) << 4);
                voff[b] = buf + rv * 128 + ((hf ^ (rv & 7)) << 4);
            }
        }
        uint32_t phase = 0;
        uint4 qf[6];
        auto load_q = [&](int u) {
            const uint32_t* q = &g_early[row_of(u)].q[j * 4];
#pragma unroll
            for (int i = 0; i < 6; i++) qf[i] = ld_relaxed_v4(q + i * 16);
        };
        load_q(uk);
        int uq[LAG];
        uint32_t sq[LAG];
#pragma unroll
        for (int i = 0; i < LAG; i++) { uq[i] = -1; sq[i] = 0; }
        uint4 mv = make_uint4(0u, 0u, 0u, 0u);
        uint32_t svp = 0;
        float freed = UPB;
        while (true) {
            const int uv = uq[0];
            uint32_t sv = sq[0];
#pragma unroll
            for (int i = 0; i + 1 < LAG; i++) { uq[i] = uq[i + 1]; sq[i] = sq[i + 1]; }
            uq[LAG - 1] = uk;
            if (uk < NUNITS) {
                PH(7);
#pragma unroll 1
                for (int it = 0; it < SPIN_MAX; it++) {
                    uint32_t lo = 0xffffffffu;
#pragma unroll
                    for (int i = 0; i < 6; i++) lo = min(min(lo, min(qf[i].x, qf[i].y)), min(qf[i].z, qf[i].w));
                    if (__all_sync(0xffffffffu, lo != 0)) break;
                    __nanosleep(250);
                    load_q(uk);
                }
                mbar_wait(bar, phase); phase ^= 1;
                PH(0); ARR();
                TSI(0, 16);
                float acc[2][4][4] = {};
#pragma unroll
                for (int ks = 0; ks < 12; ks++) {
                    const uint4 qq = qf[ks >> 1];
                    const uint32_t b0 = (ks & 1) ? qq.z : qq.x, b1 = (ks & 1) ? qq.w : qq.y;
#pragma unroll
                    for (int mt = 0; mt < 4; mt++) {
                        uint32_t a[4];
                        ldsm4(a, (koff[ks >> 2] ^ ((ks & 3) << 5)) + mt * 6144);
                        mma16816(acc[ks & 1][mt], a, b0, b1);
                    }
                }
                PH(1);
                TSI(0, 19);
                if (uv < NUNITS) request_tile(buf, uv >= 0 ? &p.v : &p.k, uv >= 0 ? uv : uk + nstatic, bar, pol);
                const float sa = sel4(j, acc[0][0][0], acc[0][1][0], acc[0][2][0], acc[0][3][0]) + sel4(j, acc[1][0][0], acc[1][1][0], acc[1][2][0], acc[1][3][0]);
                const float sc = sel4(j, acc[0][0][2], acc[0][1][2], acc[0][2][2], acc[0][3][2]) + sel4(j, acc[1][0][2], acc[1][1][2], acc[1][2][2], acc[1][3][2]);
                const uint32_t raw = pack_bf16(sa, sc);
                const float scale = -0.07216878364870322f;
                const uint32_t sk = pack_bf16(lo_f(raw) * scale, hi_f(raw) * scale);
                sq[LAG - 1] = sk;
                if (uk >= POOL0) st_relaxed(&g_st.score[uk - POOL0][lane], sk ? sk : 0x80008000u);
                int a = (int)(sk << 16), b = (int)(sk & 0xffff0000u);
                a ^= (a >> 31) & 0x7fff0000; b ^= (b >> 31) & 0x7fff0000;
                const int mx = __reduce_max_sync(0xffffffffu, max(a, b));
                if (lane == 0) st_relaxed(&g_early[row_of(uk)].umax[pos_of(uk)], (uint32_t)mx | 1u);
            }
            if (uv < 0) {
                uk += nstatic;
                load_q(uk);
                continue;
            }
            if (uv >= NUNITS) break;
            static_assert((LAG + 1) * (NWORK * NCTAS / 2) >= (UPB << NWL), "the wait for the row maxima could deadlock");
            const int bh = row_of(uv);
#pragma unroll 1
            for (int it = 0; it < SPIN_MAX; it++) {
                if (__all_sync(0xffffffffu, (mv.x & mv.y & mv.z & mv.w & 1u) && (uv < POOL0 || svp != 0) && freed == UPB)) break;
                mv = ld_relaxed_v4(&g_early[bh].umax[lane * 4]);
                if (bh >= RING && bh < RED0) freed = __uint_as_float(ld_relaxed_u32(&g_st.oacc[bh - RING][(lane & 7) * 8].w));
                if (uv >= POOL0) svp = ld_relaxed_u32(&g_st.score[uv - POOL0][lane]);
            }
            if (uv >= POOL0) sv = svp;
            PH(2);
            int un = NUNITS, vn = 0;
            draw(un, g_work, uk < NUNITS && lane == 0);
            int mx = __reduce_max_sync(0xffffffffu, max(max((int)mv.x, (int)mv.y), max((int)mv.z, (int)mv.w))) & 0xffff0000;
            mx ^= (mx >> 31) & 0x7fff0000;
            const float m = __int_as_float(mx);
            const float l2e = 1.4426950408889634f;
            const uint32_t pp = pack_bf16(exp2f((lo_f(sv) - m) * l2e), exp2f((hi_f(sv) - m) * l2e));
            uint32_t pb[8];
#pragma unroll
            for (int t = 0; t < 4; t++) {
                pb[2 * t] = __shfl_sync(0xffffffffu, pp, 8 * j + t);
                pb[2 * t + 1] = __shfl_sync(0xffffffffu, pp, 8 * j + 4 + t);
            }
            float lacc[4] = {};
            const uint32_t ones[4] = {0x3f803f80u, 0x3f803f80u, 0x3f803f80u, 0x3f803f80u};
#pragma unroll
            for (int t = 0; t < 4; t++) mma16816(lacc, ones, pb[2 * t], pb[2 * t + 1]);
            if (uv < nstatic) {
                asm volatile("bar.sync 2, %0;" :: "n"((NWORK + 1) * 32) : "memory");
                TSW(3);
            }
            const int grp = 16 * j + 4 * (g & 1) + (g >> 1);
            float4* dst = bh < RED0 ? &g_ring[bh % RING][pos_of(uv)][grp] : oacc_at(p, lds32(sb + SM_SIDE) ^ 1, bh, grp);
            float4* dst2 = other_side(dst);
            float2* ldst = lsum_at(p, lane & 1, bh);
            if (bh >= SROW0 && lane < 2) red_f2(&ldst->x, lacc[0], 1.f);
            float tag = bh < RED0 ? (float)(bh + 1) : 1.f;
            un = __shfl_sync(0xffffffffu, un, 0) + (LAG + 1) * nstatic;
            uint32_t pooled = uq[0] >= POOL0 && lane == 0;
            pin(dst); pin(dst2); pin(ldst); pin(tag); pin(voff[0]); pin(voff[1]); pin(voff[2]); pin(pooled);
            PH(3);
            LT(1);
            mbar_wait(bar, phase); phase ^= 1;
            PH(4); ARR();
            LT(2);
            draw(vn, g_st.pool, pooled);
            float acc[12][4] = {};
#pragma unroll
            for (int t = 0; t < 4; t++) {
#pragma unroll
                for (int mt = 0; mt < 12; mt++) {
                    uint32_t a[4];
                    ldsm4t(a, (voff[mt >> 2] ^ ((mt & 3) << 5)) + t * 6144);
                    mma16816(acc[mt], a, pb[2 * t], pb[2 * t + 1]);
                }
            }
            PH(5);
            if (lane == 0) PROG(un);
            if (un < NUNITS) request_tile(buf, &p.k, un, bar, pol);
            float o[6];
#pragma unroll
            for (int e = 0; e < 6; e++) {
                const int q = e % 3, c = (e / 3) * 2;
                o[e] = sel4(j, acc[q][c], acc[3 + q][c], acc[6 + q][c], acc[9 + q][c]);
            }
            if (bh >= SROW0) {
                red_f4(&dst->x, o[0], o[1], o[2], tag);
                red_f4(&dst[16].x, o[3], o[4], o[5], tag);
                red_f4(&dst2->x, o[0], o[1], o[2], tag);
                red_f4(&dst2[16].x, o[3], o[4], o[5], tag);
            } else {
                if (bh >= RED0) {
                    red_f4(&dst->x, o[0], o[1], o[2], tag);
                    red_f4(&dst[8].x, o[3], o[4], o[5], tag);
                } else {
                    st_relaxed_b128(dst, o[0], o[1], o[2], tag);
                    st_relaxed_b128(dst + 8, o[3], o[4], o[5], tag);
                }
                if (lane == 0) red_f2(&ldst->x, lacc[0], 1.f);
            }
            if (uq[0] >= POOL0) {
                vn = __shfl_sync(0xffffffffu, vn, 0);
                uq[0] = POOL0 + vn;
                constexpr int LAST = NUNITS - (UPB << NWL);
                static_assert(LAST >= POOL0, "");
                if (uq[0] >= LAST && uq[0] < NUNITS) uq[0] = LAST + (((uq[0] & (UPB - 1)) << NWL) | ((uq[0] - LAST) / UPB));
                if (vn == VTRIG && lane == 0) st_relaxed(g_st.tstart, (now_ns() + TRIG_NS) | 1u);
            }
            if (un < NUNITS) load_q(un);
            PH(6);
            if (uq[0] >= NUNITS && un >= NUNITS) break;
            uk = un;
            if (uq[0] < NUNITS) {
                const int nb = row_of(uq[0]);
                mv = ld_relaxed_v4(&g_early[nb].umax[lane * 4]);
                freed = nb >= RING && nb < RED0 ? __uint_as_float(ld_relaxed_u32(&g_st.oacc[nb - RING][(lane & 7) * 8].w)) : UPB;
                if (uq[0] >= POOL0) svp = ld_relaxed_u32(&g_st.score[uq[0] - POOL0][lane]);
                if (un >= NUNITS) {
                    request_tile(buf, &p.v, uq[0], bar, pol);
                    LT(0);
                }
            }
        }
        if (is_f) asm volatile("bar.arrive 10, %0;" :: "n"((NAUX + NWORK) * 32) : "memory");
        return;
    }

    __nv_bfloat16* xs = reinterpret_cast<__nv_bfloat16*>(smem + SM_X);
    float* red = reinterpret_cast<float*>(smem + SM_RED);
    const int frow = (lane & 7) + ((lane >> 4) << 3), fcol = (lane >> 3) & 1;
    if (cta < NQ_CTAS) {
        uint2 xr[5];
        if (warp < NB) {
#pragma unroll
            for (int i = 0; i < 5; i++) xr[i] = *reinterpret_cast<const uint2*>(p.x + warp * DM + i * 128 + lane * 4);
        }
        TS(26);
        if (warp < NB) {
            float v[20];
#pragma unroll
            for (int i = 0; i < 5; i++) {
                v[4 * i] = lo_f(xr[i].x); v[4 * i + 1] = hi_f(xr[i].x); v[4 * i + 2] = lo_f(xr[i].y); v[4 * i + 3] = hi_f(xr[i].y);
            }
            layernorm20(v);
#pragma unroll
            for (int i = 0; i < 5; i++)
                *reinterpret_cast<uint2*>(xs + warp * XPITCH + i * 128 + lane * 4) =
                    make_uint2(pack_bf16(v[4 * i], v[4 * i + 1]), pack_bf16(v[4 * i + 2], v[4 * i + 3]));
        }
        TS(27);
        aux_sync();
        mbar_wait(sb + BAR_WQ, 0);
        TS(1);
        const uint32_t xfrag = sb + SM_X + ((g & 3) * XPITCH + 2 * j) * 2;
        float acc[3][4] = {};
#pragma unroll
        for (int s = 0; s < 5; s++) {
            const int ks = warp * 5 + s;
            const uint32_t b0 = lds32(xfrag + ks * 32), b1 = lds32(xfrag + ks * 32 + 16);
            const int row = ks * 16 + frow;
#pragma unroll
            for (int mt = 0; mt < 3; mt++) {
                uint32_t a[4];
                ldsm4t(a, sb + SM_WQ + (row * 6 + 2 * mt + fcol) * 16);
                mma16816(acc[mt], a, b0, b1);
            }
        }
        if (j < 2) {
#pragma unroll
            for (int mt = 0; mt < 3; mt++) {
                *reinterpret_cast<float2*>(red + (warp * 48 + mt * 16 + g) * 4 + 2 * j) = make_float2(acc[mt][0], acc[mt][1]);
                *reinterpret_cast<float2*>(red + (warp * 48 + mt * 16 + 8 + g) * 4 + 2 * j) = make_float2(acc[mt][2], acc[mt][3]);
            }
        }
        aux_sync();
        if (tid < 96) {
            const int b = tid & 3, cp = tid >> 2;
            float s0 = 0.f, s1 = 0.f;
#pragma unroll
            for (int w = 0; w < 8; w++) { s0 += red[(w * 48 + 2 * cp) * 4 + b]; s1 += red[(w * 48 + 2 * cp + 1) * 4 + b]; }
            const int h = cta >> 2, d = (cta & 3) * 48 + 2 * cp;
            const int ch = d >> 3, jj = (d & 7) >> 1;
            st_relaxed(&g_early[b * NH + h].q[(ch >> 2) * 16 + jj * 4 + (ch & 3)], pack_neg(s0, s1));
        }
        TS(28);
    }
    if (tid < 160) *reinterpret_cast<uint2*>(smem + SM_X + 4 * HPITCH + tid * 8) = make_uint2(0x3f803f80u, 0x3f803f80u);
    fin_sync<3>();
    const int side = lds32(sb + SM_SIDE);
    mbar_wait(sb + BAR_W, 0);
    TS(7);
    uint32_t part = sb + SM_RED + (warp * 32 + 8 * j + g) * 4;

#pragma unroll 1
    for (int b = 0; b < NB; b++) {
        if (b == NB - 1 && (is_f || is_g)) asm volatile("bar.arrive 9, 288;" ::: "memory");
        if (is_l) {
            uint32_t a[6][2][4];
#pragma unroll
            for (int s = 0; s < 6; s++) {
                const int row = warp * 96 + (s < 4 ? 48 * (s >> 1) + 8 * (s & 1) + 16 * (lane & 1) + (lane & 6) + (lane >> 4) : 48 * (s - 4) + 32 + frow);
#pragma unroll
                for (int mt = 0; mt < 2; mt++) ldsm4t(a[s][mt], sb + SM_A + (row * 4 + ((2 * mt + fcol) ^ ((row >> 1) & 3))) * 16);
            }
            const int bh = b * NH + 28 + (warp >> 1);
            const float4* osrc = oacc_at(p, side, bh, (warp & 1) * 32 + lane);
            const float2* lsrc = lsum_at(p, side, bh);
            if (lane == 0) wait_row_o(p, side, bh, 1);
            __syncwarp();
            float2 lv;
#pragma unroll 1
            for (int it = 0; it < SPIN_MAX; it++) {
                lv = ld_relaxed_f2(lsrc);
                if (__all_sync(0xffffffffu, lv.y == UPB)) break;
            }
            if (warp == 7) TSW(25);
            if (fidx == 0 && lane < 28)
                reinterpret_cast<uint4*>(&g_early[bh])[(warp & 1) * 28 + lane] = make_uint4(0u, 0u, 0u, 0u);
            float rl = rcp_approx(lv.x);
            float4 ov;
            pin(osrc); pin(rl); hold(part);
#pragma unroll 1
            for (int it = 0;; it++) {
                ov = ld_relaxed_f4(osrc);
                if (__all_sync(0xffffffffu, ov.w == UPB || it == SPIN_MAX)) break;
            }
            CK(0, __float_as_uint(ov.x));
            const uint32_t xy = pack_bf16(ov.x * rl, ov.y * rl);
            const float z = ov.z * rl;
            float acc[2][2][4] = {};
#pragma unroll
            for (int s = 0; s < 6; s++) {
                uint32_t bf[2];
#pragma unroll
                for (int kh = 0; kh < 2; kh++) {
                    if (s < 4) bf[kh] = __shfl_sync(0xffffffffu, xy, 8 * s + 4 * kh + j);
                    else bf[kh] = pack_bf16(__shfl_sync(0xffffffffu, z, 16 * (s - 4) + 8 * kh + j), __shfl_sync(0xffffffffu, z, 16 * (s - 4) + 8 * kh + 4 + j));
                }
#pragma unroll
                for (int mt = 0; mt < 2; mt++) mma16816(acc[mt][s & 1], a[s][mt], bf[0], bf[1]);
            }
            sts32f(part, sel4(j, acc[0][0][0] + acc[0][1][0], acc[0][0][2] + acc[0][1][2], acc[1][0][0] + acc[1][1][0], acc[1][0][2] + acc[1][1][2]));
            CK(1, 0);
            fin_arrive<4>();
            if (warp == 7) TSW(30);
            if (warp == 5) TSW(31);
            fin_sync<5>();
            continue;
        }
        {
            const int bh = b * NH + (eidx >> 2);
            if (tid == 0) wait_row_o(p, side, bh, UPB);
            aux_sync();
            if (warp < 5) {
                uint32_t ob[12][2];
                load_o<4>(p, ob, bh, 0, j);
                float acc[2][2][4] = {};
#pragma unroll
                for (int ks = 0; ks < 12; ks++) {
                    const int row = ks * 16 + frow;
#pragma unroll
                    for (int mt = 0; mt < 2; mt++) {
                        uint32_t a[4];
                        ldsm4t(a, sb + SM_A + warp * 12288 + (row * 4 + ((2 * mt + fcol) ^ ((row >> 1) & 3))) * 16);
                        mma16816(acc[mt][ks & 1], a, ob[ks][0], ob[ks][1]);
                    }
                }
                red_f2(&g_st.attn[b][(eidx & 3) * 160 + warp * 32 + 8 * j + g].x,
                       sel4(j, acc[0][0][0] + acc[0][1][0], acc[0][0][2] + acc[0][1][2], acc[1][0][0] + acc[1][1][0], acc[1][0][2] + acc[1][1][2]), 1.f);
                TS(8);
            } else if (warp > 5 && (eidx & 3) == 0 && tid - 192 < 56) {
                reinterpret_cast<uint4*>(&g_early[bh])[tid - 192] = make_uint4(0u, 0u, 0u, 0u);
            }
        }
        if (is_f) {
            const int kq = warp >> 1, tp = warp & 1;
            uint32_t hfrag = sb + SM_X + min(g, 4) * HPITCH + (kq * 80 + 4 * j) * 4;
            uint32_t fpart = sb + SM_RED + 2 * j * FPITCH + warp * 128 + g * 16;
            uint32_t dsum = sb + SM_RED + (lane >> 3) * FPITCH + tp * 128 + (lane & 7) * 16, csum = sb + SM_RED + 4 * FPITCH + tp * 128 + (lane & 7) * 16;
            uint32_t mom = sb + SM_MOM + (lane >> 3) * 8;
            uint32_t* dst = sided<uint32_t>(p, side ^ 1, X_A + (2 * fidx + tp) * 128 + (lane ^ 2 * tp) * 4);
            uint32_t* dst2 = other_side(dst);
            uint32_t wfrag = sb + SM_G + fcol * 40960 + ((kq * 160 + frow) * 4 + (2 * tp ^ ((frow >> 1) & 3))) * 16;
            hold(wfrag); hold(fpart); hold(hfrag); hold(dsum); hold(csum); hold(mom); hold(dst); hold(dst2);
            uint4 hv[5] = {};
#pragma unroll
            for (int s = 0; s < 5; s++) lds128_if(hv[s], hfrag + s * 64, g != b);
            if (b == NB - 1) asm volatile("bar.sync 10, %0;" :: "n"((NAUX + NWORK) * 32) : "memory");
            uint32_t ga[10][2][4];
#pragma unroll
            for (int s = 0; s < 10; s++) {
                if (s % 5 == 0 && b == NB - 1) mbar_wait(sb + BAR_G + (kq * 2 + s / 5) * 8, 0);
#pragma unroll
                for (int t = 0; t < 2; t++) ldsm4t(ga[s][t], (wfrag ^ (t << 4)) + s * 1024);
            }
            if (warp == NAUX - 1) TSW(9);
            uint32_t dep = 0;
#pragma unroll
            for (int s = 0; s < 5; s++) dep ^= ga[s][0][0] ^ ga[s][1][0];
            h_sync(warp + (dep & (side >> 1)));
#pragma unroll
            for (int s = 0; s < 5; s++) lds128_if(hv[s], hfrag + s * 64, g == b);
            float acc[2][2][4] = {};
#pragma unroll
            for (int s = 0; s < 5; s++) {
#pragma unroll
                for (int t = 0; t < 2; t++) mma16816(acc[t][0], ga[2 * s][t], hv[s].x, hv[s].y);
#pragma unroll
                for (int t = 0; t < 2; t++) mma16816(acc[t][1], ga[2 * s + 1][t], hv[s].z, hv[s].w);
            }
#pragma unroll
            for (int e = 0; e < 2; e++)
                sts128f(fpart + e * FPITCH, acc[0][0][e] + acc[0][1][e], acc[0][0][2 + e] + acc[0][1][2 + e],
                        acc[1][0][e] + acc[1][1][e], acc[1][0][2 + e] + acc[1][1][2 + e], 2 * j + e < 5);
            CK(5, 0);
            if (warp < 2) {
                fin_sync<4>();
                CK(6, lds32(dsum));
                float2 m = lds64f(mom);
                m.y = rcp_approx(bf16r(sqrt_approx(m.y)));
                const float4 d = sum4x4(dsum), cs = sum4x4(csum);
                const float g0 = bf16r(fmaf(m.x, cs.x, -d.x) * m.y), g1 = bf16r(fmaf(m.x, cs.z, -d.z) * m.y);
                const float u0 = bf16r(fmaf(m.x, cs.y, -d.y) * m.y), u1 = bf16r(fmaf(m.x, cs.w, -d.w) * m.y);
                const uint32_t av = pack_neg(bf16r(g0 * sigmoid_approx(g0)) * u0, bf16r(g1 * sigmoid_approx(g1)) * u1);
                asm volatile("{\n.reg .pred p;\nsetp.eq.u32 p, %3, 3;\n@p st.relaxed.gpu.global.u32 [%0], %2;\n@p st.relaxed.gpu.global.u32 [%1], %2;\n}"
                             :: "l"(dst), "l"(dst2), "r"(av), "r"(b) : "memory");
                CK(7, 0);
                TS(14);
            } else {
                fin_arrive<4>();
            }
        } else if (is_g) {
            const uint4* asrc[3];
#pragma unroll
            for (int q = 0; q < 3; q++) {
                asrc[q] = sided<uint4>(p, side, X_A + (warp * 12 + 4 * q + 2 * (g >> 2) + (j >> 1)) * 128 + (g & 3) * 32 + (j & 1) * 16);
                hold(asrc[q]);
            }
            uint32_t ypart = sb + SM_RED2 + (warp * 2 + (j >> 1)) * YPITCH + (j & 1) * 160 + g * 16;
            const int odd = (lane >> 2) & 1, row = (warp * 12 + odd) * 16 + (lane & 1) * 8 + (lane & 2) * 2 + 2 * odd + (lane >> 4);
            uint32_t wfrag = sb + SM_G + (row * 2 + (fcol ^ ((row >> 2) & 1))) * 16;
            hold(ypart); hold(wfrag);
            if (b == NB - 1) {
                mbar_wait(sb + BAR_G + warp * 8, 0);
                if (warp == NAUX - 1) TSW(10);
            } else {
                h_sync(warp);
            }
            uint32_t wb[3][2][2][4];
#pragma unroll
            for (int s = 0; s < 12; s++) ldsm4t(wb[s >> 2][(s >> 1) & 1][s & 1], (wfrag ^ ((s & 1) << 6)) + (s >> 1) * 1024);
            if (b == NB - 1 && warp < 6) mbar_wait(sb + BAR_G + 6 * 8, 0);
            uint4 v[3] = {};
            uint32_t mq[3];
            mq[0] = mq[1] = mq[2] = b < NB - 1;
#pragma unroll 1
            for (int it = b < NB - 1 ? SPIN_MAX : 0;; it++) {
                asm volatile("{\n.reg .pred p0, p1, p2;\nsetp.eq.u32 p0, %15, 0;\nsetp.eq.u32 p1, %16, 0;\nsetp.eq.u32 p2, %17, 0;\n"
                             "@p0 ld.relaxed.gpu.global.v4.u32 {%0,%1,%2,%3}, [%12];\n"
                             "@p1 ld.relaxed.gpu.global.v4.u32 {%4,%5,%6,%7}, [%13];\n"
                             "@p2 ld.relaxed.gpu.global.v4.u32 {%8,%9,%10,%11}, [%14];\n}"
                             : "+r"(v[0].x), "+r"(v[0].y), "+r"(v[0].z), "+r"(v[0].w), "+r"(v[1].x), "+r"(v[1].y), "+r"(v[1].z), "+r"(v[1].w),
                               "+r"(v[2].x), "+r"(v[2].y), "+r"(v[2].z), "+r"(v[2].w)
                             : "l"(asrc[0]), "l"(asrc[1]), "l"(asrc[2]), "r"(mq[0]), "r"(mq[1]), "r"(mq[2]) : "memory");
#pragma unroll
                for (int q = 0; q < 3; q++) mq[q] = min(min(v[q].x, v[q].y), min(v[q].z, v[q].w));
                const uint32_t lo = min(min(mq[0], mq[1]), mq[2]);
                if (__all_sync(0xffffffffu, lo != 0 || it == SPIN_MAX)) break;
            }
            CK(8, v[0].x);
            float acc[2][2][4] = {};
#pragma unroll
            for (int q = 0; q < 3; q++) {
#pragma unroll
                for (int pr = 0; pr < 2; pr++) {
                    mma16816(acc[pr][0], wb[q][pr][0], v[q].x, v[q].y);
                    mma16816(acc[pr][1], wb[q][pr][1], v[q].z, v[q].w);
                }
            }
            float y[4];
#pragma unroll
            for (int e = 0; e < 4; e++) y[e] = j < 2 ? acc[0][0][e] + acc[0][1][e] : acc[1][0][e] + acc[1][1][e];
            asm volatile("st.shared.v4.f32 [%0], {%1,%2,%3,%4};" :: "r"(ypart), "f"(y[0]), "f"(y[2]), "f"(y[1]), "f"(y[3]) : "memory");
            CK(9, 0);
            fin_arrive<6>();
        } else {
            continue;
        }
        if (b < NB - 1) fin_sync<5>();
    }
}

typedef CUresult (*EncodeFn)(CUtensorMap*, CUtensorMapDataType, cuuint32_t, void*, const cuuint64_t*, const cuuint64_t*,
                             const cuuint32_t*, const cuuint32_t*, CUtensorMapInterleave, CUtensorMapSwizzle,
                             CUtensorMapL2promotion, CUtensorMapFloatOOBfill);

CUtensorMap make_map(EncodeFn enc, void* ptr, uint64_t cols, uint64_t rows, uint32_t bcols, uint32_t brows,
                     CUtensorMapSwizzle sw, CUtensorMapL2promotion promo) {
    CUtensorMap m;
    const cuuint64_t dims[2] = {cols, rows};
    const cuuint64_t strides[1] = {cols * 2};
    const cuuint32_t box[2] = {bcols, brows};
    const cuuint32_t es[2] = {1, 1};
    enc(&m, CU_TENSOR_MAP_DATA_TYPE_BFLOAT16, 2, ptr, dims, strides, box, es, CU_TENSOR_MAP_INTERLEAVE_NONE, sw, promo,
        CU_TENSOR_MAP_FLOAT_OOB_FILL_NONE);
    return m;
}

}

extern "C" void kernel_launch(void* const* d_in, const int* in_sizes, int n_in, void* d_out, int out_size) {
    (void)in_sizes; (void)n_in; (void)out_size;
    static EncodeFn enc = nullptr;
    static int sms = 0;
    static void* raw = nullptr;
    if (!enc) {
        cudaDriverEntryPointQueryResult qr;
        cudaGetDriverEntryPoint("cuTensorMapEncodeTiled", (void**)&enc, cudaEnableDefault, &qr);
        int dev = 0;
        cudaGetDevice(&dev);
        cudaDeviceGetAttribute(&sms, cudaDevAttrMultiProcessorCount, dev);
        cudaGetSymbolAddress(&raw, g_raw);
        cudaFuncSetAttribute(fused_decode_kernel, cudaFuncAttributeMaxDynamicSharedMemorySize, SM_TOTAL);
    }
    if (sms < NCTAS) return;
    const CUtensorMapL2promotion WPROMO = CU_TENSOR_MAP_L2_PROMOTION_L2_128B;
    Params p;
    p.k = make_map(enc, d_in[1], 64, (uint64_t)NBH * SK * 3, 64, TILE_ROWS, CU_TENSOR_MAP_SWIZZLE_128B, CU_TENSOR_MAP_L2_PROMOTION_NONE);
    p.v = make_map(enc, d_in[2], 64, (uint64_t)NBH * SK * 3, 64, TILE_ROWS, CU_TENSOR_MAP_SWIZZLE_128B, CU_TENSOR_MAP_L2_PROMOTION_NONE);
    p.wq = make_map(enc, d_in[3], NH * DH, DM, 48, 160, CU_TENSOR_MAP_SWIZZLE_NONE, WPROMO);
    p.wo = make_map(enc, d_in[4], DM, NH * DH, 32, 48, CU_TENSOR_MAP_SWIZZLE_64B, WPROMO);
    p.wg = make_map(enc, d_in[7], FF, DM, 32, 80, CU_TENSOR_MAP_SWIZZLE_64B, WPROMO);
    p.wu = make_map(enc, d_in[8], FF, DM, 32, 80, CU_TENSOR_MAP_SWIZZLE_64B, WPROMO);
    p.wd = make_map(enc, d_in[9], DM, FF, 16, 192, CU_TENSOR_MAP_SWIZZLE_32B, WPROMO);
    p.scratch = reinterpret_cast<Scratch*>((reinterpret_cast<uintptr_t>(raw) + PAGE - 1) & ~(uintptr_t)(PAGE - 1));
    p.wq_raw = (const char*)d_in[3];
    p.x = (const __nv_bfloat16*)d_in[0];
    p.wr = (const __nv_bfloat16*)d_in[6];
    p.out = (__nv_bfloat16*)d_out;
    int n[4] = {}, ne = 0;
    for (int pair = 0; pair < NCTAS / 2; pair++) {
        const int grp = pair * 10 / 66, r = pair - (grp * 66 + 9) / 10;
        const int role = r == 0 ? ROLE_L : r < 3 ? ROLE_G : r < 5 || (r == 5 && grp % 5 % 2) ? ROLE_F : ROLE_NONE;
        for (int i = 0; i < 2; i++) p.role[2 * pair + i] = (uint16_t)(role << 14 | n[role]++ << 7 | (role == ROLE_L ? 0 : ne++));
    }
    fused_decode_kernel<<<NCTAS, NTHREADS, SM_TOTAL, cudaStreamPerThread>>>(p);
}
```
